```python
import torch

def _softmax(x, axis=-1):
    return torch.softmax(x, dim=axis)
def _gelu(x):
    return torch.nn.functional.gelu(x, approximate="tanh")
def _silu(x):
    return torch.nn.functional.silu(x)
def _sigmoid(x):
    return torch.sigmoid(x)
def _layernorm(x, axis=-1, eps=1e-5):
    m = x.mean(dim=axis, keepdim=True)
    v = x.var(dim=axis, keepdim=True, unbiased=False)
    return (x - m) / torch.sqrt(v + eps)
def _scatter_add(tgt, idx, src, axis=0):
    return tgt.clone().index_add_(axis, idx, src)
def _segment_sum(src, seg, n):
    out = torch.zeros((n,) + src.shape[1:], dtype=src.dtype)
    return out.index_add_(0, seg, src)
def _pad(x, pw):
    flat = tuple(v for pair in reversed(pw) for v in pair)
    return torch.nn.functional.pad(x, flat)

kernel_name = 'standalone__fft_conv__vision'

def setup_inputs():

    _w = (lambda a: (lambda t: t.to(torch.bfloat16) if t.is_floating_point() else t)(torch.as_tensor(a)))
    H = W = 224
    C = 96
    K = 7
    return {
        "x": _w((lambda *s: torch.randn(*s, dtype=torch.bfloat16) * 0.05)(1, H, W, C)),
        "w": _w((lambda *s: torch.randn(*s, dtype=torch.bfloat16) * 0.05)(K, K, C, C)),
    }

def reference(x, w):
    B, H, W, C = x.shape
    K = w.shape[0]
    wp = _pad(w, ((0, H - K), (0, W - K), (0, 0), (0, 0)))
    Xf = (lambda x, axes=(-2,-1): torch.fft.rfft2(x.float(), dim=axes))(x, axes=(1, 2))
    Wf = (lambda x, axes=(-2,-1): torch.fft.rfft2(x.float(), dim=axes))(wp, axes=(0, 1))
    Yf = torch.einsum('bhwi,hwio->bhwo', Xf, Wf)
    y = (lambda x, s, axes=(-2,-1): torch.fft.irfft2(x, s=s, dim=axes).to(torch.bfloat16))(Yf, (H, W), axes=(1, 2))
    return y
```

```cpp
#include <cuda_runtime.h>
#include <cuda_bf16.h>
#include <cuda.h>
#include <stdint.h>

namespace {

constexpr int NT = 196;
constexpr int NFP = 121;
constexpr int BLK = 33792;
constexpr int SLAB = 242 * 128;
constexpr int WPIECE = 19456;
constexpr float S1 = 1.1667125f;
constexpr float S2 = 1.727278f;
constexpr float WSCALE = 1.0f / (242.0f * S2 * S1 * S1 * S1 * S1);

__device__ __align__(1024) unsigned char g_S[(size_t)NT * 3 * SLAB];
__device__ __align__(1024) unsigned char g_Wt[(size_t)NFP * 73728];

struct Maps {
    CUtensorMap x6, x16, y16, s, p2l, p2s, w;
};

__device__ __forceinline__ uint32_t s2u(const void* p) { return (uint32_t)__cvta_generic_to_shared(p); }
__device__ __forceinline__ void mbar_init(uint32_t b, int c) { asm volatile("mbarrier.init.shared::cta.b64 [%0],%1;" ::"r"(b), "r"(c) : "memory"); }
__device__ __forceinline__ void mbar_expect(uint32_t b, uint32_t tx) { asm volatile("mbarrier.arrive.expect_tx.shared::cta.b64 _,[%0],%1;" ::"r"(b), "r"(tx) : "memory"); }
__device__ __forceinline__ void mbar_arrive(uint32_t b) { asm volatile("mbarrier.arrive.shared::cta.b64 _,[%0];" ::"r"(b) : "memory"); }
__device__ __forceinline__ void mbar_wait(uint32_t b, uint32_t ph) {
    uint32_t ok; int it = 0;
    do {
        asm volatile("{.reg .pred p; mbarrier.try_wait.parity.shared::cta.b64 p,[%1],%2; selp.u32 %0,1,0,p;}" : "=r"(ok) : "r"(b), "r"(ph) : "memory");
    } while (!ok && ++it < (1 << 22));
}
__device__ __forceinline__ void fence_async() { asm volatile("fence.proxy.async;" ::: "memory"); }
__device__ __forceinline__ void tma_ld2(uint32_t dst, const CUtensorMap* m, uint32_t bar, int c0, int c1) {
    asm volatile("cp.async.bulk.tensor.2d.shared::cluster.global.mbarrier::complete_tx::bytes [%0],[%1,{%3,%4}],[%2];" ::"r"(dst), "l"(m), "r"(bar), "r"(c0), "r"(c1) : "memory");
}
__device__ __forceinline__ void tma_ld3(uint32_t dst, const CUtensorMap* m, uint32_t bar, int c0, int c1, int c2) {
    asm volatile("cp.async.bulk.tensor.3d.shared::cluster.global.mbarrier::complete_tx::bytes [%0],[%1,{%3,%4,%5}],[%2];" ::"r"(dst), "l"(m), "r"(bar), "r"(c0), "r"(c1), "r"(c2) : "memory");
}
__device__ __forceinline__ void tma_ld5(uint32_t dst, const CUtensorMap* m, uint32_t bar, int c0, int c1, int c2, int c3, int c4) {
    asm volatile("cp.async.bulk.tensor.5d.shared::cluster.global.mbarrier::complete_tx::bytes [%0],[%1,{%3,%4,%5,%6,%7}],[%2];" ::"r"(dst), "l"(m), "r"(bar), "r"(c0), "r"(c1), "r"(c2), "r"(c3), "r"(c4) : "memory");
}
__device__ __forceinline__ void tma_st2(const CUtensorMap* m, uint32_t src, int c0, int c1) {
    asm volatile("cp.async.bulk.tensor.2d.global.shared::cta.bulk_group [%0,{%2,%3}],[%1];" ::"l"(m), "r"(src), "r"(c0), "r"(c1) : "memory");
}
__device__ __forceinline__ void tma_st3(const CUtensorMap* m, uint32_t src, int c0, int c1, int c2) {
    asm volatile("cp.async.bulk.tensor.3d.global.shared::cta.bulk_group [%0,{%2,%3,%4}],[%1];" ::"l"(m), "r"(src), "r"(c0), "r"(c1), "r"(c2) : "memory");
}
__device__ __forceinline__ void tma_st5(const CUtensorMap* m, uint32_t src, int c0, int c1, int c2, int c3, int c4) {
    asm volatile("cp.async.bulk.tensor.5d.global.shared::cta.bulk_group [%0,{%2,%3,%4,%5,%6}],[%1];" ::"l"(m), "r"(src), "r"(c0), "r"(c1), "r"(c2), "r"(c3), "r"(c4) : "memory");
}
__device__ __forceinline__ void bulk_commit() { asm volatile("cp.async.bulk.commit_group;" ::: "memory"); }
template <int N> __device__ __forceinline__ void bulk_wait() { asm volatile("cp.async.bulk.wait_group %0;" ::"n"(N) : "memory"); }
template <int N> __device__ __forceinline__ void bulk_wait_read() { asm volatile("cp.async.bulk.wait_group.read %0;" ::"n"(N) : "memory"); }
__device__ __forceinline__ void bar_sync(int id, int n) { asm volatile("bar.sync %0,%1;" ::"r"(id), "r"(n) : "memory"); }

__device__ __forceinline__ uint4 lds128(uint32_t a) {
    uint4 v; asm volatile("ld.shared.v4.u32 {%0,%1,%2,%3},[%4];" : "=r"(v.x), "=r"(v.y), "=r"(v.z), "=r"(v.w) : "r"(a)); return v;
}
__device__ __forceinline__ void sts128(uint32_t a, uint32_t x, uint32_t y, uint32_t z, uint32_t w) {
    asm volatile("st.shared.v4.u32 [%0],{%1,%2,%3,%4};" ::"r"(a), "r"(x), "r"(y), "r"(z), "r"(w) : "memory");
}
__device__ __forceinline__ void sts64(uint32_t a, uint32_t x, uint32_t y) { asm volatile("st.shared.v2.u32 [%0],{%1,%2};" ::"r"(a), "r"(x), "r"(y) : "memory"); }
__device__ __forceinline__ void sts32(uint32_t a, uint32_t x) { asm volatile("st.shared.u32 [%0],%1;" ::"r"(a), "r"(x) : "memory"); }
__device__ __forceinline__ uint32_t pk(float lo, float hi) { uint32_t r; asm("cvt.rn.bf16x2.f32 %0,%1,%2;" : "=r"(r) : "f"(hi), "f"(lo)); return r; }

__device__ __forceinline__ void mma16z(float* d, uint32_t a0, uint32_t a1, uint32_t a2, uint32_t a3, uint32_t b0, uint32_t b1) {
    asm("mma.sync.aligned.m16n8k16.row.col.f32.bf16.bf16.f32 {%0,%1,%2,%3},{%4,%5,%6,%7},{%8,%9},{%10,%10,%10,%10};"
        : "=f"(d[0]), "=f"(d[1]), "=f"(d[2]), "=f"(d[3]) : "r"(a0), "r"(a1), "r"(a2), "r"(a3), "r"(b0), "r"(b1), "f"(0.f));
}
__device__ __forceinline__ void mma16(float* d, uint32_t a0, uint32_t a1, uint32_t a2, uint32_t a3, uint32_t b0, uint32_t b1) {
    asm("mma.sync.aligned.m16n8k16.row.col.f32.bf16.bf16.f32 {%0,%1,%2,%3},{%4,%5,%6,%7},{%8,%9},{%0,%1,%2,%3};"
        : "+f"(d[0]), "+f"(d[1]), "+f"(d[2]), "+f"(d[3]) : "r"(a0), "r"(a1), "r"(a2), "r"(a3), "r"(b0), "r"(b1));
}
__device__ __forceinline__ void mma8(float* d, uint32_t a0, uint32_t a1, uint32_t b0) {
    asm("mma.sync.aligned.m16n8k8.row.col.f32.bf16.bf16.f32 {%0,%1,%2,%3},{%4,%5},{%6},{%0,%1,%2,%3};"
        : "+f"(d[0]), "+f"(d[1]), "+f"(d[2]), "+f"(d[3]) : "r"(a0), "r"(a1), "r"(b0));
}

__device__ __forceinline__ float basis(int f, int a, int sn) {
    if (f < 0 || f > 10 || a < 0 || a > 21) return 0.f;
    int k = ((2 * f + 1) * (2 * a - 21) + 88 * 6) % 88;
    float x = (float)k * (1.0f / 44.0f);
    return S1 * (sn ? sinpif(x) : cospif(x));
}
__device__ __forceinline__ int fwmap0(int g) { return (g >> 1) + 4 * (g & 1); }
__device__ __forceinline__ void p3col(int nu, int g, int& fw, int& jcs, bool& valid) {
    valid = true;
    if (nu < 2) { fw = fwmap0(g); jcs = nu; }
    else {
        fw = (0x48 << 24 | 0x6A << 16 | 0xA9 << 8 | 0x98) >> (4 * g) & 15;
        jcs = (0xCA >> g) & 1;
        valid = (g != 5 && g != 7);
    }
}
__device__ __forceinline__ uint32_t p1_tab(int r, int lane) {
    int g = lane >> 2, q = lane & 3;
    if (r < 18) {
        int set = r / 6, j = r % 6;
        int sn = j & 1;
        int t = j < 2 ? 1 : (j < 4 ? 2 : 0);
        int b = 8 * t + 2 * q - 2;
        int fw = set == 0 ? fwmap0(g) : (((g & 1) == set - 1) ? 8 + (g >> 1) : -1);
        return pk(basis(fw, b, sn), basis(fw, b + 1, sn));
    } else if (r < 27) {
        int lam = (r - 18) / 3, j = (r - 18) % 3;
        int fh = 4 * lam + (g >> 1), sn = g & 1;
        int a = j == 0 ? 6 + 2 * q : (j == 1 ? 14 + 2 * q : (q < 3 ? 2 * q : -5));
        return pk(basis(fh, a, sn), basis(fh, a + 1, sn));
    }
    return 0;
}
__device__ __forceinline__ uint32_t p3_tab(int r, int lane) {
    int g = lane >> 2, q = lane & 3;
    if (r < 6) {
        int a = 6 + g + 8 * (r & 1), fh = 4 * (r >> 1) + q;
        return pk(basis(fh, a, 0), basis(fh, a, 1));
    }
    int beta = (r - 6) / 3, nu = (r - 6) % 3;
    int b = 6 + 8 * beta + g;
    int fw0, j0, fw1, j1; bool v0, v1;
    p3col(nu, 2 * q, fw0, j0, v0); p3col(nu, 2 * q + 1, fw1, j1, v1);
    return pk(v0 ? basis(fw0, b, j0) : 0.f, v1 ? basis(fw1, b, j1) : 0.f);
}
__device__ __forceinline__ float wcoef(int fw, int fl, int sn, int tap) {
    if (fl > 21 || tap > 48) return 0.f;
    int fh = fl >> 1, kh = tap / 7, kw = tap - 7 * kh;
    int u = (2 * fh + 1) * kh; if (fl & 1) u = -u;
    int k = (u + (2 * fw + 1) * kw + 44 * 4) % 44;
    float x = (float)k * (1.0f / 22.0f);
    return S2 * (sn ? sinpif(x) : cospif(x));
}
__device__ __forceinline__ uint32_t w_tab(int fw, int r, int lane) {
    int g = lane >> 2, q = lane & 3, nb = r >> 3, j = r & 7;
    int tap = 8 * j + 2 * q, fl = 4 * nb + (g >> 1), sn = g & 1;
    return pk(wcoef(fw, fl, sn, tap), wcoef(fw, fl, sn, tap + 1));
}
__device__ __forceinline__ uint32_t tab_addr(uint32_t base, int r, int lane) { return base + (((r >> 2) * 32 + lane) << 4) + ((r & 3) << 2); }

__device__ __forceinline__ void wgen_load(uint32_t (&A)[28], uint32_t win, int c  , int lane) {
    int mi = lane >> 3, rr = lane & 7;
#pragma unroll
    for (int s = 0; s < 7; s++) {
        int u, e, tap;
        if (s < 6) { u = s / 3; e = mi & 1; tap = 16 * (s % 3) + 8 * (mi >> 1) + rr; }
        else { u = mi >> 1; e = mi & 1; tap = 48; }
        int L = 12 * e + c, line = 3 * tap + (L >> 3);
        uint32_t ad = win + u * WPIECE + line * 128 + (((L & 7) ^ (line & 7)) << 4);
        asm volatile("ldmatrix.sync.aligned.m8n8.x4.trans.shared.b16 {%0,%1,%2,%3},[%4];"
                     : "=r"(A[4 * s]), "=r"(A[4 * s + 1]), "=r"(A[4 * s + 2]), "=r"(A[4 * s + 3]) : "r"(ad));
    }
}
__device__ __forceinline__ void wgen_item(const uint32_t (&A)[28], uint32_t tab, unsigned char* wt, int fw, int ks, int qq, int c, int lane) {
    int g = lane >> 2, q = lane & 3;
#pragma unroll
    for (int nb = 0; nb < 6; nb++) {
        uint4 b0 = lds128(tab + ((nb * 2) * 32 + lane) * 16), b1 = lds128(tab + ((nb * 2 + 1) * 32 + lane) * 16);
        float d[2][4];
#pragma unroll
        for (int u = 0; u < 2; u++) {
            mma16z(d[u], A[12 * u], A[12 * u + 1], A[12 * u + 2], A[12 * u + 3], b0.x, b0.y);
            mma16(d[u], A[12 * u + 4], A[12 * u + 5], A[12 * u + 6], A[12 * u + 7], b0.z, b0.w);
            mma16(d[u], A[12 * u + 8], A[12 * u + 9], A[12 * u + 10], A[12 * u + 11], b1.x, b1.y);
            mma8(d[u], A[24 + 2 * u], A[25 + 2 * u], b1.z);
        }
        int fl = 4 * nb + q;
        if (fl < 22) {
            uint4 v;
            v.x = pk(d[0][0] * WSCALE, d[0][2] * WSCALE); v.y = pk(d[0][1] * WSCALE, d[0][3] * WSCALE);
            v.z = pk(d[1][0] * WSCALE, d[1][2] * WSCALE); v.w = pk(d[1][1] * WSCALE, d[1][3] * WSCALE);
            size_t off = (size_t)(fw * 22 + fl) * 36864 + (ks * 4 + qq) * 1536 + (8 * c + g) * 16;
            *reinterpret_cast<uint4*>(wt + off) = v;
        }
    }
}

struct P1State { uint32_t P0[8][3][2]; uint32_t P1[4][3][2]; };

__device__ __forceinline__ void p1_step1(P1State& st, const uint32_t (&T)[28], uint32_t in0, uint32_t in1, uint32_t in2, int c, int lane) {
    int g = lane >> 2, q = lane & 3;
    uint32_t off[2];
#pragma unroll
    for (int e = 0; e < 2; e++) {
        int L = 12 * e + c, line = 12 * g + 3 * q + (L >> 3);
        off[e] = line * 128 + (((L & 7) ^ (line & 7)) << 4);
    }
#pragma unroll
    for (int nu = 0; nu < 3; nu++) {
        const int ro = (nu == 0 ? 6 : (nu == 1 ? 14 : 0)) * 1536;
        uint32_t v[3][2][4];
#pragma unroll
        for (int t = 0; t < 3; t++)
#pragma unroll
            for (int e = 0; e < 2; e++) {
                uint4 x = lds128((t == 0 ? in0 : (t == 1 ? in1 : in2)) + ro + off[e]);
                v[t][e][0] = x.x; v[t][e][1] = x.y; v[t][e][2] = x.z; v[t][e][3] = x.w;
            }
#pragma unroll
        for (int ch = 0; ch < 4; ch++) {
            float d1[4];
#pragma unroll
            for (int hf = 0; hf < 2; hf++) {
                const int cc = ch + 4 * hf, j = cc >> 1;
                const uint32_t sel = (cc & 1) ? 0x7632 : 0x5410;
                uint32_t b0 = __byte_perm(v[0][0][j], v[0][1][j], sel);
                uint32_t b1 = __byte_perm(v[1][0][j], v[1][1][j], sel);
                uint32_t b2 = __byte_perm(v[2][0][j], v[2][1][j], sel);
                float d0[4];
                mma16z(d0, T[0], T[1], T[2], T[3], b1, b2);
                mma8(d0, T[4], T[5], b0);
                if (hf == 0) mma16z(d1, T[6], T[7], T[8], T[9], b1, b2);
                else mma16(d1, T[12], T[13], T[14], T[15], b1, b2);
                mma8(d1, T[10 + 6 * hf], T[11 + 6 * hf], b0);
                st.P0[cc][nu][0] = pk(d0[0], d0[1]); st.P0[cc][nu][1] = pk(d0[2], d0[3]);
            }
            st.P1[ch][nu][0] = pk(d1[0], d1[1]); st.P1[ch][nu][1] = pk(d1[2], d1[3]);
        }
    }
}
__device__ __forceinline__ void p1_step2(const P1State& st, const uint32_t (&T)[28], uint32_t out, int wq, int lane) {
    int g = lane >> 2, q = lane & 3;
#pragma unroll
    for (int lam = 0; lam < 3; lam++) {
        const uint32_t B0 = T[18 + 3 * lam], B1 = T[19 + 3 * lam], B2 = T[20 + 3 * lam];
        bool ok = (lam < 2) || (q < 3);
        {
            uint32_t o[4][4];
#pragma unroll
            for (int j = 0; j < 4; j++) {
                float d[2][4];
#pragma unroll
                for (int e = 0; e < 2; e++) {
                    const int cc = 2 * j + e;
                    mma16z(d[e], st.P0[cc][0][0], st.P0[cc][0][1], st.P0[cc][1][0], st.P0[cc][1][1], B0, B1);
                    mma8(d[e], st.P0[cc][2][0], st.P0[cc][2][1], B2);
                }
                o[0][j] = pk(d[0][0] - d[0][3], d[1][0] - d[1][3]);
                o[1][j] = pk(d[0][0] + d[0][3], d[1][0] + d[1][3]);
                o[2][j] = pk(d[0][2] + d[0][1], d[1][2] + d[1][1]);
                o[3][j] = pk(d[0][2] - d[0][1], d[1][2] - d[1][1]);
            }
            int r0 = fwmap0(g) * 11 + 4 * lam + q;
            if (ok) {
#pragma unroll
                for (int k = 0; k < 4; k++) {
                    int r = r0 + 121 * (k >> 1), ck = 4 * (k & 1) + wq;
                    sts128(out + r * 128 + ((ck ^ (r & 7)) << 4), o[k][0], o[k][1], o[k][2], o[k][3]);
                }
            }
        }
        {
            uint32_t o[4][2];
#pragma unroll
            for (int j = 0; j < 2; j++) {
                float d[2][4];
#pragma unroll
                for (int e = 0; e < 2; e++) {
                    const int cc = 2 * j + e;
                    mma16z(d[e], st.P1[cc][0][0], st.P1[cc][0][1], st.P1[cc][1][0], st.P1[cc][1][1], B0, B1);
                    mma8(d[e], st.P1[cc][2][0], st.P1[cc][2][1], B2);
                }
                o[0][j] = pk(d[0][0] - d[0][3], d[1][0] - d[1][3]);
                o[1][j] = pk(d[0][0] + d[0][3], d[1][0] + d[1][3]);
                o[2][j] = pk(d[0][2] + d[0][1], d[1][2] + d[1][1]);
                o[3][j] = pk(d[0][2] - d[0][1], d[1][2] - d[1][1]);
            }
            int r0 = (8 + (g >> 1)) * 11 + 4 * lam + q;
            if (ok && g < 6) {
#pragma unroll
                for (int k = 0; k < 4; k++) {
                    int r = r0 + 121 * (k >> 1), ck = 4 * (k & 1) + wq;
                    sts64(out + r * 128 + ((ck ^ (r & 7)) << 4) + 8 * (g & 1), o[k][0], o[k][1]);
                }
            }
        }
    }
}

__device__ __forceinline__ void wgmma56(float (&d)[28], const uint32_t* a, uint64_t desc, int sd) {
    asm volatile("{.reg .pred p; setp.ne.b32 p,%33,0; wgmma.mma_async.sync.aligned.m64n56k16.f32.bf16.bf16 "
                 "{%0,%1,%2,%3,%4,%5,%6,%7,%8,%9,%10,%11,%12,%13,%14,%15,%16,%17,%18,%19,%20,%21,%22,%23,%24,%25,%26,%27},"
                 "{%28,%29,%30,%31},%32,p,1,1,0;}"
                 : "+f"(d[0]), "+f"(d[1]), "+f"(d[2]), "+f"(d[3]), "+f"(d[4]), "+f"(d[5]), "+f"(d[6]), "+f"(d[7]), "+f"(d[8]), "+f"(d[9]),
                   "+f"(d[10]), "+f"(d[11]), "+f"(d[12]), "+f"(d[13]), "+f"(d[14]), "+f"(d[15]), "+f"(d[16]), "+f"(d[17]), "+f"(d[18]), "+f"(d[19]),
                   "+f"(d[20]), "+f"(d[21]), "+f"(d[22]), "+f"(d[23]), "+f"(d[24]), "+f"(d[25]), "+f"(d[26]), "+f"(d[27])
                 : "r"(a[0]), "r"(a[1]), "r"(a[2]), "r"(a[3]), "l"(desc), "r"(sd));
}
__device__ __forceinline__ void p2_mma(float (&dp)[28], float (&dm)[28], const uint32_t (&Wf)[48], uint32_t in) {
    uint64_t base = (uint64_t)((in & 0x3FFFF) >> 4) | (1ull << 16) | ((uint64_t)(1024 >> 4) << 32) | (1ull << 62);
    asm volatile("wgmma.fence.sync.aligned;" ::: "memory");
#pragma unroll
    for (int ks = 0; ks < 6; ks++) {
        wgmma56(dp, &Wf[4 * ks], base + (ks >> 1) * (7168 >> 4) + (ks & 1) * 2, ks);
        wgmma56(dm, &Wf[24 + 4 * ks], base + (ks >> 1) * (7168 >> 4) + (ks & 1) * 2 + 4, ks);
    }
    asm volatile("wgmma.commit_group.sync.aligned;" ::: "memory");
}
__device__ __forceinline__ void p2_epi(const float (&dp)[28], const float (&dm)[28], uint32_t out, int wq, int lane) {
    int g = lane >> 2, q = lane & 3;
    int ck = 2 * wq + (g >> 2);
    uint32_t a0 = out + (2 * q) * 128 + ((ck ^ (2 * q)) << 4) + (g & 3) * 4;
    uint32_t a1 = out + (2 * q + 1) * 128 + ((ck ^ (2 * q + 1)) << 4) + (g & 3) * 4;
#pragma unroll
    for (int nb = 0; nb < 7; nb++) {
        float pr = dp[4 * nb] - dp[4 * nb + 3], pi = dp[4 * nb + 1] + dp[4 * nb + 2];
        float mr = dm[4 * nb] - dm[4 * nb + 3], mi = dm[4 * nb + 1] + dm[4 * nb + 2];
        sts32(a0 + nb * 1024, pk(pr + mr, pi - mi));
        sts32(a1 + nb * 1024, pk(pi + mi, mr - pr));
    }
}

__device__ __forceinline__ void p3_compute(uint32_t (&o)[2][4][4], const uint32_t (&T)[12], uint32_t in, int wq, int lane) {
    int g = lane >> 2, q = lane & 3;
    uint32_t ad[3][3];
#pragma unroll
    for (int nu = 0; nu < 3; nu++) {
        int fw, jcs; bool v; p3col(nu, g, fw, jcs, v);
#pragma unroll
        for (int ka = 0; ka < 3; ka++) {
            int fh = min(4 * ka + q, 10), r = jcs * 121 + fw * 11 + fh;
            ad[nu][ka] = in + r * 128 + (((2 * wq) ^ (r & 7)) << 4);
        }
    }
#pragma unroll
    for (int h = 0; h < 2; h++) {
        uint32_t z[3][3][4];
#pragma unroll
        for (int nu = 0; nu < 3; nu++)
#pragma unroll
            for (int ka = 0; ka < 3; ka++) {
                uint4 x = lds128(ad[nu][ka] ^ (h << 4));
                z[nu][ka][0] = x.x; z[nu][ka][1] = x.y; z[nu][ka][2] = x.z; z[nu][ka][3] = x.w;
            }
#pragma unroll
        for (int j = 0; j < 2; j++) {
            float d2[2][2][4];
#pragma unroll
            for (int e = 0; e < 2; e++) {
                const int ch = 2 * j + e;
                uint32_t P[3][2];
#pragma unroll
                for (int nu = 0; nu < 3; nu++) {
                    float d[4];
                    mma16z(d, T[0], T[1], T[2], T[3], z[nu][0][ch], z[nu][1][ch]);
                    mma8(d, T[4], T[5], z[nu][2][ch]);
                    P[nu][0] = pk(d[0], d[1]); P[nu][1] = pk(d[2], d[3]);
                }
#pragma unroll
                for (int be = 0; be < 2; be++) {
                    mma16z(d2[e][be], P[0][0], P[0][1], P[1][0], P[1][1], T[6 + 3 * be], T[7 + 3 * be]);
                    mma8(d2[e][be], P[2][0], P[2][1], T[8 + 3 * be]);
                }
            }
#pragma unroll
            for (int be = 0; be < 2; be++)
#pragma unroll
                for (int k = 0; k < 4; k++) o[be][k][2 * h + j] = pk(d2[0][be][k], d2[1][be][k]);
        }
    }
}
__device__ __forceinline__ void p3_store(const uint32_t (&o)[2][4][4], uint32_t out0, uint32_t out1, int c, int lane) {
    int g = lane >> 2, q = lane & 3;
#pragma unroll
    for (int e = 0; e < 2; e++) {
        int L = 12 * e + c, line = 12 * g + 3 * q + (L >> 3);
        uint32_t off = line * 128 + (((L & 7) ^ (line & 7)) << 4);
#pragma unroll
        for (int be = 0; be < 2; be++)
#pragma unroll
            for (int hi = 0; hi < 2; hi++) {
                const int k = 2 * hi + e;
                sts128((be ? out1 : out0) + off + hi * 8 * 1536, o[be][k][0], o[be][k][1], o[be][k][2], o[be][k][3]);
            }
    }
}

__global__ void __launch_bounds__(384, 1) k_wgen(const __grid_constant__ Maps mp) {
    extern __shared__ __align__(1024) unsigned char smraw[];
    __shared__ uint64_t bar;
    uint32_t sm = (s2u(smraw) + 1023) & ~1023u;
    int item = blockIdx.x, fw = item % 11, iq = item / 11, ks = iq >> 2, qq = iq & 3;
    int tid = threadIdx.x, lane = tid & 31, warp = tid >> 5;
    uint32_t tab = sm + 2 * WPIECE;
    if (tid == 0) {
        mbar_init(s2u(&bar), 1); fence_async();
        mbar_expect(s2u(&bar), 2 * 49 * 384);
        tma_ld3(sm, &mp.w, s2u(&bar), 0, 3 * (8 * ks + qq), 0);
        tma_ld3(sm + WPIECE, &mp.w, s2u(&bar), 0, 3 * (8 * ks + qq + 4), 0);
    }
    for (int i = tid; i < 48 * 32; i += 384) sts32(tab_addr(tab, i >> 5, i & 31), w_tab(fw, i >> 5, i & 31));
    __syncthreads();
    mbar_wait(s2u(&bar), 0);
    uint32_t A[28];
    wgen_load(A, sm, warp, lane);
    wgen_item(A, tab, g_Wt, fw, ks, qq, warp, lane);
}

__global__ void __launch_bounds__(384, 1) k_p1(const __grid_constant__ Maps mp) {
    extern __shared__ __align__(1024) unsigned char smraw[];
    __shared__ uint64_t bar;
    uint32_t sm = (s2u(smraw) + 1023) & ~1023u;
    int tile = blockIdx.x, th = tile / 14, tw = tile % 14;
    int tid = threadIdx.x, lane = tid & 31, warp = tid >> 5;
    uint32_t tab = sm + 3 * BLK;
    if (tid == 0) {
        mbar_init(s2u(&bar), 1); fence_async();
        mbar_expect(s2u(&bar), 3 * BLK);
        for (int t = 0; t < 3; t++) {
            int cb = (2 * tw - 1 + t + 28) % 28;
            tma_ld3(sm + t * BLK, &mp.x6, s2u(&bar), 0, 12 * cb, (16 * th - 6 + 224) % 224);
            tma_ld3(sm + t * BLK + 9216, &mp.x16, s2u(&bar), 0, 12 * cb, 16 * th);
        }
    }
    for (int i = tid; i < 28 * 32; i += 384) sts32(tab_addr(tab, i >> 5, i & 31), p1_tab(i >> 5, i & 31));
    __syncthreads();
    uint32_t T[28];
#pragma unroll
    for (int v = 0; v < 7; v++) { uint4 x = lds128(tab + (v * 32 + lane) * 16); T[4 * v] = x.x; T[4 * v + 1] = x.y; T[4 * v + 2] = x.z; T[4 * v + 3] = x.w; }
    mbar_wait(s2u(&bar), 0);
    P1State st;
    p1_step1(st, T, sm, sm + BLK, sm + 2 * BLK, warp, lane);
    __syncthreads();
    int wg = warp >> 2;
    p1_step2(st, T, sm + wg * BLK, warp & 3, lane);
    fence_async();
    bar_sync(1 + wg, 128);
    if ((tid & 127) == 0) { tma_st2(&mp.s, sm + wg * BLK, 0, (tile * 3 + wg) * 242); bulk_commit(); bulk_wait<0>(); }
}

__global__ void __launch_bounds__(384, 1) k_p2(const __grid_constant__ Maps mp) {
    extern __shared__ __align__(1024) unsigned char smraw[];
    __shared__ uint64_t bar[7];
    uint32_t sm = (s2u(smraw) + 1023) & ~1023u;
    int fp = blockIdx.x;
    int tid = threadIdx.x, lane = tid & 31, warp = tid >> 5, wg = warp >> 2, wq = warp & 3;
    if (tid == 0) {
        for (int s = 0; s < 7; s++) mbar_init(s2u(&bar[s]), 1);
        fence_async();
        for (int s = 0; s < 7; s++) { mbar_expect(s2u(&bar[s]), 21504); tma_ld5(sm + s * 21504, &mp.p2l, s2u(&bar[s]), 0, 0, 28 * s, 0, fp); }
    }
    uint32_t Wf[48];
    {
        const uint4* p = reinterpret_cast<const uint4*>(g_Wt + (size_t)fp * 73728 + (lane & 3) * 1536 + (8 * warp + (lane >> 2)) * 16);
#pragma unroll
        for (int k = 0; k < 12; k++) { uint4 x = __ldcg(p + k * 384); Wf[4 * k] = x.x; Wf[4 * k + 1] = x.y; Wf[4 * k + 2] = x.z; Wf[4 * k + 3] = x.w; }
    }
    __syncthreads();
    uint32_t outb = sm + 7 * 21504 + wg * 2 * 7168;
    float dp[28], dm[28];
#pragma unroll
    for (int i = 0; i < 28; i++) { dp[i] = 0.f; dm[i] = 0.f; }
    for (int s = 0; s < 7; s++) {
        mbar_wait(s2u(&bar[s]), 0);
        p2_mma(dp, dm, Wf, sm + s * 21504);
        if ((tid & 127) == 0) bulk_wait_read<1>();
        asm volatile("wgmma.wait_group.sync.aligned 0;" ::: "memory");
        bar_sync(1 + wg, 128);
        uint32_t ob = outb + (s & 1) * 7168;
        p2_epi(dp, dm, ob, wq, lane);
        fence_async();
        bar_sync(1 + wg, 128);
        if ((tid & 127) == 0) { tma_st5(&mp.p2s, ob, 0, 0, 28 * s, wg, fp); bulk_commit(); }
    }
    if ((tid & 127) == 0) bulk_wait<0>();
}

__global__ void __launch_bounds__(384, 1) k_p3(const __grid_constant__ Maps mp) {
    extern __shared__ __align__(1024) unsigned char smraw[];
    __shared__ uint64_t bar;
    uint32_t sm = (s2u(smraw) + 1023) & ~1023u;
    int tile = blockIdx.x, th = tile / 14, tw = tile % 14;
    int tid = threadIdx.x, lane = tid & 31, warp = tid >> 5, wg = warp >> 2;
    uint32_t tab = sm + 3 * BLK;
    if (tid == 0) {
        mbar_init(s2u(&bar), 1); fence_async();
        mbar_expect(s2u(&bar), 3 * SLAB);
        for (int t = 0; t < 3; t++) tma_ld2(sm + t * BLK, &mp.s, s2u(&bar), 0, (tile * 3 + t) * 242);
    }
    sts32(tab_addr(tab, tid >> 5, lane), p3_tab(tid >> 5, lane));
    __syncthreads();
    uint32_t T[12];
#pragma unroll
    for (int v = 0; v < 3; v++) { uint4 x = lds128(tab + (v * 32 + lane) * 16); T[4 * v] = x.x; T[4 * v + 1] = x.y; T[4 * v + 2] = x.z; T[4 * v + 3] = x.w; }
    mbar_wait(s2u(&bar), 0);
    uint32_t o[2][4][4];
    p3_compute(o, T, sm + wg * BLK, warp & 3, lane);
    __syncthreads();
    p3_store(o, sm, sm + BLK, warp, lane);
    fence_async();
    __syncthreads();
    if (tid == 0) {
        tma_st3(&mp.y16, sm, 0, 24 * tw, 16 * th);
        tma_st3(&mp.y16, sm + BLK, 0, 24 * tw + 12, 16 * th);
        bulk_commit(); bulk_wait<0>();
    }
}

typedef CUresult (*EncFn)(CUtensorMap*, CUtensorMapDataType, cuuint32_t, void*, const cuuint64_t*, const cuuint64_t*, const cuuint32_t*,
                          const cuuint32_t*, CUtensorMapInterleave, CUtensorMapSwizzle, CUtensorMapL2promotion, CUtensorMapFloatOOBfill);

void enc(EncFn f, CUtensorMap* m, void* p, int rank, const cuuint64_t* dims, const cuuint64_t* strides, const cuuint32_t* box) {
    cuuint32_t es[5] = {1, 1, 1, 1, 1};
    f(m, CU_TENSOR_MAP_DATA_TYPE_BFLOAT16, rank, p, dims, strides, box, es, CU_TENSOR_MAP_INTERLEAVE_NONE, CU_TENSOR_MAP_SWIZZLE_128B,
      CU_TENSOR_MAP_L2_PROMOTION_NONE, CU_TENSOR_MAP_FLOAT_OOB_FILL_NONE);
}

}

extern "C" void kernel_launch(void* const* d_in, const int* in_sizes, int n_in, void* d_out, int out_size) {
    void* fn = nullptr; cudaDriverEntryPointQueryResult qr;
    cudaGetDriverEntryPoint("cuTensorMapEncodeTiled", &fn, cudaEnableDefault, &qr);
    EncFn f = (EncFn)fn;
    void* pS; cudaGetSymbolAddress(&pS, g_S);
    Maps mp;
    {
        cuuint64_t d[3] = {64, 336, 224}, s[2] = {128, 43008};
        cuuint32_t b6[3] = {64, 12, 6}, b16[3] = {64, 12, 16};
        enc(f, &mp.x6, d_in[0], 3, d, s, b6); enc(f, &mp.x16, d_in[0], 3, d, s, b16); enc(f, &mp.y16, d_out, 3, d, s, b16);
    }
    { cuuint64_t d[2] = {64, (cuuint64_t)NT * 3 * 242}, s[1] = {128}; cuuint32_t b[2] = {64, 242}; enc(f, &mp.s, pS, 2, d, s, b); }
    {
        cuuint64_t d[5] = {64, 2, NT, 3, NFP}, s[4] = {121 * 128, 3 * SLAB, SLAB, 128};
        cuuint32_t bl[5] = {64, 2, 28, 3, 1}, bs[5] = {64, 2, 28, 1, 1};
        enc(f, &mp.p2l, pS, 5, d, s, bl); enc(f, &mp.p2s, pS, 5, d, s, bs);
    }
    { cuuint64_t d[3] = {64, 144, 49}, s[2] = {128, 18432}; cuuint32_t b[3] = {64, 3, 49}; enc(f, &mp.w, d_in[1], 3, d, s, b); }
    cudaFuncSetAttribute(k_wgen, cudaFuncAttributeMaxDynamicSharedMemorySize, 2 * WPIECE + 6144 + 1024);
    cudaFuncSetAttribute(k_p1, cudaFuncAttributeMaxDynamicSharedMemorySize, 3 * BLK + 4096 + 1024);
    cudaFuncSetAttribute(k_p2, cudaFuncAttributeMaxDynamicSharedMemorySize, 9 * 21504 + 1024);
    cudaFuncSetAttribute(k_p3, cudaFuncAttributeMaxDynamicSharedMemorySize, 3 * BLK + 4096 + 1024);
    k_wgen<<<264, 384, 2 * WPIECE + 6144 + 1024>>>(mp);
    k_p1<<<NT, 384, 3 * BLK + 4096 + 1024>>>(mp);
    k_p2<<<NFP, 384, 9 * 21504 + 1024>>>(mp);
    k_p3<<<NT, 384, 3 * BLK + 4096 + 1024>>>(mp);
}
```

```cpp
#include <cuda_runtime.h>
#include <cuda_bf16.h>
#include <cuda.h>
#include <stdint.h>

#define SPLIT 3
namespace {

constexpr int NCTA = 132;
constexpr int NT = 196;
constexpr int NU = 588;
constexpr int NFP = 121;
constexpr int BLK = 33792;
constexpr int SLAB = 242 * 128;
constexpr int WPIECE = 19456;
constexpr int STG = 21504;
constexpr int O_B4 = 0, O_B0 = 87040, O_B1 = 120832, O_B2 = 154624, O_B3 = 188416;
constexpr int O_W1 = 0, O_W0 = 2 * WPIECE, O_WT = 4 * WPIECE;
constexpr int O_IN = 33792, O_OUT = O_IN + 3 * STG, O_Z3 = O_IN + STG;
constexpr int O_C = 222208, O_BAR = 230912, SMEM = 232448;
constexpr int C_P1A = 0, C_P1B = 2560, C_P3 = 7168, C_BYTES = 8704, WT_BYTES = 6912;
constexpr int BC = 0, BW = 1, BWD = 3, BWT = 4, BX = 5, BZ = 10, BPF = 15, BPE = 22, BRD = 29, BDN = 62, NBAR = 95;

constexpr uint16_t LUT_A[11] = {0x3f95, 0x3f92, 0x3f8c, 0x3f83, 0x3f6f, 0x3f53, 0x3f33, 0x3f0f, 0x3ed1, 0x3e7e, 0x3daa};
constexpr uint16_t LUT_B[11] = {0x3fe9, 0x3fe4, 0x3fdb, 0x3fcd, 0x3fbb, 0x3fa5, 0x3f8c, 0x3f60, 0x3f23, 0x3ec7, 0x3e05};
constexpr uint16_t LUT_W[12] = {0x3abb, 0x3ab9, 0x3ab3, 0x3aaa, 0x3a9d, 0x3a8d, 0x3a75, 0x3a4a, 0x3a1b, 0x39d3, 0x3955, 0};
constexpr uint16_t basis(int setb, int f, int a, int sn) {
    if (f < 0 || f > 10 || a < 0 || a > 21) return 0;
    int k = ((2 * f + 1) * (2 * a - 21) - 22 * sn + 88 * 7) % 88;
    if (k > 44) k = 88 - k;
    int neg = 0;
    if (k > 22) { k = 44 - k; neg = 1; }
    return (uint16_t)((setb ? LUT_B[k >> 1] : LUT_A[k >> 1]) | (neg << 15));
}
constexpr uint16_t neg16(uint16_t v) { return v ? (uint16_t)(v ^ 0x8000) : v; }
constexpr uint16_t wcoef(int fw, int fl, int sn, int tap) {
    if (fl > 21) return 0;
    int fh = fl >> 1, kh = tap / 7, kw = tap - 7 * kh;
    int u = (2 * fh + 1) * kh;
    if (fl & 1) u = -u;
    int k = (u + (2 * fw + 1) * kw - 11 * sn + 44 * 4) % 44;
    if (k > 22) k = 44 - k;
    int neg = 0;
    if (k > 11) { k = 22 - k; neg = 1; }
    return (uint16_t)(LUT_W[k] | (neg << 15));
}
__host__ __device__ constexpr int fwmap0(int g) { return (g >> 1) + 4 * (g & 1); }
__host__ __device__ constexpr int p3fw(int nu, int g) { return nu < 2 ? fwmap0(g) : (int)((0x486AA998u >> (4 * g)) & 15); }
__host__ __device__ constexpr int p3cs(int nu, int g) { return nu < 2 ? nu : ((0xCA >> g) & 1); }
constexpr bool p3ok(int nu, int g) { return nu < 2 || (g != 5 && g != 7); }

struct alignas(128) CTab { uint16_t v[C_BYTES / 2]; };
struct alignas(128) WTab { uint16_t v[WT_BYTES / 2]; };
constexpr CTab make_ctab() {
    CTab t{};
    for (int lane = 0; lane < 32; lane++) {
        int g = lane >> 2, q = lane & 3;
        for (int r = 0; r < 18; r++) {
            int quad = r >> 2, j = r & 3, sn = j & 1;
            int set = quad < 3 ? quad : (quad == 3 ? 1 + (j >> 1) : 0);
            int t8 = quad < 3 ? 1 + (j >> 1) : 0;
            int b = 8 * t8 + 2 * q - 2;
            int fw = set == 0 ? fwmap0(g) : (((g & 1) == set - 1) ? 8 + (g >> 1) : -1);
            int o = (C_P1A + (quad * 32 + lane) * 16 + j * 4) / 2;
            t.v[o] = basis(0, fw, b, sn); t.v[o + 1] = basis(0, fw, b + 1, sn);
        }
        for (int r = 0; r < 12; r++) {
            int o = (C_P3 + ((r >> 2) * 32 + lane) * 16 + (r & 3) * 4) / 2;
            if (r < 6) {
                int a = 6 + g + 8 * (r & 1), fh = 4 * (r >> 1) + q;
                t.v[o] = basis(0, fh, a, 0); t.v[o + 1] = basis(0, fh, a, 1);
            } else {
                int be = r < 8 ? r - 6 : (r - 8) >> 1, nu = r < 8 ? 2 : (r & 1);
                int b = 6 + 8 * be + 4 * (g & 1) + (g >> 1);
                t.v[o] = p3ok(nu, 2 * q) ? basis(1, p3fw(nu, 2 * q), b, p3cs(nu, 2 * q)) : 0;
                t.v[o + 1] = p3ok(nu, 2 * q + 1) ? basis(1, p3fw(nu, 2 * q + 1), b, p3cs(nu, 2 * q + 1)) : 0;
            }
        }
    }
    for (int kc = 0; kc < 6; kc++)
        for (int nb = 0; nb < 6; nb++)
            for (int n = 0; n < 8; n++)
                for (int k = 0; k < 8; k++) {
                    int nu = kc >> 1, ds = kc & 1, im = nb & 1, fh = 4 * (nb >> 1) + (n >> 1), mi = n & 1;
                    int a = nu == 0 ? 6 + k : (nu == 1 ? 14 + k : (k < 6 ? k : -1));
                    uint16_t v = basis(0, fh, a, ds ^ im);
                    if (ds != im && (im ? mi : !mi)) v = neg16(v);
                    t.v[C_P1B / 2 + ((kc * 6 + nb) * 8 + n) * 8 + k] = v;
                }
    return t;
}
constexpr WTab make_wtab(int fw) {
    WTab t{};
    for (int nb = 0; nb < 6; nb++)
        for (int n = 0; n < 8; n++) {
            for (int tap = 0; tap < 48; tap++) t.v[(((tap >> 3) * 6 + nb) * 8 + n) * 8 + (tap & 7)] = wcoef(fw, 4 * nb + (n >> 1), n & 1, tap);
            t.v[((7 * 6 + nb) * 8 + n) * 8] = wcoef(fw, 4 * nb + (n >> 1), n & 1, 48);
        }
    return t;
}
__device__ const CTab g_ctab = make_ctab();
__device__ const WTab g_wtab[11] = {make_wtab(0), make_wtab(1), make_wtab(2), make_wtab(3), make_wtab(4), make_wtab(5),
                                    make_wtab(6), make_wtab(7), make_wtab(8), make_wtab(9), make_wtab(10)};

__device__ __align__(1024) unsigned char g_S[(size_t)NU * SLAB];
__device__ __align__(1024) unsigned char g_Wt[(size_t)NFP * 73728];
constexpr int CX = 0, CW = 7, CY = 18, CD = 39, NCNT = 40;
__device__ unsigned g_cnt[NCNT * 32];

struct Maps { CUtensorMap x6, x16, y, s, p2l, p2s, w; };

#define TR(role, i)

__device__ __forceinline__ uint32_t s2u(const void* p) { return (uint32_t)__cvta_generic_to_shared(p); }
__device__ __forceinline__ void mbar_init(uint32_t b, int c) { asm volatile("mbarrier.init.shared::cta.b64 [%0],%1;" ::"r"(b), "r"(c) : "memory"); }
__device__ __forceinline__ void mbar_expect(uint32_t b, uint32_t tx) { asm volatile("mbarrier.arrive.expect_tx.shared::cta.b64 _,[%0],%1;" ::"r"(b), "r"(tx) : "memory"); }
__device__ __forceinline__ void mbar_arrive(uint32_t b) { asm volatile("mbarrier.arrive.shared::cta.b64 _,[%0];" ::"r"(b) : "memory"); }
__device__ __forceinline__ void mbar_wait(uint32_t b) {
    uint32_t ok; int it = 0;
    do {
        asm volatile("{.reg .pred p; mbarrier.try_wait.parity.shared::cta.b64 p,[%1],0; selp.u32 %0,1,0,p;}" : "=r"(ok) : "r"(b) : "memory");
    } while (!ok && ++it < (1 << 16));
}
__device__ __forceinline__ void poll(int c, unsigned target) {
    unsigned v; int it = 0;
    do { asm volatile("ld.acquire.gpu.global.u32 %0,[%1];" : "=r"(v) : "l"(&g_cnt[c * 32]) : "memory"); } while (v < target && ++it < (1 << 18));
}
__device__ __forceinline__ void signal(int c) { asm volatile("red.release.gpu.global.add.u32 [%0],1;" ::"l"(&g_cnt[c * 32]) : "memory"); }
__device__ __forceinline__ void fence_async_s() { asm volatile("fence.proxy.async.shared::cta;" ::: "memory"); }
__device__ __forceinline__ void fence_async_g() { asm volatile("fence.proxy.async.global;" ::: "memory"); }
__device__ __forceinline__ void bulk_ld(uint32_t dst, const void* src, uint32_t bytes, uint32_t bar) {
    asm volatile("cp.async.bulk.shared::cluster.global.mbarrier::complete_tx::bytes [%0],[%1],%2,[%3];" ::"r"(dst), "l"(src), "r"(bytes), "r"(bar) : "memory");
}
__device__ __forceinline__ void tma_ld2(uint32_t dst, const CUtensorMap* m, uint32_t bar, int c0, int c1) {
    asm volatile("cp.async.bulk.tensor.2d.shared::cluster.global.mbarrier::complete_tx::bytes [%0],[%1,{%3,%4}],[%2];" ::"r"(dst), "l"(m), "r"(bar), "r"(c0), "r"(c1) : "memory");
}
__device__ __forceinline__ void tma_ld3(uint32_t dst, const CUtensorMap* m, uint32_t bar, int c0, int c1, int c2) {
    asm volatile("cp.async.bulk.tensor.3d.shared::cluster.global.mbarrier::complete_tx::bytes [%0],[%1,{%3,%4,%5}],[%2];" ::"r"(dst), "l"(m), "r"(bar), "r"(c0), "r"(c1), "r"(c2) : "memory");
}
__device__ __forceinline__ void tma_ld5(uint32_t dst, const CUtensorMap* m, uint32_t bar, int c0, int c1, int c2, int c3, int c4) {
    asm volatile("cp.async.bulk.tensor.5d.shared::cluster.global.mbarrier::complete_tx::bytes [%0],[%1,{%3,%4,%5,%6,%7}],[%2];" ::"r"(dst), "l"(m), "r"(bar), "r"(c0), "r"(c1), "r"(c2), "r"(c3), "r"(c4) : "memory");
}
__device__ __forceinline__ void tma_st2(const CUtensorMap* m, uint32_t src, int c0, int c1) {
    asm volatile("cp.async.bulk.tensor.2d.global.shared::cta.bulk_group [%0,{%2,%3}],[%1];" ::"l"(m), "r"(src), "r"(c0), "r"(c1) : "memory");
}
__device__ __forceinline__ void tma_st4(const CUtensorMap* m, uint32_t src, int c0, int c1, int c2, int c3) {
    asm volatile("cp.async.bulk.tensor.4d.global.shared::cta.bulk_group [%0,{%2,%3,%4,%5}],[%1];" ::"l"(m), "r"(src), "r"(c0), "r"(c1), "r"(c2), "r"(c3) : "memory");
}
__device__ __forceinline__ void tma_st5(const CUtensorMap* m, uint32_t src, int c0, int c1, int c2, int c3, int c4) {
    asm volatile("cp.async.bulk.tensor.5d.global.shared::cta.bulk_group [%0,{%2,%3,%4,%5,%6}],[%1];" ::"l"(m), "r"(src), "r"(c0), "r"(c1), "r"(c2), "r"(c3), "r"(c4) : "memory");
}
__device__ __forceinline__ void bulk_commit_wait() { asm volatile("cp.async.bulk.commit_group;\n cp.async.bulk.wait_group 0;" ::: "memory"); }
__device__ __forceinline__ void bar_sync(int id, int n) { asm volatile("bar.sync %0,%1;" ::"r"(id), "r"(n) : "memory"); }

__device__ __forceinline__ uint4 lds128(uint32_t a) {
    uint4 v; asm volatile("ld.shared.v4.u32 {%0,%1,%2,%3},[%4];" : "=r"(v.x), "=r"(v.y), "=r"(v.z), "=r"(v.w) : "r"(a)); return v;
}
__device__ __forceinline__ void sts128(uint32_t a, uint32_t x, uint32_t y, uint32_t z, uint32_t w) {
    asm volatile("st.shared.v4.u32 [%0],{%1,%2,%3,%4};" ::"r"(a), "r"(x), "r"(y), "r"(z), "r"(w) : "memory");
}
__device__ __forceinline__ void sts64(uint32_t a, uint32_t x, uint32_t y) { asm volatile("st.shared.v2.u32 [%0],{%1,%2};" ::"r"(a), "r"(x), "r"(y) : "memory"); }
__device__ __forceinline__ void sts32(uint32_t a, uint32_t x) { asm volatile("st.shared.u32 [%0],%1;" ::"r"(a), "r"(x) : "memory"); }
__device__ __forceinline__ uint32_t pk(float lo, float hi) { uint32_t r; asm("cvt.rn.bf16x2.f32 %0,%1,%2;" : "=r"(r) : "f"(hi), "f"(lo)); return r; }

__device__ __forceinline__ void mma16z(float* d, uint32_t a0, uint32_t a1, uint32_t a2, uint32_t a3, uint32_t b0, uint32_t b1) {
    asm("mma.sync.aligned.m16n8k16.row.col.f32.bf16.bf16.f32 {%0,%1,%2,%3},{%4,%5,%6,%7},{%8,%9},{%10,%10,%10,%10};"
        : "=f"(d[0]), "=f"(d[1]), "=f"(d[2]), "=f"(d[3]) : "r"(a0), "r"(a1), "r"(a2), "r"(a3), "r"(b0), "r"(b1), "f"(0.f));
}
__device__ __forceinline__ void mma16(float* d, uint32_t a0, uint32_t a1, uint32_t a2, uint32_t a3, uint32_t b0, uint32_t b1) {
    asm("mma.sync.aligned.m16n8k16.row.col.f32.bf16.bf16.f32 {%0,%1,%2,%3},{%4,%5,%6,%7},{%8,%9},{%0,%1,%2,%3};"
        : "+f"(d[0]), "+f"(d[1]), "+f"(d[2]), "+f"(d[3]) : "r"(a0), "r"(a1), "r"(a2), "r"(a3), "r"(b0), "r"(b1));
}
__device__ __forceinline__ void mma8(float* d, uint32_t a0, uint32_t a1, uint32_t b0) {
    asm("mma.sync.aligned.m16n8k8.row.col.f32.bf16.bf16.f32 {%0,%1,%2,%3},{%4,%5},{%6},{%0,%1,%2,%3};"
        : "+f"(d[0]), "+f"(d[1]), "+f"(d[2]), "+f"(d[3]) : "r"(a0), "r"(a1), "r"(b0));
}
__device__ __forceinline__ void wg_fence() { asm volatile("wgmma.fence.sync.aligned;" ::: "memory"); }
__device__ __forceinline__ void wg_commit() { asm volatile("wgmma.commit_group.sync.aligned;" ::: "memory"); }
template <int N> __device__ __forceinline__ void wg_wait() { asm volatile("wgmma.wait_group.sync.aligned %0;" ::"n"(N) : "memory"); }
template <int N> __device__ __forceinline__ void pin(float (&d)[N]) {
#pragma unroll
    for (int i = 0; i < N; i++) asm volatile("" : "+f"(d[i])::"memory");
}
#define ACC8(o) "+f"(d[o]), "+f"(d[o + 1]), "+f"(d[o + 2]), "+f"(d[o + 3]), "+f"(d[o + 4]), "+f"(d[o + 5]), "+f"(d[o + 6]), "+f"(d[o + 7])
#define OUT8(o) "=f"(d[o]), "=f"(d[o + 1]), "=f"(d[o + 2]), "=f"(d[o + 3]), "=f"(d[o + 4]), "=f"(d[o + 5]), "=f"(d[o + 6]), "=f"(d[o + 7])
template <int ACC> __device__ __forceinline__ void wgmma48(float (&d)[24], uint32_t a0, uint32_t a1, uint32_t a2, uint32_t a3, uint64_t desc) {
    if (ACC)
        asm volatile("wgmma.mma_async.sync.aligned.m64n48k16.f32.bf16.bf16 "
                     "{%0,%1,%2,%3,%4,%5,%6,%7,%8,%9,%10,%11,%12,%13,%14,%15,%16,%17,%18,%19,%20,%21,%22,%23},{%24,%25,%26,%27},%28,1,1,1,0;"
                     : ACC8(0), ACC8(8), ACC8(16) : "r"(a0), "r"(a1), "r"(a2), "r"(a3), "l"(desc));
    else
        asm volatile("wgmma.mma_async.sync.aligned.m64n48k16.f32.bf16.bf16 "
                     "{%0,%1,%2,%3,%4,%5,%6,%7,%8,%9,%10,%11,%12,%13,%14,%15,%16,%17,%18,%19,%20,%21,%22,%23},{%24,%25,%26,%27},%28,0,1,1,0;"
                     : OUT8(0), OUT8(8), OUT8(16) : "r"(a0), "r"(a1), "r"(a2), "r"(a3), "l"(desc));
}
template <int ACC> __device__ __forceinline__ void wgmma24(float (&d)[12], uint32_t a0, uint32_t a1, uint32_t a2, uint32_t a3, uint64_t desc) {
    if (ACC)
        asm volatile("wgmma.mma_async.sync.aligned.m64n24k16.f32.bf16.bf16 {%0,%1,%2,%3,%4,%5,%6,%7,%8,%9,%10,%11},{%12,%13,%14,%15},%16,1,1,1,0;"
                     : ACC8(0), "+f"(d[8]), "+f"(d[9]), "+f"(d[10]), "+f"(d[11]) : "r"(a0), "r"(a1), "r"(a2), "r"(a3), "l"(desc));
    else
        asm volatile("wgmma.mma_async.sync.aligned.m64n24k16.f32.bf16.bf16 {%0,%1,%2,%3,%4,%5,%6,%7,%8,%9,%10,%11},{%12,%13,%14,%15},%16,0,1,1,0;"
                     : OUT8(0), "=f"(d[8]), "=f"(d[9]), "=f"(d[10]), "=f"(d[11]) : "r"(a0), "r"(a1), "r"(a2), "r"(a3), "l"(desc));
}
template <int ACC> __device__ __forceinline__ void wgmma56(float (&d)[28], const uint32_t* a, uint64_t desc) {
    if (ACC)
        asm volatile("wgmma.mma_async.sync.aligned.m64n56k16.f32.bf16.bf16 "
                     "{%0,%1,%2,%3,%4,%5,%6,%7,%8,%9,%10,%11,%12,%13,%14,%15,%16,%17,%18,%19,%20,%21,%22,%23,%24,%25,%26,%27},{%28,%29,%30,%31},%32,1,1,1,0;"
                     : ACC8(0), ACC8(8), ACC8(16), "+f"(d[24]), "+f"(d[25]), "+f"(d[26]), "+f"(d[27])
                     : "r"(a[0]), "r"(a[1]), "r"(a[2]), "r"(a[3]), "l"(desc));
    else
        asm volatile("wgmma.mma_async.sync.aligned.m64n56k16.f32.bf16.bf16 "
                     "{%0,%1,%2,%3,%4,%5,%6,%7,%8,%9,%10,%11,%12,%13,%14,%15,%16,%17,%18,%19,%20,%21,%22,%23,%24,%25,%26,%27},{%28,%29,%30,%31},%32,0,1,1,0;"
                     : OUT8(0), OUT8(8), OUT8(16), "=f"(d[24]), "=f"(d[25]), "=f"(d[26]), "=f"(d[27])
                     : "r"(a[0]), "r"(a[1]), "r"(a[2]), "r"(a[3]), "l"(desc));
}
__device__ __forceinline__ uint64_t desc_tab(uint32_t a) { return (uint64_t)((a & 0x3FFFF) >> 4) | ((uint64_t)(768 >> 4) << 16) | ((uint64_t)(128 >> 4) << 32); }

__device__ __forceinline__ void staged(uint32_t bar, int lane) {
    fence_async_s();
    __syncwarp();
    if (lane == 0) mbar_arrive(bar);
}

__device__ __forceinline__ void wgen(uint32_t win, uint32_t tab, unsigned char* wt, int c, int lane) {
    uint32_t A[28];
    int mi = lane >> 3, rr = lane & 7;
    int L = 12 * (mi & 1) + c;
#pragma unroll
    for (int s = 0; s < 7; s++) {
        int u = s < 6 ? s / 3 : mi >> 1;
        int tap = s < 6 ? 16 * (s % 3) + 8 * (mi >> 1) + rr : 48;
        int line = 3 * tap + (L >> 3);
        uint32_t ad = win + u * WPIECE + line * 128 + (((L ^ line) & 7) << 4);
        asm volatile("ldmatrix.sync.aligned.m8n8.x4.trans.shared.b16 {%0,%1,%2,%3},[%4];"
                     : "=r"(A[4 * s]), "=r"(A[4 * s + 1]), "=r"(A[4 * s + 2]), "=r"(A[4 * s + 3]) : "r"(ad));
    }
    float d0[24], d1[24];
    uint64_t ds = desc_tab(tab);
    wg_fence();
    wgmma48<0>(d0, A[0], A[1], A[2], A[3], ds);
    wgmma48<0>(d1, A[12], A[13], A[14], A[15], ds);
    wgmma48<1>(d0, A[4], A[5], A[6], A[7], ds + 96);
    wgmma48<1>(d1, A[16], A[17], A[18], A[19], ds + 96);
    wgmma48<1>(d0, A[8], A[9], A[10], A[11], ds + 192);
    wgmma48<1>(d1, A[20], A[21], A[22], A[23], ds + 192);
    wgmma48<1>(d0, A[24], A[25], A[26], A[27], ds + 336);
    wgmma48<1>(d1, A[24], A[25], A[26], A[27], ds + 288);
    wg_commit();
    wg_wait<0>();
    pin(d0); pin(d1);
    int g = lane >> 2, q = lane & 3;
    unsigned char* p = wt + (size_t)q * 36864 + (8 * c + g) * 16;
#pragma unroll
    for (int nb = 0; nb < 6; nb++) {
        if (nb < 5 || q < 2) {
            uint4 v;
            v.x = pk(d0[4 * nb], d0[4 * nb + 2]); v.y = pk(d0[4 * nb + 1], d0[4 * nb + 3]);
            v.z = pk(d1[4 * nb], d1[4 * nb + 2]); v.w = pk(d1[4 * nb + 1], d1[4 * nb + 3]);
            *reinterpret_cast<uint4*>(p + (size_t)nb * 4 * 36864) = v;
        }
    }
}

__device__ __forceinline__ void p1_unit(uint32_t blk, uint32_t cst, int wg, int wq, int lane) {
    int g = lane >> 2, q = lane & 3;
    uint32_t T[20];
#pragma unroll
    for (int v = 0; v < 5; v++) { uint4 x = lds128(cst + C_P1A + (v * 32 + lane) * 16); T[4 * v] = x.x; T[4 * v + 1] = x.y; T[4 * v + 2] = x.z; T[4 * v + 3] = x.w; }
    uint32_t P[6][3][4];
    const uint32_t a0 = blk + g * 512 + (2 * q + (g & 1)) * 64 + ((wq ^ q) << 4), a1 = a0 ^ 64;
    const uint32_t sel0 = (g & 1) ? 0x1054 : 0x5410, sel1 = sel0 + 0x2222;
    uint32_t vv[2][3][2][4];
    auto ldv = [&](int nu) {
        const int ro = (nu == 0 ? 6 : (nu == 1 ? 14 : 0)) * 512;
#pragma unroll
        for (int t = 0; t < 3; t++)
#pragma unroll
            for (int e = 0; e < 2; e++) {
                uint4 x = lds128((e ? a1 : a0) + t * 11264 + ro);
                vv[nu & 1][t][e][0] = x.x; vv[nu & 1][t][e][1] = x.y; vv[nu & 1][t][e][2] = x.z; vv[nu & 1][t][e][3] = x.w;
            }
    };
    ldv(0);
#pragma unroll
    for (int nu = 0; nu < 3; nu++) {
        if (nu < 2) ldv(nu + 1);
        auto& v = vv[nu & 1];
#pragma unroll
        for (int ch = 0; ch < 4; ch++) {
            const uint32_t sel = (ch & 1) ? sel1 : sel0;
            uint32_t b[2][3];
#pragma unroll
            for (int hf = 0; hf < 2; hf++)
#pragma unroll
                for (int t = 0; t < 3; t++) b[hf][t] = __byte_perm(v[t][0][(ch >> 1) + 2 * hf], v[t][1][(ch >> 1) + 2 * hf], sel);
            float d1[4];
            mma16z(d1, T[12], T[13], T[14], T[15], b[0][0], b[1][0]);
#pragma unroll
            for (int hf = 0; hf < 2; hf++) {
                float d0[4];
                mma16z(d0, T[0], T[1], T[2], T[3], b[hf][1], b[hf][2]);
                mma8(d0, T[16], T[17], b[hf][0]);
                mma16(d1, T[4 + 4 * hf], T[5 + 4 * hf], T[6 + 4 * hf], T[7 + 4 * hf], b[hf][1], b[hf][2]);
                P[(ch >> 1) + 2 * hf][nu][ch & 1] = pk(d0[0], d0[1]);
                P[(ch >> 1) + 2 * hf][nu][2 + (ch & 1)] = pk(d0[2], d0[3]);
            }
            P[4 + (ch >> 1)][nu][ch & 1] = pk(d1[0], d1[1]);
            P[4 + (ch >> 1)][nu][2 + (ch & 1)] = pk(d1[2], d1[3]);
        }
#pragma unroll
        for (int pb = 0; pb < 6; pb++) asm volatile("" : "+r"(P[pb][nu][0]), "+r"(P[pb][nu][1]), "+r"(P[pb][nu][2]), "+r"(P[pb][nu][3]));
        if (SPLIT >> nu & 1) mbar_wait(cst + (O_BAR - O_C) + 8 * BC);
    }
    const uint64_t ds = desc_tab(cst + C_P1B);
    float d[4][12];
    auto issue = [&](float (&dd)[12], int pb, int hf) {
        wgmma24<0>(dd, P[pb][0][0], P[pb][0][1], P[pb][0][2], P[pb][0][3], ds + 24 * hf);
        wgmma24<1>(dd, P[pb][1][0], P[pb][1][1], P[pb][1][2], P[pb][1][3], ds + 24 * hf + 96);
        wgmma24<1>(dd, P[pb][2][0], P[pb][2][1], P[pb][2][2], P[pb][2][3], ds + 24 * hf + 192);
    };
    wg_fence(); issue(d[0], 4, 0); issue(d[1], 5, 0); issue(d[2], 4, 1); issue(d[3], 5, 1); wg_commit();
    bar_sync(1 + wg, 128);
    asm volatile("" : "+r"(g), "+r"(q));
    wg_wait<0>(); pin(d[0]); pin(d[1]); pin(d[2]); pin(d[3]);
    if (g < 6) {
        const int r0 = (8 + (g >> 1)) * 11 + q;
        const uint32_t b8 = blk + 8 * (g & 1);
        const uint32_t re = b8 + r0 * 128 + (((wq ^ r0) & 7) << 4), im = b8 + (r0 + 121) * 128 + (((wq ^ (r0 + 1)) & 7) << 4);
#pragma unroll
        for (int k = 0; k < 12; k++) {
            const int hf = k / 6, i = 4 * ((k % 6) >> 1) + (k & 1);
            uint32_t a = (((k & 2) ? im : re) ^ (((k ^ (k >> 2)) & 1) << 6)) + 512 * (k >> 2);
            if (k < 8 || q < 3) sts64(a, pk(d[2 * hf][i], d[2 * hf][i + 2]), pk(d[2 * hf + 1][i], d[2 * hf + 1][i + 2]));
        }
    }
    const int r0 = fwmap0(g) * 11 + q;
    const uint32_t re = blk + r0 * 128 + (((wq ^ r0) & 7) << 4), im = blk + (r0 + 121) * 128 + (((wq ^ (r0 + 1)) & 7) << 4);
#pragma unroll
    for (int hf = 0; hf < 2; hf++) {
        wg_fence(); issue(d[0], 0, hf); issue(d[1], 1, hf); issue(d[2], 2, hf); issue(d[3], 3, hf); wg_commit();
        wg_wait<0>(); pin(d[0]); pin(d[1]); pin(d[2]); pin(d[3]);
#pragma unroll
        for (int k = 6 * hf; k < 6 * hf + 6; k++) {
            const int i = 4 * ((k % 6) >> 1) + (k & 1);
            uint32_t a = (((k & 2) ? im : re) ^ (((k ^ (k >> 2)) & 1) << 6)) + 512 * (k >> 2);
            if (k < 8 || q < 3) sts128(a, pk(d[0][i], d[0][i + 2]), pk(d[1][i], d[1][i + 2]), pk(d[2][i], d[2][i + 2]), pk(d[3][i], d[3][i + 2]));
        }
    }
}

__device__ __forceinline__ void p3_unit(uint32_t blk, uint32_t cst, int wg, int wq, int lane) {
    int g = lane >> 2, q = lane & 3;
    uint32_t T[12];
#pragma unroll
    for (int v = 0; v < 3; v++) { uint4 x = lds128(cst + C_P3 + (v * 32 + lane) * 16); T[4 * v] = x.x; T[4 * v + 1] = x.y; T[4 * v + 2] = x.z; T[4 * v + 3] = x.w; }
    uint32_t ad[3][3];
#pragma unroll
    for (int nu = 0; nu < 3; nu++)
#pragma unroll
        for (int ka = 0; ka < 3; ka++) {
            int r = p3cs(nu, g) * 121 + p3fw(nu, g) * 11 + min(4 * ka + q, 10);
            ad[nu][ka] = blk + r * 128 + ((((2 * wq) ^ r) & 7) << 4);
        }
    uint32_t o[2][4][4];
#pragma unroll
    for (int h = 0; h < 2; h++) {
        uint32_t z[3][3][4];
#pragma unroll
        for (int nu = 0; nu < 3; nu++)
#pragma unroll
            for (int ka = 0; ka < 3; ka++) {
                uint4 x = lds128(ad[nu][ka] ^ (h << 4));
                z[nu][ka][0] = x.x; z[nu][ka][1] = x.y; z[nu][ka][2] = x.z; z[nu][ka][3] = x.w;
            }
#pragma unroll
        for (int j = 0; j < 2; j++) {
            float d2[2][2][4];
#pragma unroll
            for (int e = 0; e < 2; e++) {
                const int ch = 2 * j + e;
                uint32_t P[3][2];
#pragma unroll
                for (int nu = 0; nu < 3; nu++) {
                    float d[4];
                    mma16z(d, T[0], T[1], T[2], T[3], z[nu][0][ch], z[nu][1][ch]);
                    mma8(d, T[4], T[5], z[nu][2][ch]);
                    P[nu][0] = pk(d[0], d[1]); P[nu][1] = pk(d[2], d[3]);
                }
#pragma unroll
                for (int be = 0; be < 2; be++) {
                    mma16z(d2[e][be], P[0][0], P[0][1], P[1][0], P[1][1], T[8 + 2 * be], T[9 + 2 * be]);
                    mma8(d2[e][be], P[2][0], P[2][1], T[6 + be]);
                }
            }
#pragma unroll
            for (int be = 0; be < 2; be++)
#pragma unroll
                for (int k = 0; k < 4; k++) o[be][k][2 * h + j] = pk(d2[0][be][k], d2[1][be][k]);
        }
    }
    bar_sync(1 + wg, 128);
    const int p = 4 * g + q;
    const uint32_t a = blk + p * 64 + ((wq ^ ((p >> 1) & 3)) << 4);
#pragma unroll
    for (int be = 0; be < 2; be++)
#pragma unroll
        for (int k = 0; k < 4; k++)
            sts128(a + (2 * be + (k & 1)) * 4096 + (k >> 1) * 2048, o[be][k][0], o[be][k][1], o[be][k][2], o[be][k][3]);
}

__global__ void __launch_bounds__(512, 1) fftconv_kernel(const __grid_constant__ Maps mp) {
    extern __shared__ __align__(1024) unsigned char smraw[];
    const uint32_t sm = s2u(smraw);
    const uint32_t bar = sm + O_BAR;
    const int tid = threadIdx.x, lane = tid & 31, warp = tid >> 5, cta = blockIdx.x;
    const bool has4 = cta < NU - 4 * NCTA;
    const int fp = cta - (NCTA - NFP);
    TR(tid < 384 ? warp >> 2 : warp - 9, 0);
    if (warp == 12) {
        for (int i = lane; i < NBAR; i += 32) mbar_init(bar + 8 * i, i >= BDN ? 1 : (i >= BRD || i == BWD ? 4 : (i >= BPE ? 12 : 1)));
        fence_async_s();
    }
    __syncthreads();

    if (warp >= 12) {
        asm volatile("setmaxnreg.dec.sync.aligned.u32 32;");
        if (lane == 0) {
            if (warp == 12) {
                auto load_x = [&](int r, int off) {
                    int u = r * NCTA + cta, tile = u / 3, cg = u - 3 * tile, th = tile / 14, tw = tile - 14 * th;
                    uint32_t b = bar + 8 * (BX + r), dst = sm + off;
                    int h6 = th ? 16 * th - 6 : 218;
                    mbar_expect(b, BLK);
                    for (int t = 0; t < 3; t++) {
                        int w0 = 16 * tw - 8 + 8 * t; if (w0 < 0) w0 += 224;
                        tma_ld3(dst + t * 11264, &mp.x6, b, 32 * cg, w0, h6);
                        tma_ld3(dst + t * 11264 + 3072, &mp.x16, b, 32 * cg, w0, 16 * th);
                    }
                };
                const int fw = cta % 11, ip = cta / 11, pr = 8 * (ip >> 1) + 2 * (ip & 1);
                mbar_expect(bar + 8 * BW, 2 * 18816 + WT_BYTES);
                tma_ld3(sm + O_W0, &mp.w, bar + 8 * BW, 0, 3 * pr, 0);
                tma_ld3(sm + O_W0 + WPIECE, &mp.w, bar + 8 * BW, 0, 3 * pr + 12, 0);
                bulk_ld(sm + O_WT, &g_wtab[fw], WT_BYTES, bar + 8 * BW);
                mbar_expect(bar + 8 * BC, C_BYTES);
                bulk_ld(sm + O_C, &g_ctab, C_BYTES, bar + 8 * BC);
                load_x(0, O_B0);
                load_x(1, O_B1);
                mbar_expect(bar + 8 * (BW + 1), 2 * 18816);
                tma_ld3(sm + O_W1, &mp.w, bar + 8 * (BW + 1), 0, 3 * pr + 3, 0);
                tma_ld3(sm + O_W1 + WPIECE, &mp.w, bar + 8 * (BW + 1), 0, 3 * pr + 15, 0);
                load_x(2, O_B2);
                load_x(3, O_B3);
                TR(3, 1);
                mbar_wait(bar + 8 * BWD);
                if (has4) load_x(4, O_B4);
                TR(3, 2);
                if (fp >= 0) {
#pragma unroll 1
                    for (int s = 0; s < 7; s++) {
                        if (s == 2) mbar_wait(bar + 8 * BDN);
                        if (s >= 3) mbar_wait(bar + 8 * (BPE + s - 3));
                        poll(CX + s, 84);
                        fence_async_g();
                        mbar_expect(bar + 8 * (BPF + s), STG);
                        tma_ld5(sm + O_IN + (s % 3) * STG, &mp.p2l, bar + 8 * (BPF + s), 0, 0, 28 * s, 0, fp);
                        TR(3, 3 + s);
                        if (s == 0) { poll(CW + fp / 11, 12); mbar_arrive(bar + 8 * BWT); TR(3, 15); }
                    }
                }
#pragma unroll 1
                for (int r = 0; r < (has4 ? 5 : 4); r++) {
                    int u = r * NCTA + cta, tile = u / 3, cg = u - 3 * tile;
                    if (r < 2 || (r == 2 && has4)) mbar_wait(bar + 8 * (BDN + 11 * r + 1));
                    if (r == 3 && fp >= 0) { mbar_wait(bar + 8 * (BPE + 4)); mbar_wait(bar + 8 * (BPE + 5)); }
                    if (r == 4) {
                        if (fp >= 0) { for (int w = 0; w < 3; w++) mbar_wait(bar + 8 * (BDN + 11 * w + 7)); }
                        else mbar_wait(bar + 8 * (BDN + 11));
                    }
                    poll(CY + 3 * (tile / 28) + cg, NFP);
                    fence_async_g();
                    int off = r == 0 ? O_B2 : (r == 1 ? O_B3 : (r == 2 ? O_B4 : (r == 3 ? O_Z3 : O_B1)));
                    mbar_expect(bar + 8 * (BZ + r), SLAB);
                    tma_ld2(sm + off, &mp.s, bar + 8 * (BZ + r), 0, u * 242);
                    TR(3, 10 + r);
                }
                if (atomicAdd(&g_cnt[CD * 32], 1u) == NCTA - 1)
                    for (int i = 0; i < NCNT; i++) g_cnt[i * 32] = 0;
            } else {
                const int w = warp - 13;
                const uint32_t rd = bar + 8 * (BRD + 11 * w), dn = bar + 8 * (BDN + 11 * w);
#pragma unroll 1
                for (int j = 0; j < 2; j++) {
                    if (w == 2 && j == 0) { mbar_wait(rd); signal(CW + cta % 11); TR(4 + w, 1); continue; }
                    if (w == 2 && !has4) break;
                    int r = w + 2 * j, u = r * NCTA + cta;
                    mbar_wait(rd + 8 * j);
                    tma_st2(&mp.s, sm + (r < 4 ? O_B0 + r * BLK : O_B4), 0, u * 242);
                    bulk_commit_wait();
                    mbar_arrive(dn + 8 * j);
                    TR(4 + w, 12 + j);
                    signal(CX + u / 84);
                    TR(4 + w, 1 + j);
                }
                if (fp >= 0) {
#pragma unroll 1
                    for (int s = 0; s < 7; s++) {
                        mbar_wait(rd + 8 * (2 + s));
                        tma_st5(&mp.p2s, sm + O_OUT + (s & 1) * STG + w * 7168, 0, 0, 28 * s, w, fp);
                        bulk_commit_wait();
                        mbar_arrive(dn + 8 * (2 + s));
                        TR(4 + w, 14 + s);
                        signal(CY + 3 * s + w);
                        TR(4 + w, 3 + s);
                    }
                }
#pragma unroll 1
                for (int j = 0; j < 2; j++) {
                    int r = w + 3 * j;
                    if (r == 5 || (r == 4 && !has4)) break;
                    int u = r * NCTA + cta, tile = u / 3, cg = u - 3 * tile, th = tile / 14, tw = tile - 14 * th;
                    int off = r == 0 ? O_B2 : (r == 1 ? O_B3 : (r == 2 ? O_B4 : (r == 3 ? O_Z3 : O_B1)));
                    mbar_wait(rd + 8 * (9 + j));
                    tma_st4(&mp.y, sm + off, 32 * cg, 0, 16 * th, 4 * tw);
                    bulk_commit_wait();
                    TR(4 + w, 10 + j);
                }
            }
        }
    } else {
        asm volatile("setmaxnreg.inc.sync.aligned.u32 160;");
        const int wg = warp >> 2, wq = warp & 3;
        const uint32_t rd = bar + 8 * (BRD + 11 * wg), dn = bar + 8 * (BDN + 11 * wg);
        if (wg == 2) {
            const int fw = cta % 11, ip = cta / 11;
#pragma unroll 1
            for (int it = 0; it < 6; it++) {
                int hi = it >= 3;
                mbar_wait(bar + 8 * (BW + hi));
                if (it == 0) TR(2, 1);
                wgen(sm + (hi ? O_W1 : O_W0), sm + O_WT, g_Wt + (size_t)fw * 22 * 36864 + (2 * ip + hi) * 1536, 4 * (it - 3 * hi) + wq, lane);
            }
            __syncwarp();
            if (lane == 0) { mbar_arrive(bar + 8 * BWD); mbar_arrive(rd); }
            TR(2, 2);
        }
        mbar_wait(bar + 8 * BC);
#pragma unroll 1
        for (int j = (wg == 2); j < 2; j++) {
            int r = wg + 2 * j;
            if (r == 4 && !has4) break;
            mbar_wait(bar + 8 * (BX + r));
            TR(wg, 1 + 2 * j);
            p1_unit(sm + (r < 4 ? O_B0 + r * BLK : O_B4), sm + O_C, wg, wq, lane);
            staged(rd + 8 * j, lane);
            TR(wg, 2 + 2 * j);
        }
        if (fp >= 0) {
            uint32_t Wf[48];
            mbar_wait(bar + 8 * BWT);
            TR(wg, 5);
            const uint4* p = reinterpret_cast<const uint4*>(g_Wt + (size_t)fp * 73728 + (lane & 3) * 1536 + (8 * warp + (lane >> 2)) * 16);
#pragma unroll
            for (int k = 0; k < 12; k++) { uint4 x = __ldcg(p + k * 384); Wf[4 * k] = x.x; Wf[4 * k + 1] = x.y; Wf[4 * k + 2] = x.z; Wf[4 * k + 3] = x.w; }
            const int g = lane >> 2, q = lane & 3, ck = 2 * wq + (g >> 2);
            const uint32_t o0 = sm + O_OUT + wg * 7168 + (2 * q) * 128 + ((ck ^ (2 * q)) << 4) + (g & 3) * 4;
            int buf = 0;
#pragma unroll 1
            for (int s = 0; s < 7; s++) {
                float dp[28], dm[28];
                uint64_t ds = (uint64_t)(((sm + O_IN + buf * STG) & 0x3FFFF) >> 4) | (1ull << 16) | ((uint64_t)(1024 >> 4) << 32) | (1ull << 62);
                buf = buf == 2 ? 0 : buf + 1;
                mbar_wait(bar + 8 * (BPF + s));
                TR(wg, 20 + s);
                wg_fence();
                wgmma56<0>(dp, &Wf[0], ds);
                wgmma56<0>(dm, &Wf[24], ds + 4);
#pragma unroll
                for (int ks = 1; ks < 6; ks++) {
                    wgmma56<1>(dp, &Wf[4 * ks], ds + (ks >> 1) * (7168 >> 4) + (ks & 1) * 2);
                    wgmma56<1>(dm, &Wf[24 + 4 * ks], ds + (ks >> 1) * (7168 >> 4) + (ks & 1) * 2 + 4);
                }
                wg_commit();
                mbar_wait(s >= 2 ? dn + 8 * s : bar + 8 * (BDN + 11 * s));
                wg_wait<0>();
                pin(dp); pin(dm);
                if (lane == 0) mbar_arrive(bar + 8 * (BPE + s));
                const uint32_t a0 = o0 + (s & 1) * STG, a1 = (a0 + 128) ^ 16;
#pragma unroll
                for (int nb = 0; nb < 7; nb++) {
                    float pr = dp[4 * nb] - dp[4 * nb + 3], pi = dp[4 * nb + 1] + dp[4 * nb + 2];
                    float mr = dm[4 * nb] - dm[4 * nb + 3], mi = dm[4 * nb + 1] + dm[4 * nb + 2];
                    sts32(a0 + nb * 1024, pk(pr + mr, pi - mi));
                    sts32(a1 + nb * 1024, pk(pi + mi, mr - pr));
                }
                staged(rd + 8 * (2 + s), lane);
                TR(wg, 6 + s);
            }
        }
#pragma unroll 1
        for (int j = 0; j < 2; j++) {
            int r = wg + 3 * j;
            if (r == 5 || (r == 4 && !has4)) break;
            int off = r == 0 ? O_B2 : (r == 1 ? O_B3 : (r == 2 ? O_B4 : (r == 3 ? O_Z3 : O_B1)));
            mbar_wait(bar + 8 * (BZ + r));
            TR(wg, 13 + 2 * j);
            p3_unit(sm + off, sm + O_C, wg, wq, lane);
            staged(rd + 8 * (9 + j), lane);
            TR(wg, 14 + 2 * j);
        }
    }
}

typedef CUresult (*EncFn)(CUtensorMap*, CUtensorMapDataType, cuuint32_t, void*, const cuuint64_t*, const cuuint64_t*, const cuuint32_t*,
                          const cuuint32_t*, CUtensorMapInterleave, CUtensorMapSwizzle, CUtensorMapL2promotion, CUtensorMapFloatOOBfill);

void enc(EncFn f, CUtensorMap* m, void* p, int rank, const cuuint64_t* dims, const cuuint64_t* strides, const cuuint32_t* box,
         CUtensorMapSwizzle sw, CUtensorMapL2promotion pr = CU_TENSOR_MAP_L2_PROMOTION_NONE) {
    cuuint32_t es[5] = {1, 1, 1, 1, 1};
    f(m, CU_TENSOR_MAP_DATA_TYPE_BFLOAT16, rank, p, dims, strides, box, es, CU_TENSOR_MAP_INTERLEAVE_NONE, sw, pr, CU_TENSOR_MAP_FLOAT_OOB_FILL_NONE);
}

}

extern "C" void kernel_launch(void* const* d_in, const int* in_sizes, int n_in, void* d_out, int out_size) {
    void* fn = nullptr; cudaDriverEntryPointQueryResult qr;
    cudaGetDriverEntryPoint("cuTensorMapEncodeTiled", &fn, cudaEnableDefault, &qr);
    EncFn f = (EncFn)fn;
    void* pS; cudaGetSymbolAddress(&pS, g_S);
    Maps mp;
    {
        cuuint64_t d[3] = {96, 224, 224}, s[2] = {192, 43008};
        cuuint32_t b6[3] = {32, 8, 6}, b16[3] = {32, 8, 16};
        enc(f, &mp.x6, d_in[0], 3, d, s, b6, CU_TENSOR_MAP_SWIZZLE_64B);
        enc(f, &mp.x16, d_in[0], 3, d, s, b16, CU_TENSOR_MAP_SWIZZLE_64B);
    }
    { cuuint64_t d[4] = {96, 4, 224, 56}, s[3] = {192, 43008, 768}; cuuint32_t b[4] = {32, 4, 16, 4}; enc(f, &mp.y, d_out, 4, d, s, b, CU_TENSOR_MAP_SWIZZLE_64B); }
    { cuuint64_t d[2] = {64, (cuuint64_t)NU * 242}, s[1] = {128}; cuuint32_t b[2] = {64, 242}; enc(f, &mp.s, pS, 2, d, s, b, CU_TENSOR_MAP_SWIZZLE_128B); }
    {
        cuuint64_t d[5] = {64, 2, NT, 3, NFP}, s[4] = {121 * 128, 3 * SLAB, SLAB, 128};
        cuuint32_t bl[5] = {64, 2, 28, 3, 1}, bs[5] = {64, 2, 28, 1, 1};
        enc(f, &mp.p2l, pS, 5, d, s, bl, CU_TENSOR_MAP_SWIZZLE_128B);
        enc(f, &mp.p2s, pS, 5, d, s, bs, CU_TENSOR_MAP_SWIZZLE_128B);
    }
    { cuuint64_t d[3] = {64, 144, 49}, s[2] = {128, 18432}; cuuint32_t b[3] = {64, 3, 49}; enc(f, &mp.w, d_in[1], 3, d, s, b, CU_TENSOR_MAP_SWIZZLE_128B); }
    cudaFuncSetAttribute(fftconv_kernel, cudaFuncAttributeMaxDynamicSharedMemorySize, SMEM);
    fftconv_kernel<<<NCTA, 512, SMEM>>>(mp);
}
```

```cpp
#include <cuda_runtime.h>
#include <cuda_bf16.h>
#include <cuda.h>
#include <stdint.h>

#define PREFETCH 1
#define PACE 0
#define LDFENCE 1
#define SPLIT 3
namespace {

constexpr int NCTA = 132;
constexpr int NT = 196;
constexpr int NU = 588;
constexpr int NFP = 121;
constexpr int BLK = 33792;
constexpr int SLAB = 242 * 128;
constexpr int WPIECE = 19456;
constexpr int STG = 21504;
constexpr int O_B4 = 0, O_B0 = 87040, O_B1 = 120832, O_B2 = 154624, O_B3 = 188416;
constexpr int O_W1 = 0, O_W0 = 2 * WPIECE, O_WT = 4 * WPIECE;
constexpr int O_IN = 33792, O_OUT = O_IN + 3 * STG, O_Z3 = O_IN + STG;
constexpr int O_C = 222208, O_BAR = 230912, SMEM = 232448;
constexpr int C_P1A = 0, C_P1B = 2560, C_P3 = 7168, C_BYTES = 8704, WT_BYTES = 6912;
constexpr int BC = 0, BW = 1, BX = 3, BZ = 8, BWT = 13, BWS = 14, BPF = 16, BDN = 23, BPE = 56, BWC = 64, BWR = 65, BRD = 71, NBARG = 13;

constexpr uint16_t LUT_A[11] = {0x3f95, 0x3f92, 0x3f8c, 0x3f83, 0x3f6f, 0x3f53, 0x3f33, 0x3f0f, 0x3ed1, 0x3e7e, 0x3daa};
constexpr uint16_t LUT_B[11] = {0x3fe9, 0x3fe4, 0x3fdb, 0x3fcd, 0x3fbb, 0x3fa5, 0x3f8c, 0x3f60, 0x3f23, 0x3ec7, 0x3e05};
constexpr uint16_t LUT_W[12] = {0x3abb, 0x3ab9, 0x3ab3, 0x3aaa, 0x3a9d, 0x3a8d, 0x3a75, 0x3a4a, 0x3a1b, 0x39d3, 0x3955, 0};
constexpr uint16_t basis(int setb, int f, int a, int sn) {
    if (f < 0 || f > 10 || a < 0 || a > 21) return 0;
    int k = ((2 * f + 1) * (2 * a - 21) - 22 * sn + 88 * 7) % 88;
    if (k > 44) k = 88 - k;
    int neg = 0;
    if (k > 22) { k = 44 - k; neg = 1; }
    return (uint16_t)((setb ? LUT_B[k >> 1] : LUT_A[k >> 1]) | (neg << 15));
}
constexpr uint16_t neg16(uint16_t v) { return v ? (uint16_t)(v ^ 0x8000) : v; }
constexpr uint16_t wcoef(int fw, int fl, int sn, int tap) {
    if (fl > 21) return 0;
    int fh = fl >> 1, kh = tap / 7, kw = tap - 7 * kh;
    int u = (2 * fh + 1) * kh;
    if (fl & 1) u = -u;
    int k = (u + (2 * fw + 1) * kw - 11 * sn + 44 * 4) % 44;
    if (k > 22) k = 44 - k;
    int neg = 0;
    if (k > 11) { k = 22 - k; neg = 1; }
    return (uint16_t)(LUT_W[k] | (neg << 15));
}
__host__ __device__ constexpr int fwmap0(int g) { return (g >> 1) + 4 * (g & 1); }
__host__ __device__ constexpr int p3fw(int nu, int g) { return nu < 2 ? fwmap0(g) : (int)((0x486AA998u >> (4 * g)) & 15); }
__host__ __device__ constexpr int p3cs(int nu, int g) { return nu < 2 ? nu : ((0xCA >> g) & 1); }
constexpr bool p3ok(int nu, int g) { return nu < 2 || (g != 5 && g != 7); }

struct alignas(128) CTab { uint16_t v[C_BYTES / 2]; };
struct alignas(128) WTab { uint16_t v[WT_BYTES / 2]; };
constexpr CTab make_ctab() {
    CTab t{};
    for (int lane = 0; lane < 32; lane++) {
        int g = lane >> 2, q = lane & 3;
        for (int r = 0; r < 18; r++) {
            int quad = r >> 2, j = r & 3, sn = j & 1;
            int set = quad < 3 ? quad : (quad == 3 ? 1 + (j >> 1) : 0);
            int t8 = quad < 3 ? 1 + (j >> 1) : 0;
            int b = 8 * t8 + 2 * q - 2;
            int fw = set == 0 ? fwmap0(g) : (((g & 1) == set - 1) ? 8 + (g >> 1) : -1);
            int o = (C_P1A + (quad * 32 + lane) * 16 + j * 4) / 2;
            t.v[o] = basis(0, fw, b, sn); t.v[o + 1] = basis(0, fw, b + 1, sn);
        }
        for (int r = 0; r < 12; r++) {
            int o = (C_P3 + ((r >> 2) * 32 + lane) * 16 + (r & 3) * 4) / 2;
            if (r < 6) {
                int a = 6 + g + 8 * (r & 1), fh = 4 * (r >> 1) + q;
                t.v[o] = basis(0, fh, a, 0); t.v[o + 1] = basis(0, fh, a, 1);
            } else {
                int be = r < 8 ? r - 6 : (r - 8) >> 1, nu = r < 8 ? 2 : (r & 1);
                int b = 6 + 8 * be + 4 * (g & 1) + (g >> 1);
                t.v[o] = p3ok(nu, 2 * q) ? basis(1, p3fw(nu, 2 * q), b, p3cs(nu, 2 * q)) : 0;
                t.v[o + 1] = p3ok(nu, 2 * q + 1) ? basis(1, p3fw(nu, 2 * q + 1), b, p3cs(nu, 2 * q + 1)) : 0;
            }
        }
    }
    for (int kc = 0; kc < 6; kc++)
        for (int nb = 0; nb < 6; nb++)
            for (int n = 0; n < 8; n++)
                for (int k = 0; k < 8; k++) {
                    int nu = kc >> 1, ds = kc & 1, im = nb & 1, fh = 4 * (nb >> 1) + (n >> 1), mi = n & 1;
                    int a = nu == 0 ? 6 + k : (nu == 1 ? 14 + k : (k < 6 ? k : -1));
                    uint16_t v = basis(0, fh, a, ds ^ im);
                    if (ds != im && (im ? mi : !mi)) v = neg16(v);
                    t.v[C_P1B / 2 + ((kc * 6 + nb) * 8 + n) * 8 + k] = v;
                }
    return t;
}
constexpr WTab make_wtab(int fw) {
    WTab t{};
    for (int nb = 0; nb < 6; nb++)
        for (int n = 0; n < 8; n++) {
            for (int tap = 0; tap < 48; tap++) t.v[(((tap >> 3) * 6 + nb) * 8 + n) * 8 + (tap & 7)] = wcoef(fw, 4 * nb + (n >> 1), n & 1, tap);
            t.v[((7 * 6 + nb) * 8 + n) * 8] = wcoef(fw, 4 * nb + (n >> 1), n & 1, 48);
        }
    return t;
}
__device__ const CTab g_ctab = make_ctab();
__device__ const WTab g_wtab[11] = {make_wtab(0), make_wtab(1), make_wtab(2), make_wtab(3), make_wtab(4), make_wtab(5),
                                    make_wtab(6), make_wtab(7), make_wtab(8), make_wtab(9), make_wtab(10)};

__device__ __align__(1024) unsigned char g_S[(size_t)NU * SLAB];
__device__ __align__(1024) unsigned char g_Wt[(size_t)NFP * 73728];
constexpr int CX = 0, CW = 7, CY = 18, CD = 39, NCNT = 40;
__device__ unsigned g_cnt[NCNT * 32];

struct Maps {
    const unsigned char* ctab; const unsigned char* wtab; const unsigned char* wt; const unsigned char* x; unsigned* cnt;
    alignas(64) CUtensorMap w, x6, x16, wst, s, p2l, p2s, y;
};

#define TR(role, i)

__device__ __forceinline__ uint32_t s2u(const void* p) { return (uint32_t)__cvta_generic_to_shared(p); }
__device__ __forceinline__ void mbar_init(uint32_t b, int c) { asm volatile("mbarrier.init.shared::cta.b64 [%0],%1;" ::"r"(b), "r"(c) : "memory"); }
__device__ __forceinline__ void mbar_expect(uint32_t b, uint32_t tx) { asm volatile("mbarrier.arrive.expect_tx.shared::cta.b64 _,[%0],%1;" ::"r"(b), "r"(tx) : "memory"); }
__device__ __forceinline__ void mbar_arrive(uint32_t b) { asm volatile("mbarrier.arrive.shared::cta.b64 _,[%0];" ::"r"(b) : "memory"); }
__device__ __forceinline__ void mbar_wait(uint32_t b) {
    uint32_t ok; int it = 0;
    do {
        asm volatile("{.reg .pred p; mbarrier.try_wait.parity.shared::cta.b64 p,[%1],0; selp.u32 %0,1,0,p;}" : "=r"(ok) : "r"(b) : "memory");
    } while (!ok && ++it < (1 << 16));
}
__device__ __forceinline__ void signal(unsigned* c) { asm volatile("red.relaxed.gpu.global.add.u32 [%0],1;" ::"l"(c) : "memory"); }
__device__ __forceinline__ void fence_async_s() { asm volatile("fence.proxy.async.shared::cta;" ::: "memory"); }
__device__ __forceinline__ void fence_async_g() { asm volatile("fence.proxy.async.global;" ::: "memory"); }
__device__ __forceinline__ void bulk_ld(uint32_t dst, const void* src, uint32_t bytes, uint32_t bar) {
    asm volatile("cp.async.bulk.shared::cluster.global.mbarrier::complete_tx::bytes [%0],[%1],%2,[%3];" ::"r"(dst), "l"(src), "r"(bytes), "r"(bar) : "memory");
}
__device__ __forceinline__ void tma_ld2(uint32_t dst, const CUtensorMap* m, uint32_t bar, int c0, int c1) {
    asm volatile("cp.async.bulk.tensor.2d.shared::cluster.global.mbarrier::complete_tx::bytes [%0],[%1,{%3,%4}],[%2];" ::"r"(dst), "l"(m), "r"(bar), "r"(c0), "r"(c1) : "memory");
}
__device__ __forceinline__ void tma_ld3(uint32_t dst, const CUtensorMap* m, uint32_t bar, int c0, int c1, int c2) {
    asm volatile("cp.async.bulk.tensor.3d.shared::cluster.global.mbarrier::complete_tx::bytes [%0],[%1,{%3,%4,%5}],[%2];" ::"r"(dst), "l"(m), "r"(bar), "r"(c0), "r"(c1), "r"(c2) : "memory");
}
__device__ __forceinline__ void tma_ld5(uint32_t dst, const CUtensorMap* m, uint32_t bar, int c0, int c1, int c2, int c3, int c4) {
    asm volatile("cp.async.bulk.tensor.5d.shared::cluster.global.mbarrier::complete_tx::bytes [%0],[%1,{%3,%4,%5,%6,%7}],[%2];" ::"r"(dst), "l"(m), "r"(bar), "r"(c0), "r"(c1), "r"(c2), "r"(c3), "r"(c4) : "memory");
}
__device__ __forceinline__ void tma_st2(const CUtensorMap* m, uint32_t src, int c0, int c1) {
    asm volatile("cp.async.bulk.tensor.2d.global.shared::cta.bulk_group [%0,{%2,%3}],[%1];" ::"l"(m), "r"(src), "r"(c0), "r"(c1) : "memory");
}
__device__ __forceinline__ void tma_st4(const CUtensorMap* m, uint32_t src, int c0, int c1, int c2, int c3) {
    asm volatile("cp.async.bulk.tensor.4d.global.shared::cta.bulk_group [%0,{%2,%3,%4,%5}],[%1];" ::"l"(m), "r"(src), "r"(c0), "r"(c1), "r"(c2), "r"(c3) : "memory");
}
__device__ __forceinline__ void tma_st5(const CUtensorMap* m, uint32_t src, int c0, int c1, int c2, int c3, int c4) {
    asm volatile("cp.async.bulk.tensor.5d.global.shared::cta.bulk_group [%0,{%2,%3,%4,%5,%6}],[%1];" ::"l"(m), "r"(src), "r"(c0), "r"(c1), "r"(c2), "r"(c3), "r"(c4) : "memory");
}
__device__ __forceinline__ void bulk_commit_wait() { asm volatile("cp.async.bulk.commit_group;\n cp.async.bulk.wait_group 0;" ::: "memory"); }
__device__ __forceinline__ void bar_sync(int id, int n) { asm volatile("bar.sync %0,%1;" ::"r"(id), "r"(n) : "memory"); }

__device__ __forceinline__ uint4 lds128(uint32_t a) {
    uint4 v; asm volatile("ld.shared.v4.u32 {%0,%1,%2,%3},[%4];" : "=r"(v.x), "=r"(v.y), "=r"(v.z), "=r"(v.w) : "r"(a)); return v;
}
__device__ __forceinline__ void sts128(uint32_t a, uint32_t x, uint32_t y, uint32_t z, uint32_t w) {
    asm volatile("st.shared.v4.u32 [%0],{%1,%2,%3,%4};" ::"r"(a), "r"(x), "r"(y), "r"(z), "r"(w) : "memory");
}
__device__ __forceinline__ void sts64(uint32_t a, uint32_t x, uint32_t y) { asm volatile("st.shared.v2.u32 [%0],{%1,%2};" ::"r"(a), "r"(x), "r"(y) : "memory"); }
__device__ __forceinline__ void sts32(uint32_t a, uint32_t x) { asm volatile("st.shared.u32 [%0],%1;" ::"r"(a), "r"(x) : "memory"); }
__device__ __forceinline__ uint32_t pk(float lo, float hi) { uint32_t r; asm("cvt.rn.bf16x2.f32 %0,%1,%2;" : "=r"(r) : "f"(hi), "f"(lo)); return r; }

__device__ __forceinline__ void mma16z(float* d, uint32_t a0, uint32_t a1, uint32_t a2, uint32_t a3, uint32_t b0, uint32_t b1) {
    asm("mma.sync.aligned.m16n8k16.row.col.f32.bf16.bf16.f32 {%0,%1,%2,%3},{%4,%5,%6,%7},{%8,%9},{%10,%10,%10,%10};"
        : "=f"(d[0]), "=f"(d[1]), "=f"(d[2]), "=f"(d[3]) : "r"(a0), "r"(a1), "r"(a2), "r"(a3), "r"(b0), "r"(b1), "f"(0.f));
}
__device__ __forceinline__ void mma16(float* d, uint32_t a0, uint32_t a1, uint32_t a2, uint32_t a3, uint32_t b0, uint32_t b1) {
    asm("mma.sync.aligned.m16n8k16.row.col.f32.bf16.bf16.f32 {%0,%1,%2,%3},{%4,%5,%6,%7},{%8,%9},{%0,%1,%2,%3};"
        : "+f"(d[0]), "+f"(d[1]), "+f"(d[2]), "+f"(d[3]) : "r"(a0), "r"(a1), "r"(a2), "r"(a3), "r"(b0), "r"(b1));
}
__device__ __forceinline__ void mma8(float* d, uint32_t a0, uint32_t a1, uint32_t b0) {
    asm("mma.sync.aligned.m16n8k8.row.col.f32.bf16.bf16.f32 {%0,%1,%2,%3},{%4,%5},{%6},{%0,%1,%2,%3};"
        : "+f"(d[0]), "+f"(d[1]), "+f"(d[2]), "+f"(d[3]) : "r"(a0), "r"(a1), "r"(b0));
}
__device__ __forceinline__ void wg_fence() { asm volatile("wgmma.fence.sync.aligned;" ::: "memory"); }
__device__ __forceinline__ void wg_commit() { asm volatile("wgmma.commit_group.sync.aligned;" ::: "memory"); }
template <int N> __device__ __forceinline__ void wg_wait() { asm volatile("wgmma.wait_group.sync.aligned %0;" ::"n"(N) : "memory"); }
template <int N> __device__ __forceinline__ void pin(float (&d)[N]) {
#pragma unroll
    for (int i = 0; i < N; i++) asm volatile("" : "+f"(d[i])::"memory");
}
#define ACC8(o) "+f"(d[o]), "+f"(d[o + 1]), "+f"(d[o + 2]), "+f"(d[o + 3]), "+f"(d[o + 4]), "+f"(d[o + 5]), "+f"(d[o + 6]), "+f"(d[o + 7])
#define OUT8(o) "=f"(d[o]), "=f"(d[o + 1]), "=f"(d[o + 2]), "=f"(d[o + 3]), "=f"(d[o + 4]), "=f"(d[o + 5]), "=f"(d[o + 6]), "=f"(d[o + 7])
template <int ACC> __device__ __forceinline__ void wgmma48(float (&d)[24], uint32_t a0, uint32_t a1, uint32_t a2, uint32_t a3, uint64_t desc) {
    if (ACC)
        asm volatile("wgmma.mma_async.sync.aligned.m64n48k16.f32.bf16.bf16 "
                     "{%0,%1,%2,%3,%4,%5,%6,%7,%8,%9,%10,%11,%12,%13,%14,%15,%16,%17,%18,%19,%20,%21,%22,%23},{%24,%25,%26,%27},%28,1,1,1,0;"
                     : ACC8(0), ACC8(8), ACC8(16) : "r"(a0), "r"(a1), "r"(a2), "r"(a3), "l"(desc));
    else
        asm volatile("wgmma.mma_async.sync.aligned.m64n48k16.f32.bf16.bf16 "
                     "{%0,%1,%2,%3,%4,%5,%6,%7,%8,%9,%10,%11,%12,%13,%14,%15,%16,%17,%18,%19,%20,%21,%22,%23},{%24,%25,%26,%27},%28,0,1,1,0;"
                     : OUT8(0), OUT8(8), OUT8(16) : "r"(a0), "r"(a1), "r"(a2), "r"(a3), "l"(desc));
}
template <int ACC> __device__ __forceinline__ void wgmma24(float (&d)[12], uint32_t a0, uint32_t a1, uint32_t a2, uint32_t a3, uint64_t desc) {
    if (ACC)
        asm volatile("wgmma.mma_async.sync.aligned.m64n24k16.f32.bf16.bf16 {%0,%1,%2,%3,%4,%5,%6,%7,%8,%9,%10,%11},{%12,%13,%14,%15},%16,1,1,1,0;"
                     : ACC8(0), "+f"(d[8]), "+f"(d[9]), "+f"(d[10]), "+f"(d[11]) : "r"(a0), "r"(a1), "r"(a2), "r"(a3), "l"(desc));
    else
        asm volatile("wgmma.mma_async.sync.aligned.m64n24k16.f32.bf16.bf16 {%0,%1,%2,%3,%4,%5,%6,%7,%8,%9,%10,%11},{%12,%13,%14,%15},%16,0,1,1,0;"
                     : OUT8(0), "=f"(d[8]), "=f"(d[9]), "=f"(d[10]), "=f"(d[11]) : "r"(a0), "r"(a1), "r"(a2), "r"(a3), "l"(desc));
}
template <int ACC> __device__ __forceinline__ void wgmma56(float (&d)[28], const uint32_t* a, uint64_t desc) {
    if (ACC)
        asm volatile("wgmma.mma_async.sync.aligned.m64n56k16.f32.bf16.bf16 "
                     "{%0,%1,%2,%3,%4,%5,%6,%7,%8,%9,%10,%11,%12,%13,%14,%15,%16,%17,%18,%19,%20,%21,%22,%23,%24,%25,%26,%27},{%28,%29,%30,%31},%32,1,1,1,0;"
                     : ACC8(0), ACC8(8), ACC8(16), "+f"(d[24]), "+f"(d[25]), "+f"(d[26]), "+f"(d[27])
                     : "r"(a[0]), "r"(a[1]), "r"(a[2]), "r"(a[3]), "l"(desc));
    else
        asm volatile("wgmma.mma_async.sync.aligned.m64n56k16.f32.bf16.bf16 "
                     "{%0,%1,%2,%3,%4,%5,%6,%7,%8,%9,%10,%11,%12,%13,%14,%15,%16,%17,%18,%19,%20,%21,%22,%23,%24,%25,%26,%27},{%28,%29,%30,%31},%32,0,1,1,0;"
                     : OUT8(0), OUT8(8), OUT8(16), "=f"(d[24]), "=f"(d[25]), "=f"(d[26]), "=f"(d[27])
                     : "r"(a[0]), "r"(a[1]), "r"(a[2]), "r"(a[3]), "l"(desc));
}
__device__ __forceinline__ uint64_t desc_tab(uint32_t a) { return (uint64_t)((a & 0x3FFFF) >> 4) | ((uint64_t)(768 >> 4) << 16) | ((uint64_t)(128 >> 4) << 32); }

__device__ __forceinline__ void staged(uint32_t bar, int lane) {
    fence_async_s();
    __syncwarp();
    if (lane == 0) mbar_arrive(bar);
}

__device__ __forceinline__ void wgen(uint32_t win, uint32_t tab, uint32_t out, int c, int lane) {
    uint32_t A[28];
    int mi = lane >> 3, rr = lane & 7;
    int L = 12 * (mi & 1) + c;
#pragma unroll
    for (int s = 0; s < 7; s++) {
        int u = s < 6 ? s / 3 : mi >> 1;
        int tap = s < 6 ? 16 * (s % 3) + 8 * (mi >> 1) + rr : 48;
        int line = 3 * tap + (L >> 3);
        uint32_t ad = win + u * WPIECE + line * 128 + (((L ^ line) & 7) << 4);
        asm volatile("ldmatrix.sync.aligned.m8n8.x4.trans.shared.b16 {%0,%1,%2,%3},[%4];"
                     : "=r"(A[4 * s]), "=r"(A[4 * s + 1]), "=r"(A[4 * s + 2]), "=r"(A[4 * s + 3]) : "r"(ad));
    }
    float d0[24], d1[24];
    uint64_t ds = desc_tab(tab);
    wg_fence();
    wgmma48<0>(d0, A[0], A[1], A[2], A[3], ds);
    wgmma48<0>(d1, A[12], A[13], A[14], A[15], ds);
    wgmma48<1>(d0, A[4], A[5], A[6], A[7], ds + 96);
    wgmma48<1>(d1, A[16], A[17], A[18], A[19], ds + 96);
    wgmma48<1>(d0, A[8], A[9], A[10], A[11], ds + 192);
    wgmma48<1>(d1, A[20], A[21], A[22], A[23], ds + 192);
    wgmma48<1>(d0, A[24], A[25], A[26], A[27], ds + 336);
    wgmma48<1>(d1, A[24], A[25], A[26], A[27], ds + 288);
    wg_commit();
    wg_wait<0>();
    pin(d0); pin(d1);
    int g = lane >> 2, q = lane & 3;
    const uint32_t p = out + q * 512 + (8 * (c & 3) + (g ^ (2 * q))) * 16;
#pragma unroll
    for (int nb = 0; nb < 6; nb++)
        if (nb < 5 || q < 2)
            sts128(p + nb * 2048, pk(d0[4 * nb], d0[4 * nb + 2]), pk(d0[4 * nb + 1], d0[4 * nb + 3]), pk(d1[4 * nb], d1[4 * nb + 2]), pk(d1[4 * nb + 1], d1[4 * nb + 3]));
}

__device__ __forceinline__ void p1_unit(uint32_t blk, uint32_t cst, int wg, int wq, int lane) {
    int g = lane >> 2, q = lane & 3;
    uint32_t T[20];
#pragma unroll
    for (int v = 0; v < 5; v++) { uint4 x = lds128(cst + C_P1A + (v * 32 + lane) * 16); T[4 * v] = x.x; T[4 * v + 1] = x.y; T[4 * v + 2] = x.z; T[4 * v + 3] = x.w; }
    uint32_t P[6][3][4];
    const uint32_t a0 = blk + g * 512 + (2 * q + (g & 1)) * 64 + ((wq ^ q) << 4), a1 = a0 ^ 64;
    const uint32_t sel0 = (g & 1) ? 0x1054 : 0x5410, sel1 = sel0 + 0x2222;
    uint32_t vv[2][3][2][4];
    auto ldv = [&](int nu) {
        const int ro = (nu == 0 ? 6 : (nu == 1 ? 14 : 0)) * 512;
#pragma unroll
        for (int t = 0; t < 3; t++)
#pragma unroll
            for (int e = 0; e < 2; e++) {
                uint4 x = lds128((e ? a1 : a0) + t * 11264 + ro);
                vv[nu & 1][t][e][0] = x.x; vv[nu & 1][t][e][1] = x.y; vv[nu & 1][t][e][2] = x.z; vv[nu & 1][t][e][3] = x.w;
            }
    };
    ldv(0);
#pragma unroll
    for (int nu = 0; nu < 3; nu++) {
        if (nu < 2) ldv(nu + 1);
        auto& v = vv[nu & 1];
#pragma unroll
        for (int ch = 0; ch < 4; ch++) {
            const uint32_t sel = (ch & 1) ? sel1 : sel0;
            uint32_t b[2][3];
#pragma unroll
            for (int hf = 0; hf < 2; hf++)
#pragma unroll
                for (int t = 0; t < 3; t++) b[hf][t] = __byte_perm(v[t][0][(ch >> 1) + 2 * hf], v[t][1][(ch >> 1) + 2 * hf], sel);
            float d1[4];
            mma16z(d1, T[12], T[13], T[14], T[15], b[0][0], b[1][0]);
#pragma unroll
            for (int hf = 0; hf < 2; hf++) {
                float d0[4];
                mma16z(d0, T[0], T[1], T[2], T[3], b[hf][1], b[hf][2]);
                mma8(d0, T[16], T[17], b[hf][0]);
                mma16(d1, T[4 + 4 * hf], T[5 + 4 * hf], T[6 + 4 * hf], T[7 + 4 * hf], b[hf][1], b[hf][2]);
                P[(ch >> 1) + 2 * hf][nu][ch & 1] = pk(d0[0], d0[1]);
                P[(ch >> 1) + 2 * hf][nu][2 + (ch & 1)] = pk(d0[2], d0[3]);
            }
            P[4 + (ch >> 1)][nu][ch & 1] = pk(d1[0], d1[1]);
            P[4 + (ch >> 1)][nu][2 + (ch & 1)] = pk(d1[2], d1[3]);
        }
#pragma unroll
        for (int pb = 0; pb < 6; pb++) asm volatile("" : "+r"(P[pb][nu][0]), "+r"(P[pb][nu][1]), "+r"(P[pb][nu][2]), "+r"(P[pb][nu][3]));
        if (SPLIT >> nu & 1) mbar_wait(cst + (O_BAR - O_C) + 8 * BC);
    }
    const uint64_t ds = desc_tab(cst + C_P1B);
    float d[4][12];
    auto issue = [&](float (&dd)[12], int pb, int hf) {
        wgmma24<0>(dd, P[pb][0][0], P[pb][0][1], P[pb][0][2], P[pb][0][3], ds + 24 * hf);
        wgmma24<1>(dd, P[pb][1][0], P[pb][1][1], P[pb][1][2], P[pb][1][3], ds + 24 * hf + 96);
        wgmma24<1>(dd, P[pb][2][0], P[pb][2][1], P[pb][2][2], P[pb][2][3], ds + 24 * hf + 192);
    };
    wg_fence(); issue(d[0], 4, 0); issue(d[1], 5, 0); issue(d[2], 4, 1); issue(d[3], 5, 1); wg_commit();
    bar_sync(1 + wg, 128);
    asm volatile("" : "+r"(g), "+r"(q));
    wg_wait<0>(); pin(d[0]); pin(d[1]); pin(d[2]); pin(d[3]);
    if (g < 6) {
        const int r0 = (8 + (g >> 1)) * 11 + q;
        const uint32_t b8 = blk + 8 * (g & 1);
        const uint32_t re = b8 + r0 * 128 + (((wq ^ r0) & 7) << 4), im = b8 + (r0 + 121) * 128 + (((wq ^ (r0 + 1)) & 7) << 4);
#pragma unroll
        for (int k = 0; k < 12; k++) {
            const int hf = k / 6, i = 4 * ((k % 6) >> 1) + (k & 1);
            uint32_t a = (((k & 2) ? im : re) ^ (((k ^ (k >> 2)) & 1) << 6)) + 512 * (k >> 2);
            if (k < 8 || q < 3) sts64(a, pk(d[2 * hf][i], d[2 * hf][i + 2]), pk(d[2 * hf + 1][i], d[2 * hf + 1][i + 2]));
        }
    }
    const int r0 = fwmap0(g) * 11 + q;
    const uint32_t re = blk + r0 * 128 + (((wq ^ r0) & 7) << 4), im = blk + (r0 + 121) * 128 + (((wq ^ (r0 + 1)) & 7) << 4);
#pragma unroll
    for (int hf = 0; hf < 2; hf++) {
        wg_fence(); issue(d[0], 0, hf); issue(d[1], 1, hf); issue(d[2], 2, hf); issue(d[3], 3, hf); wg_commit();
        wg_wait<0>(); pin(d[0]); pin(d[1]); pin(d[2]); pin(d[3]);
#pragma unroll
        for (int k = 6 * hf; k < 6 * hf + 6; k++) {
            const int i = 4 * ((k % 6) >> 1) + (k & 1);
            uint32_t a = (((k & 2) ? im : re) ^ (((k ^ (k >> 2)) & 1) << 6)) + 512 * (k >> 2);
            if (k < 8 || q < 3) sts128(a, pk(d[0][i], d[0][i + 2]), pk(d[1][i], d[1][i + 2]), pk(d[2][i], d[2][i + 2]), pk(d[3][i], d[3][i + 2]));
        }
    }
}

__device__ __forceinline__ void p3_unit(uint32_t blk, uint32_t cst, int wg, int wq, int lane) {
    int g = lane >> 2, q = lane & 3;
    uint32_t T[12];
#pragma unroll
    for (int v = 0; v < 3; v++) { uint4 x = lds128(cst + C_P3 + (v * 32 + lane) * 16); T[4 * v] = x.x; T[4 * v + 1] = x.y; T[4 * v + 2] = x.z; T[4 * v + 3] = x.w; }
    uint32_t ad[3][3];
#pragma unroll
    for (int nu = 0; nu < 3; nu++)
#pragma unroll
        for (int ka = 0; ka < 3; ka++) {
            int r = p3cs(nu, g) * 121 + p3fw(nu, g) * 11 + min(4 * ka + q, 10);
            ad[nu][ka] = blk + r * 128 + ((((2 * wq) ^ r) & 7) << 4);
        }
    uint32_t o[2][4][4];
#pragma unroll
    for (int h = 0; h < 2; h++) {
        uint32_t z[3][3][4];
#pragma unroll
        for (int nu = 0; nu < 3; nu++)
#pragma unroll
            for (int ka = 0; ka < 3; ka++) {
                uint4 x = lds128(ad[nu][ka] ^ (h << 4));
                z[nu][ka][0] = x.x; z[nu][ka][1] = x.y; z[nu][ka][2] = x.z; z[nu][ka][3] = x.w;
            }
#pragma unroll
        for (int j = 0; j < 2; j++) {
            float d2[2][2][4];
#pragma unroll
            for (int e = 0; e < 2; e++) {
                const int ch = 2 * j + e;
                uint32_t P[3][2];
#pragma unroll
                for (int nu = 0; nu < 3; nu++) {
                    float d[4];
                    mma16z(d, T[0], T[1], T[2], T[3], z[nu][0][ch], z[nu][1][ch]);
                    mma8(d, T[4], T[5], z[nu][2][ch]);
                    P[nu][0] = pk(d[0], d[1]); P[nu][1] = pk(d[2], d[3]);
                }
#pragma unroll
                for (int be = 0; be < 2; be++) {
                    mma16z(d2[e][be], P[0][0], P[0][1], P[1][0], P[1][1], T[8 + 2 * be], T[9 + 2 * be]);
                    mma8(d2[e][be], P[2][0], P[2][1], T[6 + be]);
                }
            }
#pragma unroll
            for (int be = 0; be < 2; be++)
#pragma unroll
                for (int k = 0; k < 4; k++) o[be][k][2 * h + j] = pk(d2[0][be][k], d2[1][be][k]);
        }
    }
    bar_sync(1 + wg, 128);
    const int p = 4 * g + q;
    const uint32_t a = blk + p * 64 + ((wq ^ ((p >> 1) & 3)) << 4);
#pragma unroll
    for (int be = 0; be < 2; be++)
#pragma unroll
        for (int k = 0; k < 4; k++)
            sts128(a + (2 * be + (k & 1)) * 4096 + (k >> 1) * 2048, o[be][k][0], o[be][k][1], o[be][k][2], o[be][k][3]);
}

__global__ void __launch_bounds__(512, 1) fftconv_kernel(const __grid_constant__ Maps mp) {
    extern __shared__ __align__(1024) unsigned char smraw[];
    const uint32_t sm = s2u(smraw);
    const uint32_t bar = sm + O_BAR;
    const int tid = threadIdx.x, lane = tid & 31, warp = __shfl_sync(0xffffffffu, tid >> 5, 0), cta = blockIdx.x;
    const bool has4 = cta < NU - 4 * NCTA;
    const int fp = cta - (NCTA - NFP);
    TR(tid < 384 ? warp >> 2 : warp - 9, 0);
    {
        const int gi = warp == 12 ? 0 : warp + 1;
        if (warp <= 12 && lane == 0) {
            const int cnt = gi < 7 ? 1 : (gi == 7 ? 12 : 4);
#pragma unroll
            for (int k = 0; k < 8; k++) mbar_init(bar + 64 * gi + 8 * k, cnt);
            fence_async_s();
        }
        __syncwarp();
        if (warp == 12) asm volatile("bar.arrive 0,512;" ::: "memory");
        else { asm volatile("bar.arrive 9,512;" ::: "memory"); bar_sync(0, 512); }
    }
    if (warp >= 12) {
        asm volatile("setmaxnreg.dec.sync.aligned.u32 32;");
        if (warp == 12) {
            auto load_x = [&](int r, int off) {
                int u = r * NCTA + cta, tile = u / 3, cg = u - 3 * tile, th = tile / 14, tw = tile - 14 * th;
                uint32_t b = bar + 8 * (BX + r), dst = sm + off;
                int h6 = th ? 16 * th - 6 : 218;
                mbar_expect(b, BLK);
#pragma unroll 1
                for (int t = 0; t < 3; t++) {
                    int w0 = 16 * tw - 8 + 8 * t; if (w0 < 0) w0 += 224;
                    tma_ld3(dst + t * 11264 + 3072, &mp.x16, b, 32 * cg, w0, 16 * th);
                    tma_ld3(dst + t * 11264, &mp.x6, b, 32 * cg, w0, h6);
                }
            };
            if (lane == 0) {
                const int fw = cta % 11, ip = cta / 11, pr = 8 * (ip >> 1) + 2 * (ip & 1);
                TR(3, 18);
                mbar_expect(bar + 8 * BW, 2 * 18816 + WT_BYTES);
                tma_ld3(sm + O_W0, &mp.w, bar + 8 * BW, 0, 3 * pr, 0);
                tma_ld3(sm + O_W0 + WPIECE, &mp.w, bar + 8 * BW, 0, 3 * pr + 12, 0);
                bulk_ld(sm + O_WT, mp.wtab + fw * WT_BYTES, WT_BYTES, bar + 8 * BW);
                mbar_expect(bar + 8 * BC, C_BYTES);
                bulk_ld(sm + O_C, mp.ctab, C_BYTES, bar + 8 * BC);
                TR(3, 20);
                load_x(0, O_B0);
                TR(3, 21);
                mbar_expect(bar + 8 * (BW + 1), 2 * 18816);
                tma_ld3(sm + O_W1, &mp.w, bar + 8 * (BW + 1), 0, 3 * pr + 3, 0);
                tma_ld3(sm + O_W1 + WPIECE, &mp.w, bar + 8 * (BW + 1), 0, 3 * pr + 15, 0);
                load_x(1, O_B1);
                asm volatile("cp.async.bulk.prefetch.L2.global [%0],%1;" ::"l"(mp.x + 112 * 43008 + (size_t)cta * 34560), "r"(34560) : "memory");
                TR(3, 22);
            }
            __syncwarp();
            bar_sync(9, 512);
            if (lane == 0) {
                mbar_wait(bar + 8 * (BX + PACE));
                load_x(2, O_B2);
                TR(3, 1);
                mbar_wait(bar + 8 * BWS);
                load_x(3, O_B3);
                TR(3, 16);
                if (has4) { mbar_wait(bar + 8 * BWC); load_x(4, O_B4); }
                TR(3, 2);
            }
            __syncwarp();
            const unsigned* myc; unsigned tgt;
            {
                int u = (lane - 8) * NCTA + cta, tile = u / 3;
                int ci = lane < 7 ? CX + lane : (lane == 7 ? CW + (fp >= 0 ? fp / 11 : 0) : (lane < 13 && u < NU ? CY + 3 * (tile / 28) + (u - 3 * tile) : CX));
                myc = mp.cnt + 32 * ci;
                tgt = lane < 7 ? 84 : (lane == 7 ? 12 : NFP);
            }
            unsigned seen = 0;
            auto need = [&](int i) {
                int it = 0;
                while (!(seen >> i & 1) && ++it < (1 << 18)) {
                    unsigned v = 0;
                    if (lane < 13) asm volatile("ld.acquire.gpu.global.u32 %0,[%1];" : "=r"(v) : "l"(myc) : "memory");
                    seen = __ballot_sync(0xffffffffu, v >= tgt);
                }
                if (it) fence_async_g();
            };
            if (fp >= 0) {
                need(7);
                if (lane == 0) mbar_arrive(bar + 8 * BWT);
                TR(3, 15);
#pragma unroll 1
                for (int s = 0; s < 7; s++) {
                    need(s);
                    if (lane == 0) {
                        mbar_wait(bar + 8 * (s >= 3 ? BPE + s - 3 : (s == 2 ? BDN : BWS + 1)));
                        mbar_expect(bar + 8 * (BPF + s), STG);
                        tma_ld5(sm + O_IN + (s % 3) * STG, &mp.p2l, bar + 8 * (BPF + s), 0, 0, 28 * s, 0, fp);
                    }
                    __syncwarp();
                    TR(3, 3 + s);
                }
            }
#pragma unroll 1
            for (int r = 0; r < (has4 ? 5 : 4); r++) {
                need(8 + r);
                if (lane == 0) {
                    if (r < 2 || (r == 2 && has4)) mbar_wait(bar + 8 * (BDN + 11 * r + 1));
                    if (r == 2) mbar_wait(bar + 8 * (BWS + 1));
                    if (r == 3 && fp >= 0) { mbar_wait(bar + 8 * (BPE + 4)); mbar_wait(bar + 8 * (BPE + 5)); }
                    if (r == 4) {
                        if (fp >= 0) { for (int w = 0; w < 3; w++) mbar_wait(bar + 8 * (BDN + 11 * w + 7)); }
                        else mbar_wait(bar + 8 * (BDN + 11));
                    }
                    int off = r == 0 ? O_B2 : (r == 1 ? O_B3 : (r == 2 ? O_B4 : (r == 3 ? O_Z3 : O_B1)));
                    mbar_expect(bar + 8 * (BZ + r), SLAB);
                    tma_ld2(sm + off, &mp.s, bar + 8 * (BZ + r), 0, (r * NCTA + cta) * 242);
                }
                __syncwarp();
                TR(3, 10 + r);
            }
            unsigned last = 0;
            if (lane == 0) last = atomicAdd(mp.cnt + CD * 32, 1u) == NCTA - 1;
            if (__shfl_sync(0xffffffffu, last, 0))
                for (int i = lane; i < NCNT; i += 32) mp.cnt[i * 32] = 0;
        } else if (lane == 0) {
            const int w = warp - 13;
            const uint32_t rd = bar + 8 * (BRD + 11 * w), dn = bar + 8 * (BDN + 11 * w);
            if (w == 2) {
                const int fw = cta % 11, ip = cta / 11;
#pragma unroll 1
                for (int it = 0; it < 6; it++) {
                    int hi = it >= 3, cg = it - 3 * hi;
                    mbar_wait(bar + 8 * (BWR + it));
                    tma_st2(&mp.wst, sm + (hi ? O_W0 : O_B3) + cg * 11264, (2 * ip + hi) * 768 + cg * 256, fw * 22);
                    if (cg == 2) { bulk_commit_wait(); mbar_arrive(bar + 8 * (BWS + hi)); TR(6, 21 + hi); }
                }
                signal(mp.cnt + 32 * (CW + fw));
            }
#pragma unroll 1
            for (int j = (w == 2); j < 2; j++) {
                if (w == 2 && !has4) break;
                int r = w + 2 * j, u = r * NCTA + cta;
                mbar_wait(rd + 8 * j);
                tma_st2(&mp.s, sm + (r < 4 ? O_B0 + r * BLK : O_B4), 0, u * 242);
                bulk_commit_wait();
                signal(mp.cnt + 32 * (CX + u / 84));
                mbar_arrive(dn + 8 * j);
                TR(4 + w, 1 + j);
            }
            if (fp >= 0) {
#pragma unroll 1
                for (int s = 0; s < 7; s++) {
                    mbar_wait(rd + 8 * (2 + s));
                    tma_st5(&mp.p2s, sm + O_OUT + (s & 1) * STG + w * 7168, 0, 0, 28 * s, w, fp);
                    bulk_commit_wait();
                    signal(mp.cnt + 32 * (CY + 3 * s + w));
                    mbar_arrive(dn + 8 * (2 + s));
                    TR(4 + w, 3 + s);
                }
            }
#pragma unroll 1
            for (int j = 0; j < 2; j++) {
                int r = w + 3 * j;
                if (r == 5 || (r == 4 && !has4)) break;
                int u = r * NCTA + cta, tile = u / 3, cg = u - 3 * tile, th = tile / 14, tw = tile - 14 * th;
                int off = r == 0 ? O_B2 : (r == 1 ? O_B3 : (r == 2 ? O_B4 : (r == 3 ? O_Z3 : O_B1)));
                mbar_wait(rd + 8 * (9 + j));
                tma_st4(&mp.y, sm + off, 32 * cg, 0, 16 * th, 4 * tw);
                bulk_commit_wait();
                TR(4 + w, 10 + j);
            }
        }
    } else {
        asm volatile("setmaxnreg.inc.sync.aligned.u32 160;");
        const int wg = warp >> 2, wq = warp & 3;
        const uint32_t rd = bar + 8 * (BRD + 11 * wg), dn = bar + 8 * (BDN + 11 * wg);
        if (wg == 2) {
#pragma unroll 1
            for (int it = 0; it < 6; it++) {
                int hi = it >= 3, cg = it - 3 * hi;
                mbar_wait(bar + 8 * (BW + hi));
                if (it == 3) mbar_wait(bar + 8 * (BWR + 2));
                if (it == 0) TR(2, 1);
                wgen(sm + (hi ? O_W1 : O_W0), sm + O_WT, sm + (hi ? O_W0 : O_B3) + cg * 11264, 4 * cg + wq, lane);
                staged(bar + 8 * (BWR + it), lane);
            }
            if (lane == 0) mbar_arrive(bar + 8 * BWC);
            TR(2, 2);
        }
        mbar_wait(bar + 8 * BC);
#pragma unroll 1
        for (int j = (wg == 2); j < 2; j++) {
            int r = wg + 2 * j;
            if (r == 4 && !has4) break;
            mbar_wait(bar + 8 * (BX + r));
            TR(wg, 1 + 2 * j);
            p1_unit(sm + (r < 4 ? O_B0 + r * BLK : O_B4), sm + O_C, wg, wq, lane);
            staged(rd + 8 * j, lane);
            TR(wg, 2 + 2 * j);
        }
        if (fp >= 0) {
            uint32_t Wf[48];
            const int g = lane >> 2, q = lane & 3, ck = 2 * wq + (g >> 2);
            mbar_wait(bar + 8 * BWT);
            TR(wg, 5);
            const unsigned char* p = mp.wt + (size_t)fp * 73728 + q * 1536 + warp * 128;
            const int x = g ^ (4 * ((fp % 11) & 1));
#pragma unroll
            for (int k = 0; k < 12; k++) {
                uint4 v = __ldcg(reinterpret_cast<const uint4*>(p + k * 6144 + (x ^ (k >= 6 ? 2 : 0)) * 16));
                Wf[4 * k] = v.x; Wf[4 * k + 1] = v.y; Wf[4 * k + 2] = v.z; Wf[4 * k + 3] = v.w;
            }
            const uint32_t o0 = sm + O_OUT + wg * 7168 + (2 * q) * 128 + ((ck ^ (2 * q)) << 4) + (g & 3) * 4;
            int buf = 0;
#pragma unroll 1
            for (int s = 0; s < 7; s++) {
                float dp[28], dm[28];
                uint64_t ds = (uint64_t)(((sm + O_IN + buf * STG) & 0x3FFFF) >> 4) | (1ull << 16) | ((uint64_t)(1024 >> 4) << 32) | (1ull << 62);
                buf = buf == 2 ? 0 : buf + 1;
                mbar_wait(bar + 8 * (BPF + s));
                TR(wg, 17 + s);
                wg_fence();
                wgmma56<0>(dp, &Wf[0], ds);
                wgmma56<0>(dm, &Wf[24], ds + 4);
#pragma unroll
                for (int ks = 1; ks < 6; ks++) {
                    wgmma56<1>(dp, &Wf[4 * ks], ds + (ks >> 1) * (7168 >> 4) + (ks & 1) * 2);
                    wgmma56<1>(dm, &Wf[24 + 4 * ks], ds + (ks >> 1) * (7168 >> 4) + (ks & 1) * 2 + 4);
                }
                wg_commit();
                mbar_wait(s >= 2 ? dn + 8 * s : bar + 8 * (BDN + 11 * s));
                wg_wait<0>();
                pin(dp); pin(dm);
                if (lane == 0) mbar_arrive(bar + 8 * (BPE + s));
                const uint32_t a0 = o0 + (s & 1) * STG, a1 = (a0 + 128) ^ 16;
#pragma unroll
                for (int nb = 0; nb < 7; nb++) {
                    float pr = dp[4 * nb] - dp[4 * nb + 3], pi = dp[4 * nb + 1] + dp[4 * nb + 2];
                    float mr = dm[4 * nb] - dm[4 * nb + 3], mi = dm[4 * nb + 1] + dm[4 * nb + 2];
                    sts32(a0 + nb * 1024, pk(pr + mr, pi - mi));
                    sts32(a1 + nb * 1024, pk(pi + mi, mr - pr));
                }
                staged(rd + 8 * (2 + s), lane);
                TR(wg, 6 + s);
            }
        }
#pragma unroll 1
        for (int j = 0; j < 2; j++) {
            int r = wg + 3 * j;
            if (r == 5 || (r == 4 && !has4)) break;
            int off = r == 0 ? O_B2 : (r == 1 ? O_B3 : (r == 2 ? O_B4 : (r == 3 ? O_Z3 : O_B1)));
            mbar_wait(bar + 8 * (BZ + r));
            TR(wg, 13 + 2 * j);
            p3_unit(sm + off, sm + O_C, wg, wq, lane);
            staged(rd + 8 * (9 + j), lane);
            TR(wg, 14 + 2 * j);
        }
    }
}

typedef CUresult (*EncFn)(CUtensorMap*, CUtensorMapDataType, cuuint32_t, void*, const cuuint64_t*, const cuuint64_t*, const cuuint32_t*,
                          const cuuint32_t*, CUtensorMapInterleave, CUtensorMapSwizzle, CUtensorMapL2promotion, CUtensorMapFloatOOBfill);

void enc(EncFn f, CUtensorMap* m, void* p, int rank, const cuuint64_t* dims, const cuuint64_t* strides, const cuuint32_t* box,
         CUtensorMapSwizzle sw, CUtensorMapL2promotion pr = CU_TENSOR_MAP_L2_PROMOTION_NONE) {
    cuuint32_t es[5] = {1, 1, 1, 1, 1};
    f(m, CU_TENSOR_MAP_DATA_TYPE_BFLOAT16, rank, p, dims, strides, box, es, CU_TENSOR_MAP_INTERLEAVE_NONE, sw, pr, CU_TENSOR_MAP_FLOAT_OOB_FILL_NONE);
}

}

extern "C" void kernel_launch(void* const* d_in, const int* in_sizes, int n_in, void* d_out, int out_size) {
    void* fn = nullptr; cudaDriverEntryPointQueryResult qr;
    cudaGetDriverEntryPoint("cuTensorMapEncodeTiled", &fn, cudaEnableDefault, &qr);
    EncFn f = (EncFn)fn;
    void* pS; cudaGetSymbolAddress(&pS, g_S);
    Maps mp;
    void* pWt; cudaGetSymbolAddress(&pWt, g_Wt);
    cudaGetSymbolAddress((void**)&mp.ctab, g_ctab); cudaGetSymbolAddress((void**)&mp.wtab, g_wtab); cudaGetSymbolAddress((void**)&mp.cnt, g_cnt);
    mp.wt = (const unsigned char*)pWt; mp.x = (const unsigned char*)d_in[0];
    { cuuint64_t d[2] = {18432, 242}, s[1] = {36864}; cuuint32_t b[2] = {256, 22}; enc(f, &mp.wst, pWt, 2, d, s, b, CU_TENSOR_MAP_SWIZZLE_NONE); }
    {
        cuuint64_t d[3] = {96, 224, 224}, s[2] = {192, 43008};
        cuuint32_t b6[3] = {32, 8, 6}, b16[3] = {32, 8, 16};
        enc(f, &mp.x6, d_in[0], 3, d, s, b6, CU_TENSOR_MAP_SWIZZLE_64B);
        enc(f, &mp.x16, d_in[0], 3, d, s, b16, CU_TENSOR_MAP_SWIZZLE_64B);
    }
    { cuuint64_t d[4] = {96, 4, 224, 56}, s[3] = {192, 43008, 768}; cuuint32_t b[4] = {32, 4, 16, 4}; enc(f, &mp.y, d_out, 4, d, s, b, CU_TENSOR_MAP_SWIZZLE_64B); }
    { cuuint64_t d[2] = {64, (cuuint64_t)NU * 242}, s[1] = {128}; cuuint32_t b[2] = {64, 242}; enc(f, &mp.s, pS, 2, d, s, b, CU_TENSOR_MAP_SWIZZLE_128B); }
    {
        cuuint64_t d[5] = {64, 2, NT, 3, NFP}, s[4] = {121 * 128, 3 * SLAB, SLAB, 128};
        cuuint32_t bl[5] = {64, 2, 28, 3, 1}, bs[5] = {64, 2, 28, 1, 1};
        enc(f, &mp.p2l, pS, 5, d, s, bl, CU_TENSOR_MAP_SWIZZLE_128B);
        enc(f, &mp.p2s, pS, 5, d, s, bs, CU_TENSOR_MAP_SWIZZLE_128B);
    }
    { cuuint64_t d[3] = {64, 144, 49}, s[2] = {128, 18432}; cuuint32_t b[3] = {64, 3, 49}; enc(f, &mp.w, d_in[1], 3, d, s, b, CU_TENSOR_MAP_SWIZZLE_128B); }
    cudaFuncSetAttribute(fftconv_kernel, cudaFuncAttributeMaxDynamicSharedMemorySize, SMEM);
    fftconv_kernel<<<NCTA, 512, SMEM>>>(mp);
}
```

```cpp
#include <cuda_runtime.h>
#include <cuda_bf16.h>
#include <cuda.h>
#include <stdint.h>

#define TUNABLES {320, 310, 250, 280, 500, 250, 0, 1, 3900, 450, 0, 3, 1, 0, 0, 0}
constexpr int c_tune[16] = TUNABLES;
template <int I> struct TuneV { static constexpr int v = c_tune[I]; };
#define TV(i) TuneV<i>::v
#define RW TV(0)
#define R1 TV(1)
#define R2 TV(2)
#define R3 TV(3)
#define CREDIT TV(4)
#define LPW TV(5)
#define LPZ TV(6)
#define EARLY TV(7)
#define T0 TV(8)
#define XD TV(9)
#define XD0 TV(10)
#define PFW TV(11)
#define PP TV(12)
#define FORCE TV(13)
#define SPLIT 3

namespace {

constexpr int NCTA = 132, NH = 66;
constexpr int NUH = 294;
constexpr int NFP = 121;
constexpr int BLK = 33792;
constexpr int SLAB = 242 * 128;
constexpr int WPIECE = 19456;
constexpr int STG = 24576;
constexpr int NPS = 16, NPAGE = 21;
constexpr int O_B4 = 0, O_B0 = 87040, O_B2 = O_B0 + 2 * BLK, O_B3 = O_B0 + 3 * BLK;
constexpr int O_W1 = 0, O_W0 = 2 * WPIECE, O_WT = 4 * WPIECE;
constexpr int O_IN = 33792, O_OUT = O_IN + 3 * STG, O_Z3 = O_IN + STG, O_Z4 = 124928;
constexpr int O_C = 222208, O_BAR = 230912, SMEM = 232448;
constexpr int C_P1A = 0, C_P1B = 2560, C_P3 = 7168, C_BYTES = 8704, WT_BYTES = 6912;
constexpr int BC = 0, BW = 1, BX = 3, BZ = 8, BWF = 13, BPF = 16, BDW = 23, BD1 = 25, BD2 = 30;
constexpr int BPE = 40, BR2 = 47, BWC = 54;
constexpr int BRW = 56, BWL = 62, BR1 = 64, BR3 = 69, BWE = 74;
constexpr int BFL = 80, BCM = 95, BIS = 96, BRT = 116;
constexpr int O_NEXT = O_BAR + 1016, O_ROLE = O_BAR + 1000, O_SIDE = O_BAR + 1004, O_CM = O_BAR + 1008, O_EP = O_BAR + 1012;
constexpr uint32_t TAGM = 0x00010001u, TAGX = 0x00000001u, TAGZ = 0x00010000u;

constexpr uint16_t LUT_A[11] = {0x3f95, 0x3f92, 0x3f8c, 0x3f83, 0x3f6f, 0x3f53, 0x3f33, 0x3f0f, 0x3ed1, 0x3e7e, 0x3daa};
constexpr uint16_t LUT_B[11] = {0x3fe9, 0x3fe4, 0x3fdb, 0x3fcd, 0x3fbb, 0x3fa5, 0x3f8c, 0x3f60, 0x3f23, 0x3ec7, 0x3e05};
constexpr uint16_t LUT_W[12] = {0x3abb, 0x3ab9, 0x3ab3, 0x3aaa, 0x3a9d, 0x3a8d, 0x3a75, 0x3a4a, 0x3a1b, 0x39d3, 0x3955, 0};
constexpr uint16_t basis(int setb, int f, int a, int sn) {
    if (f < 0 || f > 10 || a < 0 || a > 21) return 0;
    int k = ((2 * f + 1) * (2 * a - 21) - 22 * sn + 88 * 7) % 88;
    if (k > 44) k = 88 - k;
    int neg = 0;
    if (k > 22) { k = 44 - k; neg = 1; }
    return (uint16_t)((setb ? LUT_B[k >> 1] : LUT_A[k >> 1]) | (neg << 15));
}
constexpr uint16_t neg16(uint16_t v) { return v ? (uint16_t)(v ^ 0x8000) : v; }
constexpr uint16_t wcoef(int fw, int fl, int sn, int tap) {
    if (fl > 21) return 0;
    int fh = fl >> 1, kh = tap / 7, kw = tap - 7 * kh;
    int u = (2 * fh + 1) * kh;
    if (fl & 1) u = -u;
    int k = (u + (2 * fw + 1) * kw - 11 * sn + 44 * 4) % 44;
    if (k > 22) k = 44 - k;
    int neg = 0;
    if (k > 11) { k = 22 - k; neg = 1; }
    return (uint16_t)(LUT_W[k] | (neg << 15));
}
struct alignas(128) CTab { uint16_t v[C_BYTES / 2]; };
struct alignas(128) WTab { uint16_t v[WT_BYTES / 2]; };
constexpr CTab make_ctab() {
    CTab t{};
    for (int lane = 0; lane < 32; lane++) {
        int g = lane >> 2, q = lane & 3;
        for (int r = 0; r < 18; r++) {
            int quad = r >> 2, j = r & 3;
            int set = quad < 3 ? quad : (quad == 3 ? 1 + (j >> 1) : 0);
            int sn = (j ^ (set == 0 ? g : g >> 1)) & 1;
            int t8 = quad < 3 ? 1 + (j >> 1) : 0;
            int b = 8 * t8 + 2 * q - 2;
            int fw = set == 0 ? g : (((g & 1) == set - 1) ? 8 + (g >> 1) : -1);
            int o = (C_P1A + (quad * 32 + lane) * 16 + j * 4) / 2;
            t.v[o] = basis(0, fw, b, sn); t.v[o + 1] = basis(0, fw, b + 1, sn);
        }
        for (int r = 0; r < 12; r++) {
            int o = (C_P3 + ((r >> 2) * 32 + lane) * 16 + (r & 3) * 4) / 2;
            if (r < 6) {
                int a = 6 + g + 8 * (r & 1), fh = 4 * (r >> 1) + q;
                t.v[o] = basis(0, fh, a, 0); t.v[o + 1] = basis(0, fh, a, 1);
            } else {
                int be = r < 8 ? r - 6 : (r - 8) >> 1, nu = r < 8 ? 2 : (r & 1);
                int b = 6 + 8 * be + 4 * (g & 1) + (g >> 1);
                t.v[o] = basis(1, 4 * nu + q, b, 0); t.v[o + 1] = basis(1, 4 * nu + q, b, 1);
            }
        }
    }
    for (int kc = 0; kc < 6; kc++)
        for (int nb = 0; nb < 6; nb++)
            for (int n = 0; n < 8; n++)
                for (int k = 0; k < 8; k++) {
                    int nu = kc >> 1, ds = kc & 1, im = nb & 1, fh = 4 * (nb >> 1) + (n >> 1), mi = n & 1;
                    int a = nu == 0 ? 6 + k : (nu == 1 ? 14 + k : (k < 6 ? k : -1));
                    uint16_t v = basis(0, fh, a, ds ^ im);
                    if (ds != im && (im ? mi : !mi)) v = neg16(v);
                    t.v[C_P1B / 2 + ((kc * 6 + nb) * 8 + n) * 8 + k] = v;
                }
    return t;
}
constexpr WTab make_wtab(int fw) {
    WTab t{};
    for (int nb = 0; nb < 6; nb++)
        for (int n = 0; n < 8; n++) {
            for (int tap = 0; tap < 48; tap++) t.v[(((tap >> 3) * 6 + nb) * 8 + n) * 8 + (tap & 7)] = wcoef(fw, 4 * nb + (n >> 1), n & 1, tap);
            t.v[((7 * 6 + nb) * 8 + n) * 8] = wcoef(fw, 4 * nb + (n >> 1), n & 1, 48);
        }
    return t;
}
__device__ const CTab g_ctab = make_ctab();
__device__ const WTab g_wtab[11] = {make_wtab(0), make_wtab(1), make_wtab(2), make_wtab(3), make_wtab(4), make_wtab(5),
                                    make_wtab(6), make_wtab(7), make_wtab(8), make_wtab(9), make_wtab(10)};

__device__ __align__(1024) unsigned char g_S[(size_t)(NPAGE + 1) << 21];
constexpr int CX = 0, CY = 8, CW = 16, CV = 32, CT = 38, CD = 40, CE = 41;
__device__ __align__(256) unsigned g_cnt[64];

struct Maps {
    const unsigned char* ctab; const unsigned char* wtab; const unsigned char* x; unsigned* cnt; unsigned char* s;
    const unsigned char* wraw;
    alignas(64) CUtensorMap w, x6, x16, wf, s32, s30, p16, p2, y;
};

#define TR(role, i)
#define TRL(role, i)
#define TRC(i)

__device__ __forceinline__ uint32_t s2u(const void* p) { return (uint32_t)__cvta_generic_to_shared(p); }
__device__ __forceinline__ void mbar_init(uint32_t b, int c) { asm volatile("mbarrier.init.shared::cta.b64 [%0],%1;" ::"r"(b), "r"(c) : "memory"); }
__device__ __forceinline__ void mbar_expect(uint32_t b, uint32_t tx) { asm volatile("mbarrier.arrive.expect_tx.shared::cta.b64 _,[%0],%1;" ::"r"(b), "r"(tx) : "memory"); }
__device__ __forceinline__ void mbar_arrive(uint32_t b) { asm volatile("mbarrier.arrive.shared::cta.b64 _,[%0];" ::"r"(b) : "memory"); }
__device__ __forceinline__ void mbar_wait(uint32_t b) {
    uint32_t ok; int it = 0;
    do {
        asm volatile("{.reg .pred p; mbarrier.try_wait.parity.shared::cta.b64 p,[%1],0; selp.u32 %0,1,0,p;}" : "=r"(ok) : "r"(b) : "memory");
    } while (!ok && ++it < (1 << 16));
}
__device__ __forceinline__ void mbar_wait_ph(uint32_t b, uint32_t ph) {
    uint32_t ok; int it = 0;
    do {
        asm volatile("{.reg .pred p; mbarrier.try_wait.parity.shared::cta.b64 p,[%1],%2; selp.u32 %0,1,0,p;}" : "=r"(ok) : "r"(b), "r"(ph) : "memory");
    } while (!ok && ++it < (1 << 16));
}
__device__ __forceinline__ bool bar_any(int id, int n, bool v) {
    uint32_t r;
    asm volatile("{.reg .pred p,q; setp.ne.u32 p,%3,0; bar.red.or.pred q,%1,%2,p; selp.u32 %0,1,0,q;}" : "=r"(r) : "r"(id), "r"(n), "r"((uint32_t)v) : "memory");
    return r;
}
__device__ __forceinline__ int laneid() { int l; asm volatile("mov.u32 %0,%%laneid;" : "=r"(l)); return l; }
__device__ __forceinline__ uint32_t lds32(uint32_t a) { uint32_t v; asm volatile("ld.shared.u32 %0,[%1];" : "=r"(v) : "r"(a) : "memory"); return v; }
__device__ __forceinline__ uint32_t tagged(uint32_t v, uint32_t m, uint32_t t) { return (v & ~m) | (t & m); }
__device__ __forceinline__ void red_add(unsigned* c, unsigned v = 1) { asm volatile("red.relaxed.gpu.global.add.u32 [%0],%1;" ::"l"(c), "r"(v) : "memory"); }
__device__ __forceinline__ void pf_l2(const void* p) { asm volatile("prefetch.global.L2 [%0];" ::"l"(p)); }
__device__ __forceinline__ void fence_async_s() { asm volatile("fence.proxy.async.shared::cta;" ::: "memory"); }
__device__ __forceinline__ void fence_async_g() { asm volatile("fence.proxy.async.global;" ::: "memory"); }
__device__ __forceinline__ void bulk_ld(uint32_t dst, const void* src, uint32_t bytes, uint32_t bar) {
    asm volatile("cp.async.bulk.shared::cluster.global.mbarrier::complete_tx::bytes [%0],[%1],%2,[%3];" ::"r"(dst), "l"(src), "r"(bytes), "r"(bar) : "memory");
}
__device__ __forceinline__ void tma_ld2(uint32_t dst, const CUtensorMap* m, uint32_t bar, int c0, int c1) {
    asm volatile("cp.async.bulk.tensor.2d.shared::cluster.global.mbarrier::complete_tx::bytes [%0],[%1,{%3,%4}],[%2];" ::"r"(dst), "l"(m), "r"(bar), "r"(c0), "r"(c1) : "memory");
}
__device__ __forceinline__ void tma_ld3(uint32_t dst, const CUtensorMap* m, uint32_t bar, int c0, int c1, int c2) {
    asm volatile("cp.async.bulk.tensor.3d.shared::cluster.global.mbarrier::complete_tx::bytes [%0],[%1,{%3,%4,%5}],[%2];" ::"r"(dst), "l"(m), "r"(bar), "r"(c0), "r"(c1), "r"(c2) : "memory");
}
__device__ __forceinline__ void tma_ld4(uint32_t dst, const CUtensorMap* m, uint32_t bar, int c0, int c1, int c2, int c3) {
    asm volatile("cp.async.bulk.tensor.4d.shared::cluster.global.mbarrier::complete_tx::bytes [%0],[%1,{%3,%4,%5,%6}],[%2];" ::"r"(dst), "l"(m), "r"(bar), "r"(c0), "r"(c1), "r"(c2), "r"(c3) : "memory");
}
__device__ __forceinline__ void bulk_st(void* dst, uint32_t src, uint32_t bytes) {
    asm volatile("cp.async.bulk.global.shared::cta.bulk_group [%0],[%1],%2;" ::"l"(dst), "r"(src), "r"(bytes) : "memory");
}
__device__ __forceinline__ void tma_ld5(uint32_t dst, const CUtensorMap* m, uint32_t bar, int c0, int c1, int c2, int c3, int c4) {
    asm volatile("cp.async.bulk.tensor.5d.shared::cluster.global.mbarrier::complete_tx::bytes [%0],[%1,{%3,%4,%5,%6,%7}],[%2];" ::"r"(dst), "l"(m), "r"(bar), "r"(c0), "r"(c1), "r"(c2), "r"(c3), "r"(c4) : "memory");
}
__device__ __forceinline__ void tma_st2(const CUtensorMap* m, uint32_t src, int c0, int c1) {
    asm volatile("cp.async.bulk.tensor.2d.global.shared::cta.bulk_group [%0,{%2,%3}],[%1];" ::"l"(m), "r"(src), "r"(c0), "r"(c1) : "memory");
}
__device__ __forceinline__ void tma_st4(const CUtensorMap* m, uint32_t src, int c0, int c1, int c2, int c3) {
    asm volatile("cp.async.bulk.tensor.4d.global.shared::cta.bulk_group [%0,{%2,%3,%4,%5}],[%1];" ::"l"(m), "r"(src), "r"(c0), "r"(c1), "r"(c2), "r"(c3) : "memory");
}
__device__ __forceinline__ void tma_st5(const CUtensorMap* m, uint32_t src, int c0, int c1, int c2, int c3, int c4) {
    asm volatile("cp.async.bulk.tensor.5d.global.shared::cta.bulk_group [%0,{%2,%3,%4,%5,%6}],[%1];" ::"l"(m), "r"(src), "r"(c0), "r"(c1), "r"(c2), "r"(c3), "r"(c4) : "memory");
}
__device__ __forceinline__ void bulk_commit() { asm volatile("cp.async.bulk.commit_group;" ::: "memory"); }
template <int N> __device__ __forceinline__ void bulk_wait() { asm volatile("cp.async.bulk.wait_group %0;" ::"n"(N) : "memory"); }
template <int N> __device__ __forceinline__ void bulk_wait_read() { asm volatile("cp.async.bulk.wait_group.read %0;" ::"n"(N) : "memory"); }
__device__ __forceinline__ void bar_sync(int id, int n) { asm volatile("bar.sync %0,%1;" ::"r"(id), "r"(n) : "memory"); }

__device__ __forceinline__ uint4 lds128(uint32_t a) {
    uint4 v; asm volatile("ld.shared.v4.u32 {%0,%1,%2,%3},[%4];" : "=r"(v.x), "=r"(v.y), "=r"(v.z), "=r"(v.w) : "r"(a)); return v;
}
__device__ __forceinline__ void sts128(uint32_t a, uint32_t x, uint32_t y, uint32_t z, uint32_t w) {
    asm volatile("st.shared.v4.u32 [%0],{%1,%2,%3,%4};" ::"r"(a), "r"(x), "r"(y), "r"(z), "r"(w) : "memory");
}
__device__ __forceinline__ void sts64(uint32_t a, uint32_t x, uint32_t y) { asm volatile("st.shared.v2.u32 [%0],{%1,%2};" ::"r"(a), "r"(x), "r"(y) : "memory"); }
__device__ __forceinline__ void sts128p(uint32_t a, uint32_t x, uint32_t y, uint32_t z, uint32_t w, bool p) {
    asm volatile("{.reg .pred p; setp.ne.u32 p,%5,0; @p st.shared.v4.u32 [%0],{%1,%2,%3,%4};}" ::"r"(a), "r"(x), "r"(y), "r"(z), "r"(w), "r"((uint32_t)p) : "memory");
}
__device__ __forceinline__ void sts32(uint32_t a, uint32_t x) { asm volatile("st.shared.u32 [%0],%1;" ::"r"(a), "r"(x) : "memory"); }
__device__ __forceinline__ uint32_t pk(float lo, float hi) { uint32_t r; asm("cvt.rn.bf16x2.f32 %0,%1,%2;" : "=r"(r) : "f"(hi), "f"(lo)); return r; }

__device__ __forceinline__ uint32_t pkv(float lo, float hi) { uint32_t r; asm volatile("cvt.rn.bf16x2.f32 %0,%1,%2;" : "=r"(r) : "f"(hi), "f"(lo)); return r; }

__device__ __forceinline__ void mma16z(float* d, uint32_t a0, uint32_t a1, uint32_t a2, uint32_t a3, uint32_t b0, uint32_t b1) {
    asm("mma.sync.aligned.m16n8k16.row.col.f32.bf16.bf16.f32 {%0,%1,%2,%3},{%4,%5,%6,%7},{%8,%9},{%10,%10,%10,%10};"
        : "=f"(d[0]), "=f"(d[1]), "=f"(d[2]), "=f"(d[3]) : "r"(a0), "r"(a1), "r"(a2), "r"(a3), "r"(b0), "r"(b1), "f"(0.f));
}
__device__ __forceinline__ void mma16(float* d, uint32_t a0, uint32_t a1, uint32_t a2, uint32_t a3, uint32_t b0, uint32_t b1) {
    asm("mma.sync.aligned.m16n8k16.row.col.f32.bf16.bf16.f32 {%0,%1,%2,%3},{%4,%5,%6,%7},{%8,%9},{%0,%1,%2,%3};"
        : "+f"(d[0]), "+f"(d[1]), "+f"(d[2]), "+f"(d[3]) : "r"(a0), "r"(a1), "r"(a2), "r"(a3), "r"(b0), "r"(b1));
}
__device__ __forceinline__ void mma8(float* d, uint32_t a0, uint32_t a1, uint32_t b0) {
    asm("mma.sync.aligned.m16n8k8.row.col.f32.bf16.bf16.f32 {%0,%1,%2,%3},{%4,%5},{%6},{%0,%1,%2,%3};"
        : "+f"(d[0]), "+f"(d[1]), "+f"(d[2]), "+f"(d[3]) : "r"(a0), "r"(a1), "r"(b0));
}
__device__ __forceinline__ void wg_fence() { asm volatile("wgmma.fence.sync.aligned;" ::: "memory"); }
__device__ __forceinline__ void wg_commit() { asm volatile("wgmma.commit_group.sync.aligned;" ::: "memory"); }
template <int N> __device__ __forceinline__ void wg_wait() { asm volatile("wgmma.wait_group.sync.aligned %0;" ::"n"(N) : "memory"); }
template <int N> __device__ __forceinline__ void pin(float (&d)[N]) {
#pragma unroll
    for (int i = 0; i < N; i++) asm volatile("" : "+f"(d[i])::"memory");
}
#define ACC8(o) "+f"(d[o]), "+f"(d[o + 1]), "+f"(d[o + 2]), "+f"(d[o + 3]), "+f"(d[o + 4]), "+f"(d[o + 5]), "+f"(d[o + 6]), "+f"(d[o + 7])
#define OUT8(o) "=f"(d[o]), "=f"(d[o + 1]), "=f"(d[o + 2]), "=f"(d[o + 3]), "=f"(d[o + 4]), "=f"(d[o + 5]), "=f"(d[o + 6]), "=f"(d[o + 7])
template <int ACC> __device__ __forceinline__ void wgmma48(float (&d)[24], uint32_t a0, uint32_t a1, uint32_t a2, uint32_t a3, uint64_t desc) {
    if (ACC)
        asm volatile("wgmma.mma_async.sync.aligned.m64n48k16.f32.bf16.bf16 "
                     "{%0,%1,%2,%3,%4,%5,%6,%7,%8,%9,%10,%11,%12,%13,%14,%15,%16,%17,%18,%19,%20,%21,%22,%23},{%24,%25,%26,%27},%28,%29,1,1,0;"
                     : ACC8(0), ACC8(8), ACC8(16) : "r"(a0), "r"(a1), "r"(a2), "r"(a3), "l"(desc), "n"(ACC & 1));
    else
        asm volatile("wgmma.mma_async.sync.aligned.m64n48k16.f32.bf16.bf16 "
                     "{%0,%1,%2,%3,%4,%5,%6,%7,%8,%9,%10,%11,%12,%13,%14,%15,%16,%17,%18,%19,%20,%21,%22,%23},{%24,%25,%26,%27},%28,0,1,1,0;"
                     : OUT8(0), OUT8(8), OUT8(16) : "r"(a0), "r"(a1), "r"(a2), "r"(a3), "l"(desc));
}
template <int ACC> __device__ __forceinline__ void wgmma_p2(float (&d)[32], const uint32_t* a, uint64_t desc) {
    if (ACC)
        asm volatile("wgmma.mma_async.sync.aligned.m64n64k16.f32.bf16.bf16 "
                     "{%0,%1,%2,%3,%4,%5,%6,%7,%8,%9,%10,%11,%12,%13,%14,%15,%16,%17,%18,%19,%20,%21,%22,%23,%24,%25,%26,%27,%28,%29,%30,%31},{%32,%33,%34,%35},%36,1,1,1,0;"
                     : ACC8(0), ACC8(8), ACC8(16), ACC8(24) : "r"(a[0]), "r"(a[1]), "r"(a[2]), "r"(a[3]), "l"(desc));
    else
        asm volatile("wgmma.mma_async.sync.aligned.m64n64k16.f32.bf16.bf16 "
                     "{%0,%1,%2,%3,%4,%5,%6,%7,%8,%9,%10,%11,%12,%13,%14,%15,%16,%17,%18,%19,%20,%21,%22,%23,%24,%25,%26,%27,%28,%29,%30,%31},{%32,%33,%34,%35},%36,0,1,1,0;"
                     : OUT8(0), OUT8(8), OUT8(16), OUT8(24) : "r"(a[0]), "r"(a[1]), "r"(a[2]), "r"(a[3]), "l"(desc));
}
template <int ACC> __device__ __forceinline__ void wgmma_p2(float (&d)[4], const uint32_t* a, uint64_t desc) {
    if (ACC)
        asm volatile("wgmma.mma_async.sync.aligned.m64n8k16.f32.bf16.bf16 {%0,%1,%2,%3},{%4,%5,%6,%7},%8,1,1,1,0;"
                     : "+f"(d[0]), "+f"(d[1]), "+f"(d[2]), "+f"(d[3]) : "r"(a[0]), "r"(a[1]), "r"(a[2]), "r"(a[3]), "l"(desc));
    else
        asm volatile("wgmma.mma_async.sync.aligned.m64n8k16.f32.bf16.bf16 {%0,%1,%2,%3},{%4,%5,%6,%7},%8,0,1,1,0;"
                     : "=f"(d[0]), "=f"(d[1]), "=f"(d[2]), "=f"(d[3]) : "r"(a[0]), "r"(a[1]), "r"(a[2]), "r"(a[3]), "l"(desc));
}
__device__ __forceinline__ uint64_t desc_tab(uint32_t a) { return (uint64_t)((a & 0x3FFFF) >> 4) | ((uint64_t)(768 >> 4) << 16) | ((uint64_t)(128 >> 4) << 32); }

__device__ __forceinline__ void staged(uint32_t bar, int lane) {
    fence_async_s();
    __syncwarp();
    if (lane == 0) mbar_arrive(bar);
}

__device__ __forceinline__ void wgen(uint32_t win, uint32_t tab, uint32_t out, int c, int qq, int lane, uint32_t consumed, uint32_t chain, uint32_t gate) {
    uint32_t A[28];
    int mi = lane >> 3, rr = lane & 7;
    int L = 12 * (mi & 1) + c;
#pragma unroll
    for (int s = 0; s < 7; s++) {
        int u = s < 6 ? s / 3 : mi >> 1;
        int tap = s < 6 ? 16 * (s % 3) + 8 * (mi >> 1) + rr : 48;
        int line = 3 * tap + (L >> 3);
        uint32_t ad = win + u * WPIECE + line * 128 + (((L ^ line) & 7) << 4);
        asm volatile("ldmatrix.sync.aligned.m8n8.x4.trans.shared.b16 {%0,%1,%2,%3},[%4];"
                     : "=r"(A[4 * s]), "=r"(A[4 * s + 1]), "=r"(A[4 * s + 2]), "=r"(A[4 * s + 3]) : "r"(ad));
    }
    float d0[24], d1[24];
    uint64_t ds = desc_tab(tab);
    wg_fence();
    wgmma48<0>(d0, A[0], A[1], A[2], A[3], ds);
    wgmma48<0>(d1, A[12], A[13], A[14], A[15], ds);
    wgmma48<1>(d0, A[4], A[5], A[6], A[7], ds + 96);
    wgmma48<1>(d1, A[16], A[17], A[18], A[19], ds + 96);
    wgmma48<1>(d0, A[8], A[9], A[10], A[11], ds + 192);
    wgmma48<1>(d1, A[20], A[21], A[22], A[23], ds + 192);
    wgmma48<1>(d0, A[24], A[25], A[26], A[27], ds + 336);
    wgmma48<1>(d1, A[24], A[25], A[26], A[27], ds + 288);
    wg_commit();
    if (lane == 0) { if (chain) mbar_arrive(chain); mbar_arrive(consumed); }
    mbar_wait(gate);
    wg_wait<0>();
    pin(d0); pin(d1);
    int g = lane >> 2, q = lane & 3;
    const uint32_t p = out + q * 512 + (8 * (c & 3) + (g ^ (2 * (q ^ qq)))) * 16;
#pragma unroll
    for (int nb = 0; nb < 6; nb++)
        if (nb < 5 || q < 2)
            sts128(p + nb * 2048, pk(d0[4 * nb], d0[4 * nb + 2]), pk(d0[4 * nb + 1], d0[4 * nb + 3]), pk(d1[4 * nb], d1[4 * nb + 2]), pk(d1[4 * nb + 1], d1[4 * nb + 3]));
}

__device__ __forceinline__ void p1_unit(uint32_t blk, uint32_t out, uint32_t cst, int wg, int wq, int lane) {
    int g = lane >> 2, q = lane & 3;
    uint32_t T[20];
#pragma unroll
    for (int v = 0; v < 5; v++) { uint4 x = lds128(cst + C_P1A + (v * 32 + lane) * 16); T[4 * v] = x.x; T[4 * v + 1] = x.y; T[4 * v + 2] = x.z; T[4 * v + 3] = x.w; }
    uint32_t P[6][3][4];
    const uint32_t a0 = blk + g * 512 + (2 * q + (g & 1)) * 64 + ((wq ^ q) << 4), a1 = a0 ^ 64;
    const uint32_t sel0 = (g & 1) ? 0x1054 : 0x5410, sel1 = sel0 + 0x2222;
    uint32_t vv[2][3][2][4];
    auto ldv = [&](int nu) {
        const int ro = (nu == 0 ? 6 : (nu == 1 ? 14 : 0)) * 512;
#pragma unroll
        for (int t = 0; t < 3; t++)
#pragma unroll
            for (int e = 0; e < 2; e++) {
                uint4 x = lds128((e ? a1 : a0) + t * 11264 + ro);
                vv[nu & 1][t][e][0] = x.x; vv[nu & 1][t][e][1] = x.y; vv[nu & 1][t][e][2] = x.z; vv[nu & 1][t][e][3] = x.w;
            }
    };
    ldv(0);
#pragma unroll
    for (int nu = 0; nu < 3; nu++) {
        if (nu < 2) ldv(nu + 1);
        auto& v = vv[nu & 1];
#pragma unroll
        for (int ch = 0; ch < 4; ch++) {
            const uint32_t sel = (ch & 1) ? sel1 : sel0;
            uint32_t b[2][3];
#pragma unroll
            for (int hf = 0; hf < 2; hf++)
#pragma unroll
                for (int t = 0; t < 3; t++) b[hf][t] = __byte_perm(v[t][0][(ch >> 1) + 2 * hf], v[t][1][(ch >> 1) + 2 * hf], sel);
            float d1[4];
            mma16z(d1, T[12], T[13], T[14], T[15], b[0][0], b[1][0]);
#pragma unroll
            for (int hf = 0; hf < 2; hf++) {
                float d0[4];
                mma16z(d0, T[0], T[1], T[2], T[3], b[hf][1], b[hf][2]);
                mma8(d0, T[16], T[17], b[hf][0]);
                mma16(d1, T[4 + 4 * hf], T[5 + 4 * hf], T[6 + 4 * hf], T[7 + 4 * hf], b[hf][1], b[hf][2]);
                P[(ch >> 1) + 2 * hf][nu][ch & 1] = pk(d0[0], d0[1]);
                P[(ch >> 1) + 2 * hf][nu][2 + (ch & 1)] = pk(d0[2], d0[3]);
            }
            P[4 + (ch >> 1)][nu][ch & 1] = pk(d1[0], d1[1]);
            P[4 + (ch >> 1)][nu][2 + (ch & 1)] = pk(d1[2], d1[3]);
        }
#pragma unroll
        for (int pb = 0; pb < 6; pb++) asm volatile("" : "+r"(P[pb][nu][0]), "+r"(P[pb][nu][1]), "+r"(P[pb][nu][2]), "+r"(P[pb][nu][3]));
                if (SPLIT >> nu & 1) mbar_wait(cst + (O_BAR - O_C) + 8 * BC);
    }
    const uint64_t ds = desc_tab(cst + C_P1B);
    float dA[24], dB[24];
    auto issue = [&](int pb) {
        wg_fence();
        if (pb == 4) {
            wgmma48<0>(dA, P[pb][0][0], P[pb][0][1], P[pb][0][2], P[pb][0][3], ds);
            wgmma48<0>(dB, P[pb + 1][0][0], P[pb + 1][0][1], P[pb + 1][0][2], P[pb + 1][0][3], ds);
        } else {
            wgmma48<2>(dA, P[pb][0][0], P[pb][0][1], P[pb][0][2], P[pb][0][3], ds);
            wgmma48<2>(dB, P[pb + 1][0][0], P[pb + 1][0][1], P[pb + 1][0][2], P[pb + 1][0][3], ds);
        }
        wgmma48<1>(dA, P[pb][1][0], P[pb][1][1], P[pb][1][2], P[pb][1][3], ds + 96);
        wgmma48<1>(dB, P[pb + 1][1][0], P[pb + 1][1][1], P[pb + 1][1][2], P[pb + 1][1][3], ds + 96);
        wgmma48<1>(dA, P[pb][2][0], P[pb][2][1], P[pb][2][2], P[pb][2][3], ds + 192);
        wgmma48<1>(dB, P[pb + 1][2][0], P[pb + 1][2][1], P[pb + 1][2][2], P[pb + 1][2][3], ds + 192);
        wg_commit();
    };
    issue(4);
    bar_sync(1 + wg, 128);
    asm volatile("" : "+r"(g), "+r"(q));
    wg_wait<0>(); pin(dA); pin(dB);
    uint32_t o[12][2];
#pragma unroll
    for (int k = 0; k < 12; k++) { const int i = 4 * (k >> 1) + (k & 1); o[k][0] = pkv(dA[i], dA[i + 2]); o[k][1] = pkv(dB[i], dB[i + 2]); }
    issue(0);
    {
        const int sw = (g >> 1) & 1, r0 = 2 * ((g < 6 ? 8 + (g >> 1) : 1) * 11 + q) + sw;
        const uint32_t a0 = out + r0 * 128 + ((((4 * sw + wq) ^ r0) & 7) << 4) + 8 * (g & 1);
        const uint32_t m = wq == 3 && (g & 1) ? TAGM : 0, m0 = sw ? m : 0, m1 = m ^ m0;
#pragma unroll
        for (int k = 11; k >= 0; k--) {
            sts64((a0 ^ ((k & 2) * 72 + (k & 1) * 64)) + 1024 * (k >> 2), o[k][0], tagged(o[k][1], (k & 1) ? m1 : m0, TAGX));
            if (k == 8) __syncwarp();
        }
    }
    wg_wait<0>(); pin(dA); pin(dB);
#pragma unroll
    for (int k = 0; k < 12; k++) { const int i = 4 * (k >> 1) + (k & 1); o[k][0] = pkv(dA[i], dA[i + 2]); o[k][1] = pkv(dB[i], dB[i + 2]); }
    issue(2);
    mbar_wait(cst + (O_BAR - O_C) + 8 * BC);
    const int r0 = 2 * (g * 11 + q) + (g & 1);
    const uint32_t ao = out + r0 * 128 + ((((4 * (g & 1) + wq) ^ r0) & 7) << 4);
    const uint32_t m = wq == 3 ? TAGM : 0, m0 = (g & 1) ? m : 0, m1 = m ^ m0;
    wg_wait<0>(); pin(dA); pin(dB);
#pragma unroll
    for (int k = 0; k < 12; k++) {
        const int i = 4 * (k >> 1) + (k & 1);
        sts128p((ao ^ ((k & 2) * 72 + (k & 1) * 64)) + 1024 * (k >> 2), o[k][0], o[k][1], pk(dA[i], dA[i + 2]),
                tagged(pk(dB[i], dB[i + 2]), (k & 1) ? m1 : m0, TAGX), k < 8 || q < 3);
    }
}

template <int NB>
__device__ __forceinline__ void p2_step(const uint32_t (&Wf)[48], uint32_t in, uint32_t a0, uint32_t m, uint32_t ofree, uint32_t empty, int lane, int wg, int s) {
    float dp[4 * NB], dm[4 * NB];
    const uint64_t ds = (uint64_t)((in & 0x3FFFF) >> 4) | (1ull << 16) | ((uint64_t)(1024 >> 4) << 32) | (1ull << 62);
    if (wg > 0 || (wg == 0 && s)) bar_sync(4 + wg, 256);
    wg_fence();
    wgmma_p2<0>(dp, &Wf[0], ds);
    wgmma_p2<0>(dm, &Wf[24], ds + 4);
#pragma unroll
    for (int ks = 1; ks < 6; ks++) {
        wgmma_p2<1>(dp, &Wf[4 * ks], ds + (ks >> 1) * (8192 >> 4) + (ks & 1) * 2);
        wgmma_p2<1>(dm, &Wf[24 + 4 * ks], ds + (ks >> 1) * (8192 >> 4) + (ks & 1) * 2 + 4);
        if (ks == 3) wg_commit();
    }
    wg_commit();
    wg_wait<1>();
    if (wg >= 0 && (wg < 2 || s < 5)) asm volatile("bar.arrive %0,256;" ::"r"(wg == 2 ? 4 : 5 + wg) : "memory");
    mbar_wait(ofree);
    wg_wait<0>();
    pin(dp); pin(dm);
    if (lane == 0) mbar_arrive(empty);
#pragma unroll
    for (int nb = 0; nb < NB; nb++) {
        float pr = dp[4 * nb] - dp[4 * nb + 3], pi = dp[4 * nb + 1] + dp[4 * nb + 2];
        float mr = dm[4 * nb] - dm[4 * nb + 3], mi = dm[4 * nb + 1] + dm[4 * nb + 2];
        sts32(a0 + nb * 1024, tagged(pk(pr + mr, pi - mi), m, TAGZ));
        sts32((a0 ^ 144) + nb * 1024, tagged(pk(pi + mi, mr - pr), m, TAGZ));
    }
}

__device__ __forceinline__ bool p3_unit(uint32_t blk, uint32_t cst, int wg, int wq, int lane) {
    int g = lane >> 2, q = lane & 3;
    uint32_t T[12];
#pragma unroll
    for (int v = 0; v < 3; v++) { uint4 x = lds128(cst + C_P3 + (v * 32 + lane) * 16); T[4 * v] = x.x; T[4 * v + 1] = x.y; T[4 * v + 2] = x.z; T[4 * v + 3] = x.w; }
    uint32_t ad[3][2];
#pragma unroll
    for (int nu = 0; nu < 3; nu++)
#pragma unroll
        for (int ka = 0; ka < 2; ka++) {
            int r = 2 * (min(4 * nu + (g >> 1), 10) * 11 + (ka ? min(8 + q, 10) : q)) + (g & 1);
            ad[nu][ka] = blk + r * 128 + ((((2 * wq) ^ r) & 7) << 4);
        }
    uint32_t o[2][4][4], bad = 0;
#pragma unroll
    for (int h = 0; h < 2; h++) {
        uint32_t z[3][3][4];
#pragma unroll
        for (int nu = 0; nu < 3; nu++)
#pragma unroll
            for (int ka = 0; ka < 3; ka++) {
                uint4 x = lds128((ad[nu][ka >> 1] ^ (h << 4)) + (ka & 1) * 1024);
                z[nu][ka][0] = x.x; z[nu][ka][1] = x.y; z[nu][ka][2] = x.z; z[nu][ka][3] = x.w;
                if (h) bad |= x.w ^ TAGZ;
            }
#pragma unroll
        for (int j = 0; j < 2; j++) {
            float d2[2][2][4];
#pragma unroll
            for (int e = 0; e < 2; e++) {
                const int ch = 2 * j + e;
                uint32_t P[3][2];
#pragma unroll
                for (int nu = 0; nu < 3; nu++) {
                    float d[4];
                    mma16z(d, T[0], T[1], T[2], T[3], z[nu][0][ch], z[nu][1][ch]);
                    mma8(d, T[4], T[5], z[nu][2][ch]);
                    P[nu][0] = pk(d[0], d[1]); P[nu][1] = pk(d[2], d[3]);
                }
#pragma unroll
                for (int be = 0; be < 2; be++) {
                    mma16z(d2[e][be], P[0][0], P[0][1], P[1][0], P[1][1], T[8 + 2 * be], T[9 + 2 * be]);
                    mma8(d2[e][be], P[2][0], P[2][1], T[6 + be]);
                }
            }
#pragma unroll
            for (int be = 0; be < 2; be++)
#pragma unroll
                for (int k = 0; k < 4; k++) o[be][k][2 * h + j] = pk(d2[0][be][k], d2[1][be][k]);
        }
    }
    if (bar_any(1 + wg, 128, wq == 3 && (bad & TAGM))) return false;
    const int p = 4 * g + q;
    const uint32_t a = blk + p * 64 + ((wq ^ ((p >> 1) & 3)) << 4);
#pragma unroll
    for (int be = 0; be < 2; be++)
#pragma unroll
        for (int k = 0; k < 4; k++)
            sts128(a + (2 * be + (k & 1)) * 4096 + (k >> 1) * 2048, o[be][k][0], o[be][k][1], o[be][k][2], o[be][k][3]);
    return true;
}

template <int Z> __device__ __forceinline__ int s_row(int gr, int st, int cg, int ci, unsigned cm) {
    const int sf = (ci >> 2) & 1, y = 3 * (3 * gr + cg) + ((st ^ sf) << (Z ^ (cm >> 31))), pg = y >> 2;
    const int r = (pg << 14) | ((ci & 1) << 6) | ((ci & 2) << 8) | ((y & 1) << 10) | ((y & 2) << 11);
    return r | ((((Z ? st : sf) ^ ci ^ (ci >> 1) ^ y ^ (y >> 1) ^ (cm >> pg)) & 1) << 5);
}
__device__ __forceinline__ int w_row(int fw, int hg, int cg, int io, unsigned cm) {
    const int home = fw == 5 ? hg >> 1 : fw > 5;
    const int col = fw == 5 ? 15 + (hg & 1) : 3 * (fw > 5 ? fw - 6 : fw) + hg;
    const int z = 9 * col + 3 * cg + io, pg = NPS + (z >> 5);
    const int r = (pg << 12) | ((z & 1) << 4) | ((z & 6) << 6) | ((z & 24) << 7);
    return r | (((home ^ __popc(z & 15) ^ (cm >> pg)) & 1) << 3);
}
__device__ __forceinline__ int s_tile(int t) { return ((t & 3) << 7) | ((t & 4) << 9) | ((t & 8) << 10); }
__device__ __forceinline__ int xoff(int r) { return r < 3 ? O_B0 + r * BLK : (r == 3 ? O_B4 : O_B3); }
__device__ __forceinline__ int soff(int r) { return r == 2 ? O_B2 + 2048 : xoff(r); }
__device__ __forceinline__ int zoff(int r) { return r == 0 ? O_B2 + 2048 : (r == 1 ? O_B3 : (r == 2 ? O_B4 : (r == 3 ? O_Z3 : O_Z4))); }

__device__ __forceinline__ bool first_is_far(unsigned char* page, int c, int lane) {
    unsigned* a = reinterpret_cast<unsigned*>(page + (size_t)(64 + 30 + (c & 1) + s_tile(c >> 1) + ((c & 96) << 4) + ((c & 128) << 5)) * 128);
    a[lane] = 0; a[1024 + lane] = 0;
    __syncwarp();
    unsigned t1 = 0, t2 = 0;
    if (lane == 0)
        asm volatile("{.reg .u32 a,b;\n atom.relaxed.gpu.global.exch.b32 a,[%2],1;\n atom.relaxed.gpu.global.exch.b32 b,[%2+4096],1;\n"
                     " and.b32 a,a,0x80000000;\n mov.u32 %0,%%clock;\n add.u32 %0,%0,a;\n and.b32 b,b,0x80000000;\n mov.u32 %1,%%clock;\n add.u32 %1,%1,b;}"
                     : "=&r"(t1), "=&r"(t2) : "l"(a + lane) : "memory");
    return (int)(t2 - t1) < 90;
}

struct Role {
    int sd, k, fp, wfw, wip, nu;
    __device__ __forceinline__ Role(int rho) {
        sd = rho >= NH;
        const int kk = sd ? NCTA - 1 - rho : rho;
        k = NH - 1 - kk;
        nu = k < NUH - 4 * NH ? 5 : 4;
        fp = k >= 5 + sd ? 60 * sd + k - 5 : -1;
        wfw = kk < 60 ? 6 * sd + kk / 12 : 5; wip = kk < 60 ? kk % 12 : 6 * sd + kk - 60;
    }
};
__device__ __forceinline__ int stage_row(const Role& R, int s, int lane, unsigned cm, int z) {
    const int ci = R.fp > 0 ? (R.fp - 1) / 15 : 0, rw = 2 * (ci ? R.fp - 15 * ci - 1 : R.fp);
    return (z ? s_row<1>(s, lane & 1, lane >> 1, ci, cm) : s_row<0>(s, lane & 1, lane >> 1, ci, cm)) + rw;
}
__device__ __forceinline__ int stage_off(int s, int lane) { return (lane >> 1) * 8192 + (lane & 1) * (s < 6 ? 4096 : 512); }
template <int Z> __device__ __forceinline__ int unit_row(const Role& R, int r, int lane, unsigned cm) {
    const int u = r * NH + R.k, ts = u / 3;
    return s_row<Z>(ts >> 4, R.sd, u - 3 * ts, lane, cm) + s_tile(ts);
}
__device__ __forceinline__ int unit_off(int lane) { return lane ? 3840 * lane + 256 : 0; }

__global__ void __launch_bounds__(512, 1) fftconv_kernel(const __grid_constant__ Maps mp) {
    extern __shared__ __align__(1024) unsigned char smraw[];
    const uint32_t sm = s2u(smraw);
    const uint32_t bar = sm + O_BAR;
    const int tid = threadIdx.x, lane = tid & 31, warp = __shfl_sync(0xffffffffu, tid >> 5, 0), cta = blockIdx.x;
    const uint32_t tstart = clock();
    auto init_bars = [&](int gi) {
        if (lane == 0) {
            const int cnt = gi < 5 || gi >= 10 ? 1 : (gi < 7 ? 12 : 4);
#pragma unroll
            for (int i = 0; i < 8; i++) mbar_init(bar + 64 * gi + 8 * i, cnt);
            fence_async_s();
        }
        __syncwarp();
    };

    if (warp >= 12) {
        asm volatile("setmaxnreg.dec.sync.aligned.u32 32;");
        if (warp == 13) {
            const bool far = first_is_far(mp.s, cta, lane);
            if (lane == 0) sts32(sm + O_SIDE, far);
            __syncwarp();
            asm volatile("bar.arrive 10,64;" ::: "memory");
            TR(5, 20);
            if (lane == 0) {
                const int side = (far ^ 1 ^ __popc(cta >> 5)) & 1;
                const unsigned t = atomicAdd(mp.cnt + CT + side, 1u);
                sts32(sm + O_ROLE, side ? NCTA - 1 - t : t);
            }
            __syncwarp();
            TR(5, 21);
            bar_sync(0, 512);
            asm volatile("bar.arrive 11,64;" ::: "memory");
        } else if (warp == 14) {
            asm volatile("bar.arrive 0,512;" ::: "memory");
            const int p = cta % (NPAGE - 1);
            const bool far = first_is_far(mp.s + ((size_t)(p + 1) << 21), cta, lane);
            bar_sync(10, 64);
            if (lane == 0) red_add(mp.cnt + CV + (p >> 2), 1u << (8 * (p & 3) + 4 * (far ^ lds32(sm + O_SIDE))));
            unsigned v; int it = 0;
            do {
                asm volatile("ld.acquire.gpu.global.u32 %0,[%1];" : "=r"(v) : "l"(mp.cnt + CV + ((lane >> 2) & 7)) : "memory");
                v = (v >> (8 * (lane & 3))) & 255;
            } while (__any_sync(0xffffffffu, lane < NPAGE - 1 && (v & 15) + (v >> 4) < (lane < NCTA % (NPAGE - 1) ? 7u : 6u)) && ++it < (1 << 18));
            const unsigned cm = __ballot_sync(0xffffffffu, lane < NPAGE - 1 && (v >> 4) > (v & 15)) << 1;
            bar_sync(11, 64);
            if (lane == 0) { sts32(sm + O_CM, cm | (lds32(sm + O_EP) << 31)); mbar_arrive(bar + 8 * BCM); }
            __syncwarp();
            TR(5, 22);
        } else {
            if (warp == 15) {
                unsigned e = 0;
                if (lane == 0) asm volatile("ld.relaxed.gpu.global.u32 %0,[%1];" : "=r"(e) : "l"(mp.cnt + CE) : "memory");
                init_bars(13); init_bars(14);
                if (lane == 0) sts32(sm + O_EP, e);
            } else {
                init_bars(0);
                if (lane == 0) { mbar_expect(bar + 8 * BC, C_BYTES); bulk_ld(sm + O_C, mp.ctab, C_BYTES, bar + 8 * BC); }
            }
            __syncwarp();
            bar_sync(0, 512);
        }
        const Role R(__shfl_sync(0xffffffffu, lds32(sm + O_ROLE), 0));

        if (warp == 12) {
            auto load_x = [&](int r) {
                const int u = r * NH + R.k, ts = u / 3, cg = u - 3 * ts, tr = ts / 14, th = 7 * R.sd + tr, tw = ts - 14 * tr;
                const uint32_t b = bar + 8 * (BX + r);
                if (lane == 0) mbar_expect(b, BLK);
                __syncwarp();
                const int t = lane >> 1, top = lane & 1;
                int w0 = 16 * tw - 8 + 8 * t; if (w0 < 0) w0 += 224;
#pragma unroll 1
                for (int i = 0; i < 3; i++) {
                    while ((int)(clock() - tstart) < (3 * r + i) * XD + XD0) {}
                    if (t == i) tma_ld3(sm + xoff(r) + t * 11264 + (top ? 0 : 3072), top ? &mp.x6 : &mp.x16, b, 32 * cg, w0, top ? (th ? 16 * th - 6 : 218) : 16 * th);
                    __syncwarp();
                }
            };
            TR(3, 18);
            if (lane < 2) mbar_expect(bar + 8 * (BW + lane), 2 * 18816 + (lane ? 0 : WT_BYTES));
            __syncwarp();
            if (lane == 0) bulk_ld(sm + O_WT, mp.wtab + R.wfw * WT_BYTES, WT_BYTES, bar + 8 * BW);
            if (lane < 4)
                tma_ld3(sm + ((lane & 2) ? O_W1 : O_W0) + (lane & 1) * WPIECE, &mp.w, bar + 8 * (BW + (lane >> 1)), 0,
                        3 * (8 * (R.wip >> 1) + 2 * (R.wip & 1) + 4 * (lane & 1) + (lane >> 1)), 0);
            __syncwarp();
            TR(3, 20);
#pragma unroll 1
            for (int r = 0; r < R.nu; r++) {
                if (r >= 3) mbar_wait(bar + 8 * (r == 3 ? BWC + 1 : BDW));
                load_x(r);
                TR(3, 21 + r);
            }
            mbar_wait(bar + 8 * BCM);
            const unsigned cm = __shfl_sync(0xffffffffu, lds32(sm + O_CM), 0);
            auto need = [&](int i) { mbar_wait(bar + 8 * (BFL + i)); fence_async_g(); };
            auto gap = [&](uint32_t t0, int d) { while ((int)(clock() - t0) < d) {} };
            if (R.fp >= 0) {
                {
                    const int fw = R.fp / 11, fh = R.fp - 11 * fw, b = lane / 3, io = lane - 3 * b;
                    const int row = w_row(fw, fh >> 2, b ? b - 1 : 2, io, cm) + 2 * (fh & 3);
                    need(7);
                    if (lane < 3) mbar_expect(bar + 8 * (BWF + lane), STG);
                    __syncwarp();
                    TR(3, 17);
                    const uint32_t t0 = clock();
#pragma unroll 1
                    for (int i = 0; i < 9; i++) {
                        if (i == 6) mbar_wait(bar + 8 * BD1);
                        gap(t0, i * LPW);
                        if (lane == i) tma_ld4(sm + O_IN + lane * 8192, &mp.wf, bar + 8 * (BWF + b), 0, row, 0, 0);
                        __syncwarp();
                    }
                    TR(3, 15);
                }
                int buf = 0;
#pragma unroll 1
                for (int s = 0; s < 7; s++) {
                    const int row = stage_row(R, s, lane, cm, 0);
                    const uint32_t dst = sm + O_IN + buf * STG + stage_off(s, lane);
                    need(s);
                    mbar_wait(bar + 8 * (s >= 3 ? BPE + s - 3 : BWE + s));
                    if (lane == 0) mbar_expect(bar + 8 * (BPF + s), s < 6 ? STG : 3072);
                    __syncwarp();
                    if (lane < 6) tma_ld5(dst, s < 6 ? &mp.p16 : &mp.p2, bar + 8 * (BPF + s), 0, row, 0, 0, 0);
                    __syncwarp();
                    buf = buf == 2 ? 0 : buf + 1;
                    TR(3, 3 + s);
                }
            }
#pragma unroll 1
            for (int r = 0; r < R.nu; r++) {
                const int row = unit_row<1>(R, r, lane, cm);
                if (r == 0) { mbar_wait(bar + 8 * (BD1 + R.nu - 2)); mbar_wait(bar + 8 * (BD1 + R.nu - 1)); }
                if (r >= 3 && R.fp >= 0) { mbar_wait(bar + 8 * ((r == 3 ? BPE : BD2) + 4)); mbar_wait(bar + 8 * ((r == 3 ? BPE : BD2) + 5)); }
                if (lane == 0) mbar_expect(bar + 8 * (BZ + r), SLAB);
                need(8 + (r * NH + R.k) / 48);
                const uint32_t t0 = clock();
#pragma unroll 1
                for (int i = 0; i < 4; i++) {
                    if (r < 3) gap(t0, i * 2 * LPZ);
                    if ((lane & 27) == i) tma_ld2(sm + zoff(r) + unit_off(lane), lane ? &mp.s30 : &mp.s32, bar + 8 * (BZ + r), 0, row);
                    __syncwarp();
                }
                TR(3, 10 + r);
            }
        } else if (warp == 13) {
            const unsigned* myc = mp.cnt + (lane == 7 ? CW + (R.fp >= 0 ? R.fp / 11 : 0) : (lane & 15));
            const unsigned tgt = lane < 6 ? 96 : (lane < 8 ? 12 : NFP);
            bool open = lane < 15;
            mbar_wait(bar + 8 * BDW); mbar_wait(bar + 8 * (BDW + 1));
            if (lane == 0) { asm volatile("fence.acq_rel.gpu;" ::: "memory"); red_add(mp.cnt + CW + R.wfw); TR(7, 0); }
            __syncwarp();
            int it = 0;
            while (__any_sync(0xffffffffu, open) && ++it < (1 << 18)) {
                unsigned v;
                asm volatile("ld.acquire.gpu.global.u32 %0,[%1];" : "=r"(v) : "l"(myc) : "memory");
                if (open && v >= tgt) { mbar_arrive(bar + 8 * (BFL + lane)); open = false; TRL(5, lane); }
            }
            unsigned last = 0;
            if (lane == 0) last = atomicAdd(mp.cnt + CD, 1u) == NCTA - 1;
            if (__shfl_sync(0xffffffffu, last, 0)) { mp.cnt[lane] = 0; mp.cnt[32 + lane] = lane == CE - 32 ? lds32(sm + O_EP) + 1 : 0; }
        } else {
            const int me = warp & 1;
            uint32_t next = tstart + T0;
            auto pace = [&](int cost) {
                uint32_t now;
                do { now = clock(); } while ((int)(now - next) < 0);
                next = ((int)(now - next) > CREDIT ? now - CREDIT : next) + cost;
            };
            const int bal = R.nu == 5 ? 236 : 275;
            mbar_wait(bar + 8 * BCM);
            const unsigned cm = __shfl_sync(0xffffffffu, lds32(sm + O_CM), 0);
            {
                const int iq = 2 * R.wip + me, w = lane / 3, hg = lane - 3 * w;
                unsigned char* dst = mp.s + (size_t)w_row(R.wfw, hg, w, iq >> 3, cm) * 512 + ((iq & 3) << 14) + ((iq & 4) << 16);
                const uint32_t src = sm + (me ? O_W0 : O_B3) + w * 11264 + hg * 4096;
                fence_async_g();
                if (me) { mbar_wait(bar + 8 * (BIS + 17)); next = lds32(sm + O_NEXT); }
#pragma unroll 1
                for (int i = 0; i < 3; i++) {
                    mbar_wait(bar + 8 * (BRW + 3 * me + i));
                    if (i == 0) TR(4, me);
                    pace((RW * 11 / 4 * bal) >> 8);
                    if (w == i) bulk_st(dst, src, hg < 2 ? 4096 : 3072);
                    __syncwarp();
                }
                if (lane == 0) { sts32(sm + O_NEXT, next); mbar_arrive(bar + 8 * (BIS + 17 + me)); }
                bulk_commit(); bulk_wait<0>();
                __syncwarp();
                if (lane == 0) mbar_arrive(bar + 8 * (BDW + me));
                TR(6, me);
            }
            const int n2 = R.fp >= 0 ? R.nu + 7 : R.nu;
#pragma unroll 1
            for (int j = me; j < n2 + R.nu; j += 2) {
                int dn = 0, cn = 0;
                auto turn = [&](int rd) {
                    mbar_wait(bar + 8 * rd);
                    mbar_wait(bar + 8 * (j ? BIS + j - 1 : BIS + 18));
                    next = lds32(sm + O_NEXT);
                    if (EARLY == 2 && dn && lane == 0) red_add(mp.cnt + cn);
                };
                if (j < R.nu) {
                    const int row = unit_row<0>(R, j, lane, cm);
                    const uint32_t src = sm + soff(j) + unit_off(lane);
                    dn = BD1 + j; cn = CX + (j * NH + R.k) / 48;
                    turn(BR1 + j);
                    TR(4, 2 + j);
#pragma unroll 1
                    for (int i = 0; i < 4; i++) {
                        pace((R1 * 121 / 64 * bal) >> 8);
                        if ((lane & 27) == i) tma_st2(lane == 0 || (lane == 4 && !R.sd) ? &mp.s32 : &mp.s30, src, 0, row);
                        __syncwarp();
                    }
                } else if (j < n2) {
                    const int s = j - R.nu, l6 = lane & 7;
                    const int row = stage_row(R, s, l6, cm, lane < 8);
                    const uint32_t src = sm + O_OUT + (s & 1) * STG + stage_off(s, l6);
                    const int mine = lane < 6 || (R.fp == 15 && lane < 16 && (lane & 9) == 9) ? l6 >> 1 : -1;
                    dn = BD2 + s; cn = CY + s;
                    turn(BR2 + s);
                    TR(4, 7 + s);
#pragma unroll 1
                    for (int w = 0; w < 3; w++) {
                        pace(s < 6 ? 2 * R2 : R2 / 4);
                        if (mine == w) tma_st5(s < 6 ? &mp.p16 : &mp.p2, src, 0, row, 0, 0, 0);
                        __syncwarp();
                    }
                } else {
                    const int r = j - n2, u = r * NH + R.k, ts = u / 3, cg = u - 3 * ts, tr = ts / 14, th = 7 * R.sd + tr, tw = ts - 14 * tr;
                    turn(BR3 + r);
                    TR(4, 14 + r);
#pragma unroll 1
                    for (int c = 0; c < 2; c++) {
                        if (r < 3) pace(2 * R3);
                        if (lane == 0) tma_st4(&mp.y, sm + zoff(r) + c * 8192, 32 * cg, 0, 16 * th, 4 * tw + 2 * c);
                        __syncwarp();
                    }
                }
                if (lane == 0) { sts32(sm + O_NEXT, next); mbar_arrive(bar + 8 * (BIS + j)); if (EARLY == 1 && dn) red_add(mp.cnt + cn); }
                bulk_commit(); bulk_wait<0>();
                __syncwarp();
                if (dn && lane == 0) {
                    if (EARLY == 0) red_add(mp.cnt + cn);
                    mbar_arrive(bar + 8 * dn);
                    TR(6, dn - BDW);
                }
                __syncwarp();
            }
            TR(4, 19 + me);
        }
    } else {
        asm volatile("setmaxnreg.inc.sync.aligned.u32 160;");
        const int wg = warp >> 2, wq = warp & 3;
        if (PFW & 1) {
            if (tid < 54) { int l = cta * 54 + tid; if (l < 7056) pf_l2(mp.wraw + l * 128); }
            else if (tid >= 64 && tid < 69) { int l = cta * 5 + tid - 64; if (l < 594) pf_l2(mp.wtab + l * 128); }
            else if (tid >= 96 && tid < 105) asm volatile("prefetch.tensormap [%0];" ::"l"(&mp.w + (tid - 96)) : "memory");
        }
        init_bars(warp + 1);
        if ((PFW & 2) && tid >= 128 && tid < 128 + 112) {
            int l = (cta >> 1) * 112 + tid - 128 + (112 * (cta & 1) - 6) * 336;
            pf_l2(mp.x + (size_t)(l < 0 ? l + 224 * 336 : l) * 128);
        }
        bar_sync(0, 512);
        const Role R(__shfl_sync(0xffffffffu, lds32(sm + O_ROLE), 0));
#pragma unroll 1
        for (int it = 0; it <= wg; it++) {
            const int j = it > 0, cg = j ? wg + it - 2 : wg;
            mbar_wait(bar + 8 * (j == 0 && wg ? BWL + wg - 1 : BW + j));
            TR(wg, 24 + 2 * it);
            wgen(sm + (j ? O_W1 : O_W0), sm + O_WT, sm + (j ? O_W0 : O_B3) + cg * 11264, 4 * cg + wq, (2 * R.wip + j) & 3, lane, bar + 8 * (BWC + j),
                 j == 0 && wg < 2 ? bar + 8 * (BWL + wg) : 0, bar + 8 * (j ? BWC : BW));
            staged(bar + 8 * (BRW + 3 * j + cg), lane);
            TR(wg, 25 + 2 * it);
        }
        mbar_wait(bar + 8 * BC);
#pragma unroll 1
        for (int r = wg; r < R.nu; r += 3) {
            mbar_wait(bar + 8 * (BX + r));
            TR(wg, 1 + 2 * (r / 3));
            p1_unit(sm + xoff(r), sm + soff(r), sm + O_C, wg, wq, lane);
            staged(bar + 8 * (BR1 + r), lane);
            TR(wg, 2 + 2 * (r / 3));
        }
        if (R.fp >= 0) {
            uint32_t Wf[48];
            const int g = lane >> 2, q = lane & 3, ck = 2 * wq + (g >> 2);
            {
                const int b = wg == 2 ? 0 : wg + 1;
                const uint32_t p = sm + O_IN + b * STG + q * 1024 + wq * 128 + ((g ^ (2 * q) ^ (4 * ((R.fp % 11) & 1))) << 4);
                mbar_wait(bar + 8 * (BWF + b));
                TR(wg, 5);
#pragma unroll
                for (int i = 0; i < 12; i++) {
                    uint4 v = lds128((p ^ (i >= 6 ? 544 : 0)) + (i % 6) * 4096);
                    Wf[4 * i] = v.x; Wf[4 * i + 1] = v.y; Wf[4 * i + 2] = v.z; Wf[4 * i + 3] = v.w;
                }
                staged(bar + 8 * (BWE + b), lane);
            }
            const uint32_t o0 = sm + O_OUT + wg * 8192 + (2 * q) * 128 + ((ck ^ (2 * q)) << 4) + (g & 3) * 4;
            const uint32_t m = wq == 3 && g == 7 ? TAGM : 0;
            uint32_t ph = 0;
            auto landed = [&](int s, uint32_t in) {
                const int t = tid & 127;
                const uint32_t tw = ((7 ^ (t & 7)) << 4) + 12;
                const uint32_t c0 = in + (s < 6 ? t : min(t >> 3, 2) * 64 + (t & 7)) * 128 + tw, c1 = s < 6 ? in + (128 + (t & 63)) * 128 + tw : c0;
                mbar_wait(bar + 8 * (BPF + s));
#pragma unroll 1
                for (int it = 0; it < 4096; it++) {
                    if (!bar_any(1 + wg, 128, ((lds32(c0) ^ TAGX) | (lds32(c1) ^ TAGX)) & TAGM)) break;
                    fence_async_s();
                    bar_sync(7, 384);
                    if (warp == 0) {
                        TRC(0);
                        if (lane == 0) mbar_expect(bar + 8 * BRT, s < 6 ? STG : 3072);
                        __syncwarp();
                        const int l = laneid();
                        if (l < 6) tma_ld5(in + stage_off(s, l), s < 6 ? &mp.p16 : &mp.p2, bar + 8 * BRT, 0, stage_row(Role(lds32(sm + O_ROLE)), s, l, lds32(sm + O_CM), 0), 0, 0, 0);
                        __syncwarp();
                    }
                    mbar_wait_ph(bar + 8 * BRT, ph); ph ^= 1;
                }
            };
            int buf = 0;
            mbar_wait(bar + 8 * BD1);
#pragma unroll 1
            for (int s = 0; s < 6; s++) {
                landed(s, sm + O_IN + buf * STG);
                p2_step<8>(Wf, sm + O_IN + buf * STG, o0 + (s & 1) * STG, m, bar + 8 * (s >= 2 ? BD2 + s - 2 : BD1 + 1), bar + 8 * (BPE + s), lane, PP ? wg : -1, s);
                buf = buf == 2 ? 0 : buf + 1;
                staged(bar + 8 * (BR2 + s), lane);
                TR(wg, 6 + s);
            }
            landed(6, sm + O_IN);
            p2_step<1>(Wf, sm + O_IN, o0, m, bar + 8 * (BD2 + 4), bar + 8 * (BPE + 6), lane, -1, 6);
            staged(bar + 8 * (BR2 + 6), lane);
            TR(wg, 12);
        }
        uint32_t ph = 0;
#pragma unroll 1
        for (int r = wg; r < R.nu; r += 3) {
            mbar_wait(bar + 8 * (BZ + r));
            TR(wg, 13 + 2 * (r / 3));
#pragma unroll 1
            for (int it = 0; it < 4096; it++) {
                if (p3_unit(sm + zoff(r), sm + O_C, wg, wq, laneid())) break;
                if (wq == 0) {
                    TRC(1);
                    fence_async_s();
                    if (lane == 0) mbar_expect(bar + 8 * (BRT + 1 + wg), SLAB);
                    __syncwarp();
                    const int l = laneid();
                    if (l < 8) tma_ld2(sm + zoff(r) + unit_off(l), l ? &mp.s30 : &mp.s32, bar + 8 * (BRT + 1 + wg), 0, unit_row<1>(Role(lds32(sm + O_ROLE)), r, l, lds32(sm + O_CM)));
                    __syncwarp();
                }
                mbar_wait_ph(bar + 8 * (BRT + 1 + wg), ph); ph ^= 1;
            }
            staged(bar + 8 * (BR3 + r), lane);
            TR(wg, 14 + 2 * (r / 3));
        }
    }
}

typedef CUresult (*EncFn)(CUtensorMap*, CUtensorMapDataType, cuuint32_t, void*, const cuuint64_t*, const cuuint64_t*, const cuuint32_t*,
                          const cuuint32_t*, CUtensorMapInterleave, CUtensorMapSwizzle, CUtensorMapL2promotion, CUtensorMapFloatOOBfill);

void enc(EncFn f, CUtensorMap* m, void* p, int rank, const cuuint64_t* dims, const cuuint64_t* strides, const cuuint32_t* box,
         CUtensorMapSwizzle sw, CUtensorMapL2promotion pr = CU_TENSOR_MAP_L2_PROMOTION_NONE) {
    cuuint32_t es[5] = {1, 1, 1, 1, 1};
    f(m, CU_TENSOR_MAP_DATA_TYPE_BFLOAT16, rank, p, dims, strides, box, es, CU_TENSOR_MAP_INTERLEAVE_NONE, sw, pr, CU_TENSOR_MAP_FLOAT_OOB_FILL_NONE);
}

}

extern "C" void kernel_launch(void* const* d_in, const int* in_sizes, int n_in, void* d_out, int out_size) {
    void* fn = nullptr; cudaDriverEntryPointQueryResult qr;
    cudaGetDriverEntryPoint("cuTensorMapEncodeTiled", &fn, cudaEnableDefault, &qr);
    EncFn f = (EncFn)fn;
    void* pS; cudaGetSymbolAddress(&pS, g_S);
    pS = (void*)(((uintptr_t)pS + (1u << 21) - 1) & ~(uintptr_t)((1u << 21) - 1));
    Maps mp;
    cudaGetSymbolAddress((void**)&mp.ctab, g_ctab); cudaGetSymbolAddress((void**)&mp.wtab, g_wtab); cudaGetSymbolAddress((void**)&mp.cnt, g_cnt);
    mp.s = (unsigned char*)pS; mp.x = (const unsigned char*)d_in[0]; mp.wraw = (const unsigned char*)d_in[1];
    { cuuint64_t d[4] = {256, NPAGE << 12, 4, 2}, s[3] = {512, 1 << 14, 1 << 18}; cuuint32_t b[4] = {256, 2, 4, 2}; enc(f, &mp.wf, pS, 4, d, s, b, CU_TENSOR_MAP_SWIZZLE_NONE); }
    {
        cuuint64_t d[3] = {96, 224, 224}, s[2] = {192, 43008};
        cuuint32_t b6[3] = {32, 8, 6}, b16[3] = {32, 8, 16};
        enc(f, &mp.x6, d_in[0], 3, d, s, b6, CU_TENSOR_MAP_SWIZZLE_64B, CU_TENSOR_MAP_L2_PROMOTION_L2_128B);
        enc(f, &mp.x16, d_in[0], 3, d, s, b16, CU_TENSOR_MAP_SWIZZLE_64B, CU_TENSOR_MAP_L2_PROMOTION_L2_128B);
    }
    { cuuint64_t d[4] = {96, 4, 224, 56}, s[3] = {192, 43008, 768}; cuuint32_t b[4] = {32, 4, 16, 2}; enc(f, &mp.y, d_out, 4, d, s, b, CU_TENSOR_MAP_SWIZZLE_64B); }
    {
        cuuint64_t d[2] = {64, NPAGE << 14}, s[1] = {128};
        cuuint32_t b32[2] = {64, 32}, b30[2] = {64, 30};
        enc(f, &mp.s32, pS, 2, d, s, b32, CU_TENSOR_MAP_SWIZZLE_128B);
        enc(f, &mp.s30, pS, 2, d, s, b30, CU_TENSOR_MAP_SWIZZLE_128B);
    }
    {
        cuuint64_t d[5] = {64, NPAGE << 14, 4, 2, 2}, s[4] = {128, 1 << 14, 1 << 18, 1 << 20};
        cuuint32_t b16[5] = {64, 2, 4, 2, 2}, b2[5] = {64, 2, 2, 1, 1};
        enc(f, &mp.p16, pS, 5, d, s, b16, CU_TENSOR_MAP_SWIZZLE_128B);
        enc(f, &mp.p2, pS, 5, d, s, b2, CU_TENSOR_MAP_SWIZZLE_128B);
    }
    { cuuint64_t d[3] = {64, 144, 49}, s[2] = {128, 18432}; cuuint32_t b[3] = {64, 3, 49}; enc(f, &mp.w, d_in[1], 3, d, s, b, CU_TENSOR_MAP_SWIZZLE_128B); }
    cudaFuncSetAttribute(fftconv_kernel, cudaFuncAttributeMaxDynamicSharedMemorySize, SMEM);
    fftconv_kernel<<<NCTA, 512, SMEM>>>(mp);
}
```

```cpp
#include <cuda_runtime.h>
#include <cuda_bf16.h>
#include <cuda.h>
#include <stdint.h>

#define TUNABLES {320, 310, 250, 280, 500, 250, 0, 1, 3900, 450, 0, 1, 1, 0, 600, 0}
constexpr int c_tune[16] = TUNABLES;
template <int I> struct TuneV { static constexpr int v = c_tune[I]; };
#define TV(i) TuneV<i>::v
#define RW TV(0)
#define R1 TV(1)
#define R2 TV(2)
#define R3 TV(3)
#define CREDIT TV(4)
#define LPW TV(5)
#define LPZ TV(6)
#define EARLY TV(7)
#define T0 TV(8)
#define XD TV(9)
#define XD0 TV(10)
#define PFW TV(11)
#define PP TV(12)
#define FORCE TV(13)
#define WD TV(14)
#define SPLIT 3

namespace {

constexpr int NCTA = 132, NH = 66;
constexpr int NUH = 294;
constexpr int NFP = 121;
constexpr int BLK = 33792;
constexpr int SLAB = 242 * 128;
constexpr int WPIECE = 19456;
constexpr int STG = 24576;
constexpr int NPS = 16, NPAGE = 21;
constexpr int O_B4 = 0, O_B0 = 87040, O_B2 = O_B0 + 2 * BLK, O_B3 = O_B0 + 3 * BLK;
constexpr int O_W1 = 0, O_W0 = 2 * WPIECE, O_WT = 4 * WPIECE;
constexpr int O_IN = 33792, O_OUT = O_IN + 3 * STG, O_Z3 = O_IN + STG, O_Z4 = 124928;
constexpr int O_C = 222208, O_BAR = 230912, SMEM = 232448;
constexpr int C_P1A = 0, C_P1B = 2560, C_P3 = 7168, C_BYTES = 8704, WT_BYTES = 6912;
constexpr int BC = 0, BW = 1, BX = 3, BZ = 8, BWF = 13, BPF = 16, BDW = 23, BD1 = 25, BD2 = 30;
constexpr int BPE = 40, BR2 = 47, BWC = 54;
constexpr int BRW = 56, BWL = 62, BR1 = 64, BR3 = 69, BWE = 74;
constexpr int BFL = 80, BCM = 95, BIS = 96, BRT = 116;
constexpr int O_NEXT = O_BAR + 1016, O_ROLE = O_BAR + 1000, O_PT = O_BAR + 976, O_CM = O_BAR + 1008, O_EP = O_BAR + 1012;
constexpr uint32_t TAGM = 0x00010001u, TAGX = 0x00000001u, TAGZ = 0x00010000u;

constexpr uint16_t LUT_A[11] = {0x3f95, 0x3f92, 0x3f8c, 0x3f83, 0x3f6f, 0x3f53, 0x3f33, 0x3f0f, 0x3ed1, 0x3e7e, 0x3daa};
constexpr uint16_t LUT_B[11] = {0x3fe9, 0x3fe4, 0x3fdb, 0x3fcd, 0x3fbb, 0x3fa5, 0x3f8c, 0x3f60, 0x3f23, 0x3ec7, 0x3e05};
constexpr uint16_t LUT_W[12] = {0x3abb, 0x3ab9, 0x3ab3, 0x3aaa, 0x3a9d, 0x3a8d, 0x3a75, 0x3a4a, 0x3a1b, 0x39d3, 0x3955, 0};
constexpr uint16_t basis(int setb, int f, int a, int sn) {
    if (f < 0 || f > 10 || a < 0 || a > 21) return 0;
    int k = ((2 * f + 1) * (2 * a - 21) - 22 * sn + 88 * 7) % 88;
    if (k > 44) k = 88 - k;
    int neg = 0;
    if (k > 22) { k = 44 - k; neg = 1; }
    return (uint16_t)((setb ? LUT_B[k >> 1] : LUT_A[k >> 1]) | (neg << 15));
}
constexpr uint16_t neg16(uint16_t v) { return v ? (uint16_t)(v ^ 0x8000) : v; }
constexpr uint16_t wcoef(int fw, int fl, int sn, int tap) {
    if (fl > 21) return 0;
    int fh = fl >> 1, kh = tap / 7, kw = tap - 7 * kh;
    int u = (2 * fh + 1) * kh;
    if (fl & 1) u = -u;
    int k = (u + (2 * fw + 1) * kw - 11 * sn + 44 * 4) % 44;
    if (k > 22) k = 44 - k;
    int neg = 0;
    if (k > 11) { k = 22 - k; neg = 1; }
    return (uint16_t)(LUT_W[k] | (neg << 15));
}
struct alignas(128) CTab { uint16_t v[C_BYTES / 2]; };
struct alignas(128) WTab { uint16_t v[WT_BYTES / 2]; };
constexpr CTab make_ctab() {
    CTab t{};
    for (int lane = 0; lane < 32; lane++) {
        int g = lane >> 2, q = lane & 3;
        for (int r = 0; r < 18; r++) {
            int quad = r >> 2, j = r & 3;
            int set = quad < 3 ? quad : (quad == 3 ? 1 + (j >> 1) : 0);
            int sn = (j ^ (set == 0 ? g : g >> 1)) & 1;
            int t8 = quad < 3 ? 1 + (j >> 1) : 0;
            int b = 8 * t8 + 2 * q - 2;
            int fw = set == 0 ? g : (((g & 1) == set - 1) ? 8 + (g >> 1) : -1);
            int o = (C_P1A + (quad * 32 + lane) * 16 + j * 4) / 2;
            t.v[o] = basis(0, fw, b, sn); t.v[o + 1] = basis(0, fw, b + 1, sn);
        }
        for (int r = 0; r < 12; r++) {
            int o = (C_P3 + ((r >> 2) * 32 + lane) * 16 + (r & 3) * 4) / 2;
            if (r < 6) {
                int a = 6 + g + 8 * (r & 1), fh = 4 * (r >> 1) + q;
                t.v[o] = basis(0, fh, a, 0); t.v[o + 1] = basis(0, fh, a, 1);
            } else {
                int be = r < 8 ? r - 6 : (r - 8) >> 1, nu = r < 8 ? 2 : (r & 1);
                int b = 6 + 8 * be + 4 * (g & 1) + (g >> 1);
                t.v[o] = basis(1, 4 * nu + q, b, 0); t.v[o + 1] = basis(1, 4 * nu + q, b, 1);
            }
        }
    }
    for (int kc = 0; kc < 6; kc++)
        for (int nb = 0; nb < 6; nb++)
            for (int n = 0; n < 8; n++)
                for (int k = 0; k < 8; k++) {
                    int nu = kc >> 1, ds = kc & 1, im = nb & 1, fh = 4 * (nb >> 1) + (n >> 1), mi = n & 1;
                    int a = nu == 0 ? 6 + k : (nu == 1 ? 14 + k : (k < 6 ? k : -1));
                    uint16_t v = basis(0, fh, a, ds ^ im);
                    if (ds != im && (im ? mi : !mi)) v = neg16(v);
                    t.v[C_P1B / 2 + ((kc * 6 + nb) * 8 + n) * 8 + k] = v;
                }
    return t;
}
constexpr WTab make_wtab(int fw) {
    WTab t{};
    for (int nb = 0; nb < 6; nb++)
        for (int n = 0; n < 8; n++) {
            for (int tap = 0; tap < 48; tap++) t.v[(((tap >> 3) * 6 + nb) * 8 + n) * 8 + (tap & 7)] = wcoef(fw, 4 * nb + (n >> 1), n & 1, tap);
            t.v[((7 * 6 + nb) * 8 + n) * 8] = wcoef(fw, 4 * nb + (n >> 1), n & 1, 48);
        }
    return t;
}
__device__ const CTab g_ctab = make_ctab();
__device__ const WTab g_wtab[11] = {make_wtab(0), make_wtab(1), make_wtab(2), make_wtab(3), make_wtab(4), make_wtab(5),
                                    make_wtab(6), make_wtab(7), make_wtab(8), make_wtab(9), make_wtab(10)};

__device__ __align__(1024) unsigned char g_S[(size_t)(NPAGE + 1) << 21];
constexpr int CX = 0, CY = 8, CW = 16, CV = 32, CD = 40, CT = 64, CG = 96;
__device__ __align__(512) unsigned g_cnt[128];

struct Maps {
    const unsigned char* ctab; const unsigned char* wtab; const unsigned char* x; unsigned* cnt; unsigned char* s;
    const unsigned char* wraw;
    alignas(64) CUtensorMap w, x6, x16, wf, s32, s30, p16, p2, y;
};

#define TR(role, i)
#define TRL(role, i)
#define TRC(i)

__device__ __forceinline__ uint32_t s2u(const void* p) { return (uint32_t)__cvta_generic_to_shared(p); }
__device__ __forceinline__ void mbar_init(uint32_t b, int c) { asm volatile("mbarrier.init.shared::cta.b64 [%0],%1;" ::"r"(b), "r"(c) : "memory"); }
__device__ __forceinline__ void mbar_expect(uint32_t b, uint32_t tx) { asm volatile("mbarrier.arrive.expect_tx.shared::cta.b64 _,[%0],%1;" ::"r"(b), "r"(tx) : "memory"); }
__device__ __forceinline__ void mbar_arrive(uint32_t b) { asm volatile("mbarrier.arrive.shared::cta.b64 _,[%0];" ::"r"(b) : "memory"); }
__device__ __forceinline__ void mbar_wait(uint32_t b) {
    uint32_t ok; int it = 0;
    do {
        asm volatile("{.reg .pred p; mbarrier.try_wait.parity.shared::cta.b64 p,[%1],0; selp.u32 %0,1,0,p;}" : "=r"(ok) : "r"(b) : "memory");
    } while (!ok && ++it < (1 << 16));
}
__device__ __forceinline__ void mbar_wait_ph(uint32_t b, uint32_t ph) {
    uint32_t ok; int it = 0;
    do {
        asm volatile("{.reg .pred p; mbarrier.try_wait.parity.shared::cta.b64 p,[%1],%2; selp.u32 %0,1,0,p;}" : "=r"(ok) : "r"(b), "r"(ph) : "memory");
    } while (!ok && ++it < (1 << 16));
}
__device__ __forceinline__ bool bar_any(int id, int n, bool v) {
    uint32_t r;
    asm volatile("{.reg .pred p,q; setp.ne.u32 p,%3,0; bar.red.or.pred q,%1,%2,p; selp.u32 %0,1,0,q;}" : "=r"(r) : "r"(id), "r"(n), "r"((uint32_t)v) : "memory");
    return r;
}
__device__ __forceinline__ int laneid() { int l; asm volatile("mov.u32 %0,%%laneid;" : "=r"(l)); return l; }
__device__ __forceinline__ uint32_t lds32(uint32_t a) { uint32_t v; asm volatile("ld.shared.u32 %0,[%1];" : "=r"(v) : "r"(a) : "memory"); return v; }
__device__ __forceinline__ uint32_t lds16(uint32_t a) { uint32_t v; asm volatile("ld.shared.u16 %0,[%1];" : "=r"(v) : "r"(a) : "memory"); return v; }
__device__ __forceinline__ uint32_t tagged(uint32_t v, uint32_t m, uint32_t t) { return (v & ~m) | (t & m); }
__device__ __forceinline__ void red_add(unsigned* c, unsigned v = 1) { asm volatile("red.relaxed.gpu.global.add.u32 [%0],%1;" ::"l"(c), "r"(v) : "memory"); }
__device__ __forceinline__ void pf_l2(const void* p) { asm volatile("prefetch.global.L2 [%0];" ::"l"(p)); }
__device__ __forceinline__ void fence_async_s() { asm volatile("fence.proxy.async.shared::cta;" ::: "memory"); }
__device__ __forceinline__ void fence_async_g() { asm volatile("fence.proxy.async.global;" ::: "memory"); }
__device__ __forceinline__ void bulk_ld(uint32_t dst, const void* src, uint32_t bytes, uint32_t bar) {
    asm volatile("cp.async.bulk.shared::cluster.global.mbarrier::complete_tx::bytes [%0],[%1],%2,[%3];" ::"r"(dst), "l"(src), "r"(bytes), "r"(bar) : "memory");
}
__device__ __forceinline__ void tma_ld2(uint32_t dst, const CUtensorMap* m, uint32_t bar, int c0, int c1) {
    asm volatile("cp.async.bulk.tensor.2d.shared::cluster.global.mbarrier::complete_tx::bytes [%0],[%1,{%3,%4}],[%2];" ::"r"(dst), "l"(m), "r"(bar), "r"(c0), "r"(c1) : "memory");
}
__device__ __forceinline__ void tma_ld3(uint32_t dst, const CUtensorMap* m, uint32_t bar, int c0, int c1, int c2) {
    asm volatile("cp.async.bulk.tensor.3d.shared::cluster.global.mbarrier::complete_tx::bytes [%0],[%1,{%3,%4,%5}],[%2];" ::"r"(dst), "l"(m), "r"(bar), "r"(c0), "r"(c1), "r"(c2) : "memory");
}
__device__ __forceinline__ void tma_ld4(uint32_t dst, const CUtensorMap* m, uint32_t bar, int c0, int c1, int c2, int c3) {
    asm volatile("cp.async.bulk.tensor.4d.shared::cluster.global.mbarrier::complete_tx::bytes [%0],[%1,{%3,%4,%5,%6}],[%2];" ::"r"(dst), "l"(m), "r"(bar), "r"(c0), "r"(c1), "r"(c2), "r"(c3) : "memory");
}
__device__ __forceinline__ void bulk_st(void* dst, uint32_t src, uint32_t bytes) {
    asm volatile("cp.async.bulk.global.shared::cta.bulk_group [%0],[%1],%2;" ::"l"(dst), "r"(src), "r"(bytes) : "memory");
}
__device__ __forceinline__ void tma_ld5(uint32_t dst, const CUtensorMap* m, uint32_t bar, int c0, int c1, int c2, int c3, int c4) {
    asm volatile("cp.async.bulk.tensor.5d.shared::cluster.global.mbarrier::complete_tx::bytes [%0],[%1,{%3,%4,%5,%6,%7}],[%2];" ::"r"(dst), "l"(m), "r"(bar), "r"(c0), "r"(c1), "r"(c2), "r"(c3), "r"(c4) : "memory");
}
__device__ __forceinline__ void tma_st2(const CUtensorMap* m, uint32_t src, int c0, int c1) {
    asm volatile("cp.async.bulk.tensor.2d.global.shared::cta.bulk_group [%0,{%2,%3}],[%1];" ::"l"(m), "r"(src), "r"(c0), "r"(c1) : "memory");
}
__device__ __forceinline__ void tma_st4(const CUtensorMap* m, uint32_t src, int c0, int c1, int c2, int c3) {
    asm volatile("cp.async.bulk.tensor.4d.global.shared::cta.bulk_group [%0,{%2,%3,%4,%5}],[%1];" ::"l"(m), "r"(src), "r"(c0), "r"(c1), "r"(c2), "r"(c3) : "memory");
}
__device__ __forceinline__ void tma_st5(const CUtensorMap* m, uint32_t src, int c0, int c1, int c2, int c3, int c4) {
    asm volatile("cp.async.bulk.tensor.5d.global.shared::cta.bulk_group [%0,{%2,%3,%4,%5,%6}],[%1];" ::"l"(m), "r"(src), "r"(c0), "r"(c1), "r"(c2), "r"(c3), "r"(c4) : "memory");
}
__device__ __forceinline__ void bulk_commit() { asm volatile("cp.async.bulk.commit_group;" ::: "memory"); }
template <int N> __device__ __forceinline__ void bulk_wait() { asm volatile("cp.async.bulk.wait_group %0;" ::"n"(N) : "memory"); }
template <int N> __device__ __forceinline__ void bulk_wait_read() { asm volatile("cp.async.bulk.wait_group.read %0;" ::"n"(N) : "memory"); }
__device__ __forceinline__ void bar_sync(int id, int n) { asm volatile("bar.sync %0,%1;" ::"r"(id), "r"(n) : "memory"); }

__device__ __forceinline__ uint4 lds128(uint32_t a) {
    uint4 v; asm volatile("ld.shared.v4.u32 {%0,%1,%2,%3},[%4];" : "=r"(v.x), "=r"(v.y), "=r"(v.z), "=r"(v.w) : "r"(a)); return v;
}
__device__ __forceinline__ void sts128(uint32_t a, uint32_t x, uint32_t y, uint32_t z, uint32_t w) {
    asm volatile("st.shared.v4.u32 [%0],{%1,%2,%3,%4};" ::"r"(a), "r"(x), "r"(y), "r"(z), "r"(w) : "memory");
}
__device__ __forceinline__ void sts64(uint32_t a, uint32_t x, uint32_t y) { asm volatile("st.shared.v2.u32 [%0],{%1,%2};" ::"r"(a), "r"(x), "r"(y) : "memory"); }
__device__ __forceinline__ void sts128p(uint32_t a, uint32_t x, uint32_t y, uint32_t z, uint32_t w, bool p) {
    asm volatile("{.reg .pred p; setp.ne.u32 p,%5,0; @p st.shared.v4.u32 [%0],{%1,%2,%3,%4};}" ::"r"(a), "r"(x), "r"(y), "r"(z), "r"(w), "r"((uint32_t)p) : "memory");
}
__device__ __forceinline__ void sts32(uint32_t a, uint32_t x) { asm volatile("st.shared.u32 [%0],%1;" ::"r"(a), "r"(x) : "memory"); }
__device__ __forceinline__ uint32_t pk(float lo, float hi) { uint32_t r; asm("cvt.rn.bf16x2.f32 %0,%1,%2;" : "=r"(r) : "f"(hi), "f"(lo)); return r; }

__device__ __forceinline__ uint32_t pkv(float lo, float hi) { uint32_t r; asm volatile("cvt.rn.bf16x2.f32 %0,%1,%2;" : "=r"(r) : "f"(hi), "f"(lo)); return r; }

__device__ __forceinline__ void mma16z(float* d, uint32_t a0, uint32_t a1, uint32_t a2, uint32_t a3, uint32_t b0, uint32_t b1) {
    asm("mma.sync.aligned.m16n8k16.row.col.f32.bf16.bf16.f32 {%0,%1,%2,%3},{%4,%5,%6,%7},{%8,%9},{%10,%10,%10,%10};"
        : "=f"(d[0]), "=f"(d[1]), "=f"(d[2]), "=f"(d[3]) : "r"(a0), "r"(a1), "r"(a2), "r"(a3), "r"(b0), "r"(b1), "f"(0.f));
}
__device__ __forceinline__ void mma16(float* d, uint32_t a0, uint32_t a1, uint32_t a2, uint32_t a3, uint32_t b0, uint32_t b1) {
    asm("mma.sync.aligned.m16n8k16.row.col.f32.bf16.bf16.f32 {%0,%1,%2,%3},{%4,%5,%6,%7},{%8,%9},{%0,%1,%2,%3};"
        : "+f"(d[0]), "+f"(d[1]), "+f"(d[2]), "+f"(d[3]) : "r"(a0), "r"(a1), "r"(a2), "r"(a3), "r"(b0), "r"(b1));
}
__device__ __forceinline__ void mma8(float* d, uint32_t a0, uint32_t a1, uint32_t b0) {
    asm("mma.sync.aligned.m16n8k8.row.col.f32.bf16.bf16.f32 {%0,%1,%2,%3},{%4,%5},{%6},{%0,%1,%2,%3};"
        : "+f"(d[0]), "+f"(d[1]), "+f"(d[2]), "+f"(d[3]) : "r"(a0), "r"(a1), "r"(b0));
}
__device__ __forceinline__ void wg_fence() { asm volatile("wgmma.fence.sync.aligned;" ::: "memory"); }
__device__ __forceinline__ void wg_commit() { asm volatile("wgmma.commit_group.sync.aligned;" ::: "memory"); }
template <int N> __device__ __forceinline__ void wg_wait() { asm volatile("wgmma.wait_group.sync.aligned %0;" ::"n"(N) : "memory"); }
template <int N> __device__ __forceinline__ void pin(float (&d)[N]) {
#pragma unroll
    for (int i = 0; i < N; i++) asm volatile("" : "+f"(d[i])::"memory");
}
#define ACC8(o) "+f"(d[o]), "+f"(d[o + 1]), "+f"(d[o + 2]), "+f"(d[o + 3]), "+f"(d[o + 4]), "+f"(d[o + 5]), "+f"(d[o + 6]), "+f"(d[o + 7])
#define OUT8(o) "=f"(d[o]), "=f"(d[o + 1]), "=f"(d[o + 2]), "=f"(d[o + 3]), "=f"(d[o + 4]), "=f"(d[o + 5]), "=f"(d[o + 6]), "=f"(d[o + 7])
template <int ACC> __device__ __forceinline__ void wgmma48(float (&d)[24], uint32_t a0, uint32_t a1, uint32_t a2, uint32_t a3, uint64_t desc) {
    if (ACC)
        asm volatile("wgmma.mma_async.sync.aligned.m64n48k16.f32.bf16.bf16 "
                     "{%0,%1,%2,%3,%4,%5,%6,%7,%8,%9,%10,%11,%12,%13,%14,%15,%16,%17,%18,%19,%20,%21,%22,%23},{%24,%25,%26,%27},%28,%29,1,1,0;"
                     : ACC8(0), ACC8(8), ACC8(16) : "r"(a0), "r"(a1), "r"(a2), "r"(a3), "l"(desc), "n"(ACC & 1));
    else
        asm volatile("wgmma.mma_async.sync.aligned.m64n48k16.f32.bf16.bf16 "
                     "{%0,%1,%2,%3,%4,%5,%6,%7,%8,%9,%10,%11,%12,%13,%14,%15,%16,%17,%18,%19,%20,%21,%22,%23},{%24,%25,%26,%27},%28,0,1,1,0;"
                     : OUT8(0), OUT8(8), OUT8(16) : "r"(a0), "r"(a1), "r"(a2), "r"(a3), "l"(desc));
}
template <int ACC> __device__ __forceinline__ void wgmma_p2(float (&d)[32], const uint32_t* a, uint64_t desc) {
    if (ACC)
        asm volatile("wgmma.mma_async.sync.aligned.m64n64k16.f32.bf16.bf16 "
                     "{%0,%1,%2,%3,%4,%5,%6,%7,%8,%9,%10,%11,%12,%13,%14,%15,%16,%17,%18,%19,%20,%21,%22,%23,%24,%25,%26,%27,%28,%29,%30,%31},{%32,%33,%34,%35},%36,1,1,1,0;"
                     : ACC8(0), ACC8(8), ACC8(16), ACC8(24) : "r"(a[0]), "r"(a[1]), "r"(a[2]), "r"(a[3]), "l"(desc));
    else
        asm volatile("wgmma.mma_async.sync.aligned.m64n64k16.f32.bf16.bf16 "
                     "{%0,%1,%2,%3,%4,%5,%6,%7,%8,%9,%10,%11,%12,%13,%14,%15,%16,%17,%18,%19,%20,%21,%22,%23,%24,%25,%26,%27,%28,%29,%30,%31},{%32,%33,%34,%35},%36,0,1,1,0;"
                     : OUT8(0), OUT8(8), OUT8(16), OUT8(24) : "r"(a[0]), "r"(a[1]), "r"(a[2]), "r"(a[3]), "l"(desc));
}
template <int ACC> __device__ __forceinline__ void wgmma_p2(float (&d)[4], const uint32_t* a, uint64_t desc) {
    if (ACC)
        asm volatile("wgmma.mma_async.sync.aligned.m64n8k16.f32.bf16.bf16 {%0,%1,%2,%3},{%4,%5,%6,%7},%8,1,1,1,0;"
                     : "+f"(d[0]), "+f"(d[1]), "+f"(d[2]), "+f"(d[3]) : "r"(a[0]), "r"(a[1]), "r"(a[2]), "r"(a[3]), "l"(desc));
    else
        asm volatile("wgmma.mma_async.sync.aligned.m64n8k16.f32.bf16.bf16 {%0,%1,%2,%3},{%4,%5,%6,%7},%8,0,1,1,0;"
                     : "=f"(d[0]), "=f"(d[1]), "=f"(d[2]), "=f"(d[3]) : "r"(a[0]), "r"(a[1]), "r"(a[2]), "r"(a[3]), "l"(desc));
}
__device__ __forceinline__ uint64_t desc_tab(uint32_t a) { return (uint64_t)((a & 0x3FFFF) >> 4) | ((uint64_t)(768 >> 4) << 16) | ((uint64_t)(128 >> 4) << 32); }

__device__ __forceinline__ void staged(uint32_t bar, int lane) {
    fence_async_s();
    __syncwarp();
    if (lane == 0) mbar_arrive(bar);
}

__device__ __forceinline__ void wgen(uint32_t win, uint32_t tab, uint32_t out, int c, int qq, int lane, uint32_t consumed, uint32_t chain, uint32_t gate, uint32_t tag) {
    uint32_t A[28];
    int mi = lane >> 3, rr = lane & 7;
    int L = 12 * (mi & 1) + c;
#pragma unroll
    for (int s = 0; s < 7; s++) {
        int u = s < 6 ? s / 3 : mi >> 1;
        int tap = s < 6 ? 16 * (s % 3) + 8 * (mi >> 1) + rr : 48;
        int line = 3 * tap + (L >> 3);
        uint32_t ad = win + u * WPIECE + line * 128 + (((L ^ line) & 7) << 4);
        asm volatile("ldmatrix.sync.aligned.m8n8.x4.trans.shared.b16 {%0,%1,%2,%3},[%4];"
                     : "=r"(A[4 * s]), "=r"(A[4 * s + 1]), "=r"(A[4 * s + 2]), "=r"(A[4 * s + 3]) : "r"(ad));
    }
    float d0[24], d1[24];
    uint64_t ds = desc_tab(tab);
    wg_fence();
    wgmma48<0>(d0, A[0], A[1], A[2], A[3], ds);
    wgmma48<0>(d1, A[12], A[13], A[14], A[15], ds);
    wgmma48<1>(d0, A[4], A[5], A[6], A[7], ds + 96);
    wgmma48<1>(d1, A[16], A[17], A[18], A[19], ds + 96);
    wgmma48<1>(d0, A[8], A[9], A[10], A[11], ds + 192);
    wgmma48<1>(d1, A[20], A[21], A[22], A[23], ds + 192);
    wgmma48<1>(d0, A[24], A[25], A[26], A[27], ds + 336);
    wgmma48<1>(d1, A[24], A[25], A[26], A[27], ds + 288);
    wg_commit();
    if (lane == 0) { if (chain) mbar_arrive(chain); mbar_arrive(consumed); }
    mbar_wait(gate);
    wg_wait<0>();
    pin(d0); pin(d1);
    int g = lane >> 2, q = lane & 3;
    const uint32_t p = out + q * 512 + (8 * (c & 3) + (g ^ (2 * (q ^ qq)))) * 16;
#pragma unroll
    for (int nb = 0; nb < 6; nb++)
        if (nb < 5 || q < 2)
            sts128(p + nb * 2048, pk(d0[4 * nb], d0[4 * nb + 2]), pk(d0[4 * nb + 1], d0[4 * nb + 3]), pk(d1[4 * nb], d1[4 * nb + 2]),
                   tagged(pk(d1[4 * nb + 1], d1[4 * nb + 3]), g == 7, tag));
}

__device__ __forceinline__ void p1_unit(uint32_t blk, uint32_t out, uint32_t cst, int wg, int wq, int lane) {
    int g = lane >> 2, q = lane & 3;
    uint32_t T[20];
#pragma unroll
    for (int v = 0; v < 5; v++) { uint4 x = lds128(cst + C_P1A + (v * 32 + lane) * 16); T[4 * v] = x.x; T[4 * v + 1] = x.y; T[4 * v + 2] = x.z; T[4 * v + 3] = x.w; }
    uint32_t P[6][3][4];
    const uint32_t a0 = blk + g * 512 + (2 * q + (g & 1)) * 64 + ((wq ^ q) << 4), a1 = a0 ^ 64;
    const uint32_t sel0 = (g & 1) ? 0x1054 : 0x5410, sel1 = sel0 + 0x2222;
    uint32_t vv[2][3][2][4];
    auto ldv = [&](int nu) {
        const int ro = (nu == 0 ? 6 : (nu == 1 ? 14 : 0)) * 512;
#pragma unroll
        for (int t = 0; t < 3; t++)
#pragma unroll
            for (int e = 0; e < 2; e++) {
                uint4 x = lds128((e ? a1 : a0) + t * 11264 + ro);
                vv[nu & 1][t][e][0] = x.x; vv[nu & 1][t][e][1] = x.y; vv[nu & 1][t][e][2] = x.z; vv[nu & 1][t][e][3] = x.w;
            }
    };
    ldv(0);
#pragma unroll
    for (int nu = 0; nu < 3; nu++) {
        if (nu < 2) ldv(nu + 1);
        auto& v = vv[nu & 1];
#pragma unroll
        for (int ch = 0; ch < 4; ch++) {
            const uint32_t sel = (ch & 1) ? sel1 : sel0;
            uint32_t b[2][3];
#pragma unroll
            for (int hf = 0; hf < 2; hf++)
#pragma unroll
                for (int t = 0; t < 3; t++) b[hf][t] = __byte_perm(v[t][0][(ch >> 1) + 2 * hf], v[t][1][(ch >> 1) + 2 * hf], sel);
            float d1[4];
            mma16z(d1, T[12], T[13], T[14], T[15], b[0][0], b[1][0]);
#pragma unroll
            for (int hf = 0; hf < 2; hf++) {
                float d0[4];
                mma16z(d0, T[0], T[1], T[2], T[3], b[hf][1], b[hf][2]);
                mma8(d0, T[16], T[17], b[hf][0]);
                mma16(d1, T[4 + 4 * hf], T[5 + 4 * hf], T[6 + 4 * hf], T[7 + 4 * hf], b[hf][1], b[hf][2]);
                P[(ch >> 1) + 2 * hf][nu][ch & 1] = pk(d0[0], d0[1]);
                P[(ch >> 1) + 2 * hf][nu][2 + (ch & 1)] = pk(d0[2], d0[3]);
            }
            P[4 + (ch >> 1)][nu][ch & 1] = pk(d1[0], d1[1]);
            P[4 + (ch >> 1)][nu][2 + (ch & 1)] = pk(d1[2], d1[3]);
        }
#pragma unroll
        for (int pb = 0; pb < 6; pb++) asm volatile("" : "+r"(P[pb][nu][0]), "+r"(P[pb][nu][1]), "+r"(P[pb][nu][2]), "+r"(P[pb][nu][3]));
                if (SPLIT >> nu & 1) mbar_wait(cst + (O_BAR - O_C) + 8 * BC);
    }
    const uint64_t ds = desc_tab(cst + C_P1B);
    float dA[24], dB[24];
    auto issue = [&](int pb) {
        wg_fence();
        if (pb == 4) {
            wgmma48<0>(dA, P[pb][0][0], P[pb][0][1], P[pb][0][2], P[pb][0][3], ds);
            wgmma48<0>(dB, P[pb + 1][0][0], P[pb + 1][0][1], P[pb + 1][0][2], P[pb + 1][0][3], ds);
        } else {
            wgmma48<2>(dA, P[pb][0][0], P[pb][0][1], P[pb][0][2], P[pb][0][3], ds);
            wgmma48<2>(dB, P[pb + 1][0][0], P[pb + 1][0][1], P[pb + 1][0][2], P[pb + 1][0][3], ds);
        }
        wgmma48<1>(dA, P[pb][1][0], P[pb][1][1], P[pb][1][2], P[pb][1][3], ds + 96);
        wgmma48<1>(dB, P[pb + 1][1][0], P[pb + 1][1][1], P[pb + 1][1][2], P[pb + 1][1][3], ds + 96);
        wgmma48<1>(dA, P[pb][2][0], P[pb][2][1], P[pb][2][2], P[pb][2][3], ds + 192);
        wgmma48<1>(dB, P[pb + 1][2][0], P[pb + 1][2][1], P[pb + 1][2][2], P[pb + 1][2][3], ds + 192);
        wg_commit();
    };
    issue(4);
    bar_sync(1 + wg, 128);
    asm volatile("" : "+r"(g), "+r"(q));
    wg_wait<0>(); pin(dA); pin(dB);
    uint32_t o[12][2];
#pragma unroll
    for (int k = 0; k < 12; k++) { const int i = 4 * (k >> 1) + (k & 1); o[k][0] = pkv(dA[i], dA[i + 2]); o[k][1] = pkv(dB[i], dB[i + 2]); }
    issue(0);
    {
        const int sw = (g >> 1) & 1, r0 = 2 * ((g < 6 ? 8 + (g >> 1) : 1) * 11 + q) + sw;
        const uint32_t a0 = out + r0 * 128 + ((((4 * sw + wq) ^ r0) & 7) << 4) + 8 * (g & 1);
        const uint32_t m = wq == 3 && (g & 1) ? TAGM : 0, m0 = sw ? m : 0, m1 = m ^ m0;
#pragma unroll
        for (int k = 11; k >= 0; k--) {
            sts64((a0 ^ ((k & 2) * 72 + (k & 1) * 64)) + 1024 * (k >> 2), o[k][0], tagged(o[k][1], (k & 1) ? m1 : m0, TAGX));
            if (k == 8) __syncwarp();
        }
    }
    wg_wait<0>(); pin(dA); pin(dB);
#pragma unroll
    for (int k = 0; k < 12; k++) { const int i = 4 * (k >> 1) + (k & 1); o[k][0] = pkv(dA[i], dA[i + 2]); o[k][1] = pkv(dB[i], dB[i + 2]); }
    issue(2);
    mbar_wait(cst + (O_BAR - O_C) + 8 * BC);
    const int r0 = 2 * (g * 11 + q) + (g & 1);
    const uint32_t ao = out + r0 * 128 + ((((4 * (g & 1) + wq) ^ r0) & 7) << 4);
    const uint32_t m = wq == 3 ? TAGM : 0, m0 = (g & 1) ? m : 0, m1 = m ^ m0;
    wg_wait<0>(); pin(dA); pin(dB);
#pragma unroll
    for (int k = 0; k < 12; k++) {
        const int i = 4 * (k >> 1) + (k & 1);
        sts128p((ao ^ ((k & 2) * 72 + (k & 1) * 64)) + 1024 * (k >> 2), o[k][0], o[k][1], pk(dA[i], dA[i + 2]),
                tagged(pk(dB[i], dB[i + 2]), (k & 1) ? m1 : m0, TAGX), k < 8 || q < 3);
    }
}

template <int NB>
__device__ __forceinline__ void p2_step(const uint32_t (&Wf)[48], uint32_t in, uint32_t a0, uint32_t m, uint32_t ofree, uint32_t empty, int lane, int wg, int s) {
    float dp[4 * NB], dm[4 * NB];
    const uint64_t ds = (uint64_t)((in & 0x3FFFF) >> 4) | (1ull << 16) | ((uint64_t)(1024 >> 4) << 32) | (1ull << 62);
    if (wg > 0 || (wg == 0 && s)) bar_sync(4 + wg, 256);
    wg_fence();
    wgmma_p2<0>(dp, &Wf[0], ds);
    wgmma_p2<0>(dm, &Wf[24], ds + 4);
#pragma unroll
    for (int ks = 1; ks < 6; ks++) {
        wgmma_p2<1>(dp, &Wf[4 * ks], ds + (ks >> 1) * (8192 >> 4) + (ks & 1) * 2);
        wgmma_p2<1>(dm, &Wf[24 + 4 * ks], ds + (ks >> 1) * (8192 >> 4) + (ks & 1) * 2 + 4);
        if (ks == 3) wg_commit();
    }
    wg_commit();
    wg_wait<1>();
    if (wg >= 0 && (wg < 2 || s < 5)) asm volatile("bar.arrive %0,256;" ::"r"(wg == 2 ? 4 : 5 + wg) : "memory");
    mbar_wait(ofree);
    wg_wait<0>();
    pin(dp); pin(dm);
    if (lane == 0) mbar_arrive(empty);
#pragma unroll
    for (int nb = 0; nb < NB; nb++) {
        float pr = dp[4 * nb] - dp[4 * nb + 3], pi = dp[4 * nb + 1] + dp[4 * nb + 2];
        float mr = dm[4 * nb] - dm[4 * nb + 3], mi = dm[4 * nb + 1] + dm[4 * nb + 2];
        sts32(a0 + nb * 1024, tagged(pk(pr + mr, pi - mi), m, TAGZ));
        sts32((a0 ^ 144) + nb * 1024, tagged(pk(pi + mi, mr - pr), m, TAGZ));
    }
}

__device__ __forceinline__ bool p3_unit(uint32_t blk, uint32_t cst, int wg, int wq, int lane) {
    int g = lane >> 2, q = lane & 3;
    uint32_t T[12];
#pragma unroll
    for (int v = 0; v < 3; v++) { uint4 x = lds128(cst + C_P3 + (v * 32 + lane) * 16); T[4 * v] = x.x; T[4 * v + 1] = x.y; T[4 * v + 2] = x.z; T[4 * v + 3] = x.w; }
    uint32_t ad[3][2];
#pragma unroll
    for (int nu = 0; nu < 3; nu++)
#pragma unroll
        for (int ka = 0; ka < 2; ka++) {
            int r = 2 * (min(4 * nu + (g >> 1), 10) * 11 + (ka ? min(8 + q, 10) : q)) + (g & 1);
            ad[nu][ka] = blk + r * 128 + ((((2 * wq) ^ r) & 7) << 4);
        }
    uint32_t o[2][4][4], bad = 0;
#pragma unroll
    for (int h = 0; h < 2; h++) {
        uint32_t z[3][3][4];
#pragma unroll
        for (int nu = 0; nu < 3; nu++)
#pragma unroll
            for (int ka = 0; ka < 3; ka++) {
                uint4 x = lds128((ad[nu][ka >> 1] ^ (h << 4)) + (ka & 1) * 1024);
                z[nu][ka][0] = x.x; z[nu][ka][1] = x.y; z[nu][ka][2] = x.z; z[nu][ka][3] = x.w;
                if (h) bad |= x.w ^ TAGZ;
            }
#pragma unroll
        for (int j = 0; j < 2; j++) {
            float d2[2][2][4];
#pragma unroll
            for (int e = 0; e < 2; e++) {
                const int ch = 2 * j + e;
                uint32_t P[3][2];
#pragma unroll
                for (int nu = 0; nu < 3; nu++) {
                    float d[4];
                    mma16z(d, T[0], T[1], T[2], T[3], z[nu][0][ch], z[nu][1][ch]);
                    mma8(d, T[4], T[5], z[nu][2][ch]);
                    P[nu][0] = pk(d[0], d[1]); P[nu][1] = pk(d[2], d[3]);
                }
#pragma unroll
                for (int be = 0; be < 2; be++) {
                    mma16z(d2[e][be], P[0][0], P[0][1], P[1][0], P[1][1], T[8 + 2 * be], T[9 + 2 * be]);
                    mma8(d2[e][be], P[2][0], P[2][1], T[6 + be]);
                }
            }
#pragma unroll
            for (int be = 0; be < 2; be++)
#pragma unroll
                for (int k = 0; k < 4; k++) o[be][k][2 * h + j] = pk(d2[0][be][k], d2[1][be][k]);
        }
    }
    if (bar_any(1 + wg, 128, wq == 3 && (bad & TAGM))) return false;
    const int p = 4 * g + q;
    const uint32_t a = blk + p * 64 + ((wq ^ ((p >> 1) & 3)) << 4);
#pragma unroll
    for (int be = 0; be < 2; be++)
#pragma unroll
        for (int k = 0; k < 4; k++)
            sts128(a + (2 * be + (k & 1)) * 4096 + (k >> 1) * 2048, o[be][k][0], o[be][k][1], o[be][k][2], o[be][k][3]);
    return true;
}

template <int Z> __device__ __forceinline__ int s_row(int gr, int st, int cg, int ci, unsigned cm) {
    const int sf = (ci >> 2) & 1, y = 3 * (3 * gr + cg) + ((st ^ sf) << (Z ^ (cm >> 31))), pg = y >> 2;
    const int r = (pg << 14) | ((ci & 1) << 6) | ((ci & 2) << 8) | ((y & 1) << 10) | ((y & 2) << 11);
    return r | ((((Z ? st : sf) ^ ci ^ (ci >> 1) ^ y ^ (y >> 1) ^ (cm >> pg)) & 1) << 5);
}
__device__ __forceinline__ int w_row(int fw, int hg, int cg, int io, unsigned cm) {
    const int home = fw == 5 ? hg >> 1 : fw > 5;
    const int col = fw == 5 ? 15 + (hg & 1) : 3 * (fw > 5 ? fw - 6 : fw) + hg;
    const int z = 9 * col + 3 * cg + io, pg = NPS + (z >> 5);
    const int r = (pg << 12) | ((z & 1) << 4) | ((z & 6) << 6) | ((z & 24) << 7);
    return r | (((home ^ __popc(z & 15) ^ (cm >> pg)) & 1) << 3);
}
__device__ __forceinline__ int s_tile(int t) { return ((t & 3) << 7) | ((t & 4) << 9) | ((t & 8) << 10); }
__device__ __forceinline__ int xoff(int r) { return r < 3 ? O_B0 + r * BLK : (r == 3 ? O_B4 : O_B3); }
__device__ __forceinline__ int soff(int r) { return r == 2 ? O_B2 + 2048 : xoff(r); }
__device__ __forceinline__ int zoff(int r) { return r == 0 ? O_B2 + 2048 : (r == 1 ? O_B3 : (r == 2 ? O_B4 : (r == 3 ? O_Z3 : O_Z4))); }

struct Role1 {
    int sd, k, nu;
    __device__ __forceinline__ Role1(int cta) { sd = cta >= NH; k = cta - sd * NH; nu = k < NUH - 4 * NH ? 5 : 4; }
};
struct Role {
    int sd, k, fp, wfw, nu;
    __device__ __forceinline__ Role(int v) {
        const int rho = v & 255;
        wfw = v >> 8;
        sd = rho >= NH;
        const int kk = sd ? NCTA - 1 - rho : rho;
        k = NH - 1 - kk;
        nu = k < NUH - 4 * NH ? 5 : 4;
        fp = k >= 5 + sd ? 60 * sd + k - 5 : -1;
    }
};
__device__ __forceinline__ int stage_row(const Role& R, int s, int lane, unsigned cm, int z) {
    const int ci = R.fp > 0 ? (R.fp - 1) / 15 : 0, rw = 2 * (ci ? R.fp - 15 * ci - 1 : R.fp);
    return (z ? s_row<1>(s, lane & 1, lane >> 1, ci, cm) : s_row<0>(s, lane & 1, lane >> 1, ci, cm)) + rw;
}
__device__ __forceinline__ int stage_off(int s, int lane) { return (lane >> 1) * 8192 + (lane & 1) * (s < 6 ? 4096 : 512); }
template <int Z, class RT> __device__ __forceinline__ int unit_row(const RT& R, int r, int lane, unsigned cm) {
    const int u = r * NH + R.k, ts = u / 3;
    return s_row<Z>(ts >> 4, R.sd, u - 3 * ts, lane, cm) + s_tile(ts);
}
__device__ __forceinline__ int unit_off(int lane) { return lane ? 3840 * lane + 256 : 0; }

__global__ void __launch_bounds__(512, 1) fftconv_kernel(const __grid_constant__ Maps mp) {
    extern __shared__ __align__(1024) unsigned char smraw[];
    const uint32_t sm = s2u(smraw);
    const uint32_t bar = sm + O_BAR;
    const int tid = threadIdx.x, lane = tid & 31;
    const uint32_t tstart = clock();
    int far = 0;
    if (tid < 128) {
        const int c = blockIdx.x, vp = min(c & 31, NPAGE - 2);
        const int r0 = 94 + (c & 1) + ((c >> 1) << 7);
        const int r1 = ((vp + 1) << 14) + 94 + ((c >> 5) & 1) + ((c >> 6) << 7) + (vp < NPS - 1 ? 0 : ((0xA151 >> (5 * (vp - NPS + 1))) & 31) << 9);
        unsigned* a = reinterpret_cast<unsigned*>(mp.s) + ((tid & 64 ? r1 : r0) + (tid & 32)) * 32 + lane;
        const bool on = tid < 64 || (c & 31) < NPAGE - 1;
        if (on) *a = 0;
        bar_sync(10, 128);
        TR(5, 18);
        unsigned t = 0;
        if (on) asm volatile("{.reg .u32 v; .reg .pred p;\n atom.relaxed.gpu.global.exch.b32 v,[%1],1;\n setp.eq.u32 p,v,0;\n @p mov.u32 %0,%%clock;}" : "+r"(t) : "l"(a) : "memory");
        if (lane == 0) sts32(sm + O_PT + (tid >> 3), t);
        bar_sync(10, 128);
        const uint4 tt = lds128(sm + O_PT);
        far = (((int)(tt.x - tt.y) > 0) ^ __popc(r0 & 0x1640)) & 1;
        if (tid == 64 && on)
            red_add(mp.cnt + CV + (vp >> 2), 1u << (8 * (vp & 3) + 4 * ((far ^ ((int)(tt.z - tt.w) > 0) ^ __popc(r1 & 0x1640)) & 1)));
        __syncwarp();
        TR(5, 19);
    }
    const int warp = __shfl_sync(0xffffffffu, tid >> 5, 0);
    int cta;
    asm volatile("mov.u32 %0,%%ctaid.x;" : "=r"(cta));
    const int wip = cta % 12;
    const Role1 X(cta);
    auto init_bars = [&](int gi) {
        if (lane == 0) {
            const int cnt = gi < 5 || gi >= 10 ? 1 : (gi < 7 ? 12 : 4);
#pragma unroll
            for (int i = 0; i < 8; i++) mbar_init(bar + 64 * gi + 8 * i, cnt);
            fence_async_s();
        }
        __syncwarp();
    };

    auto load_x = [&](int r) {
        const int u = r * NH + X.k, ts = u / 3, cg = u - 3 * ts, tr = ts / 14, th = 7 * X.sd + tr, tw = ts - 14 * tr;
        const uint32_t b = bar + 8 * (BX + r);
        if (lane == 0) mbar_expect(b, BLK);
        __syncwarp();
        const int t = lane >> 1, top = lane & 1;
        int w0 = 16 * tw - 8 + 8 * t; if (w0 < 0) w0 += 224;
#pragma unroll 1
        for (int i = 0; i < 3; i++) {
            while ((int)(clock() - tstart) < (3 * r + i) * XD + XD0) {}
            if (t == i) tma_ld3(sm + xoff(r) + t * 11264 + (top ? 0 : 3072), top ? &mp.x6 : &mp.x16, b, 32 * cg, w0, top ? (th ? 16 * th - 6 : 218) : 16 * th);
            __syncwarp();
        }
    };
    auto load_w = [&](int j) {
        if (lane < 2) tma_ld3(sm + (j ? O_W1 : O_W0) + lane * WPIECE, &mp.w, bar + 8 * (BW + j), 0, 3 * (8 * (wip >> 1) + 2 * (wip & 1) + 4 * lane + j), 0);
        __syncwarp();
    };
    if (warp == 0) {
        unsigned t = 0;
        if (lane < 2) t = atomicAdd(mp.cnt + (lane ? CG + 2 * wip : CT) + far, 1u);
        bar_sync(12, 64);
        TR(5, 20);
        if (far) t = (lane ? 10 : NCTA - 1) - t;
        if (lane == 1) bulk_ld(sm + O_WT, mp.wtab + t * WT_BYTES, WT_BYTES, bar + 8 * BW);
        if (lane < 2) asm volatile("st.shared.u8 [%0],%1;" ::"r"(sm + O_ROLE + lane), "r"(t) : "memory");
        __syncwarp();
        TR(5, 21);
    } else if (warp < 4) {
    } else if (warp == 15) {
        unsigned e = 0;
        if (lane < 3) asm volatile("ld.relaxed.gpu.global.u32 %0,[%1];" : "=r"(e) : "l"(mp.cnt + 63 + 32 * lane) : "memory");
        init_bars(1);
        e = __reduce_add_sync(0xffffffffu, e);
        if (lane == 0) sts32(sm + O_EP, e & 1);
        __syncwarp();
    } else if (warp == 12) {
        init_bars(0);
        if (lane < 3) mbar_expect(bar + 8 * lane, lane == BC ? C_BYTES : 2 * 18816 + (lane == BW ? WT_BYTES : 0));
        __syncwarp();
        asm volatile("bar.arrive 12,64;" ::: "memory");
        while ((int)(clock() - tstart) < WD) {}
        TR(3, 18);
        load_w(0);
        TR(3, 19);
        if (FORCE) load_x(0);
    } else {
        if (PFW & 1) {
            const int t = tid - 224;
            if ((PFW & 4) && t >= 0 && t < 54) { int l = cta * 54 + t; if (l < 7056) pf_l2(mp.wraw + l * 128); }
            else if (t >= 64 && t < 70) { int l = cta * 5 + t - 64; if (t == 69) { if (cta < 68) pf_l2(mp.ctab + cta * 128); } else if (l < 594) pf_l2(mp.wtab + l * 128); }
            else if (t >= 96 && t < 105) asm volatile("prefetch.tensormap [%0];" ::"l"(&mp.w + (t - 96)) : "memory");
        }
        init_bars(warp < 12 ? warp + 1 : warp);
        if (warp < 7) init_bars(warp - 2);
    }
    __syncthreads();

    if (warp >= 12) {
        asm volatile("setmaxnreg.dec.sync.aligned.u32 32;");
        if (warp == 14) {
            unsigned v; int it = 0;
            do {
                asm volatile("ld.acquire.gpu.global.u32 %0,[%1];" : "=r"(v) : "l"(mp.cnt + CV + ((lane >> 2) & 7)) : "memory");
                v = (v >> (8 * (lane & 3))) & 255;
            } while (__any_sync(0xffffffffu, lane < NPAGE - 1 && (v & 15) + (v >> 4) < (lane < 4 ? 5u : 4u)) && ++it < (1 << 18));
            const unsigned cm = __ballot_sync(0xffffffffu, lane < NPAGE - 1 && (v >> 4) > (v & 15)) << 1;
            if (lane == 0) { sts32(sm + O_CM, cm | (lds32(sm + O_EP) << 31)); mbar_arrive(bar + 8 * BCM); }
            __syncwarp();
            TR(5, 22);
        }
        const Role R(__shfl_sync(0xffffffffu, lds16(sm + O_ROLE), 0));

        if (warp == 12) {
            TR(3, 20);
            if (lane == 0) bulk_ld(sm + O_C, mp.ctab, C_BYTES, bar + 8 * BC);
            load_w(1);
#pragma unroll 1
            for (int r = FORCE; r < X.nu; r++) {
                if (r >= 3) mbar_wait(bar + 8 * (r == 3 ? BWC + 1 : BDW));
                load_x(r);
                TR(3, 21 + r);
            }
            mbar_wait(bar + 8 * BCM);
            const unsigned cm = __shfl_sync(0xffffffffu, lds32(sm + O_CM), 0);
            auto need = [&](int i) { mbar_wait(bar + 8 * (BFL + i)); fence_async_g(); };
            auto gap = [&](uint32_t t0, int d) { while ((int)(clock() - t0) < d) {} };
            if (R.fp >= 0) {
                {
                    const int fw = R.fp / 11, fh = R.fp - 11 * fw, b = lane / 3, io = lane - 3 * b;
                    const int row = w_row(fw, fh >> 2, b ? b - 1 : 2, io, cm) + 2 * (fh & 3);
                    need(7);
                    mbar_wait(bar + 8 * (BDW + 1));
                    if (lane < 3) mbar_expect(bar + 8 * (BWF + lane), STG);
                    __syncwarp();
                    TR(3, 17);
                    const uint32_t t0 = clock();
#pragma unroll 1
                    for (int i = 0; i < 9; i++) {
                        if (i == 6) mbar_wait(bar + 8 * BD1);
                        gap(t0, i * LPW);
                        if (lane == i) tma_ld4(sm + O_IN + lane * 8192, &mp.wf, bar + 8 * (BWF + b), 0, row, 0, 0);
                        __syncwarp();
                    }
                    TR(3, 15);
                }
                int buf = 0;
#pragma unroll 1
                for (int s = 0; s < 7; s++) {
                    const int row = stage_row(R, s, lane, cm, 0);
                    const uint32_t dst = sm + O_IN + buf * STG + stage_off(s, lane);
                    need(s);
                    mbar_wait(bar + 8 * (s >= 3 ? BPE + s - 3 : BWE + s));
                    if (lane == 0) mbar_expect(bar + 8 * (BPF + s), s < 6 ? STG : 3072);
                    __syncwarp();
                    if (lane < 6) tma_ld5(dst, s < 6 ? &mp.p16 : &mp.p2, bar + 8 * (BPF + s), 0, row, 0, 0, 0);
                    __syncwarp();
                    buf = buf == 2 ? 0 : buf + 1;
                    TR(3, 3 + s);
                }
            }
#pragma unroll 1
            for (int r = 0; r < R.nu; r++) {
                const int row = unit_row<1>(R, r, lane, cm);
                if (r == 0) { mbar_wait(bar + 8 * (BD1 + X.nu - 2)); mbar_wait(bar + 8 * (BD1 + X.nu - 1)); }
                if (r >= 3 && R.fp >= 0) { mbar_wait(bar + 8 * ((r == 3 ? BPE : BD2) + 4)); mbar_wait(bar + 8 * ((r == 3 ? BPE : BD2) + 5)); }
                if (lane == 0) mbar_expect(bar + 8 * (BZ + r), SLAB);
                need(8 + (r * NH + R.k) / 48);
                const uint32_t t0 = clock();
#pragma unroll 1
                for (int i = 0; i < 4; i++) {
                    if (r < 3) gap(t0, i * 2 * LPZ);
                    if ((lane & 27) == i) tma_ld2(sm + zoff(r) + unit_off(lane), lane ? &mp.s30 : &mp.s32, bar + 8 * (BZ + r), 0, row);
                    __syncwarp();
                }
                TR(3, 10 + r);
            }
        } else if (warp == 13) {
            const unsigned* myc = mp.cnt + (lane == 7 ? CW + (R.fp >= 0 ? R.fp / 11 : 0) : (lane & 15));
            const unsigned tgt = lane < 6 ? 96 : (lane < 8 ? 12 : NFP);
            bool open = lane < 15;
            mbar_wait(bar + 8 * (BIS + 18));
            int it = 0;
            while (__any_sync(0xffffffffu, open) && ++it < (1 << 18)) {
                unsigned v;
                asm volatile("ld.acquire.gpu.global.u32 %0,[%1];" : "=r"(v) : "l"(myc) : "memory");
                if (open && v >= tgt) { mbar_arrive(bar + 8 * (BFL + lane)); open = false; TRL(5, lane); }
            }
            unsigned last = 0;
            if (lane == 0) last = atomicAdd(mp.cnt + CD, 1u) == NCTA - 1;
            if (__shfl_sync(0xffffffffu, last, 0)) {
                const unsigned e = lane == 31 ? lds32(sm + O_EP) ^ 1 : 0;
                mp.cnt[lane] = 0; mp.cnt[32 + lane] = e; mp.cnt[64 + lane] = e; mp.cnt[96 + lane] = e;
            }
        } else {
            const int me = warp & 1;
            uint32_t next = tstart + T0;
            auto pace = [&](int cost) {
                uint32_t now;
                do { now = clock(); } while ((int)(now - next) < 0);
                next = ((int)(now - next) > CREDIT ? now - CREDIT : next) + cost;
            };
            const int bal = X.nu == 5 ? 236 : 275;
            mbar_wait(bar + 8 * BCM);
            const unsigned cm = __shfl_sync(0xffffffffu, lds32(sm + O_CM), 0);
            {
                const int iq = 2 * wip + me, w = lane / 3, hg = lane - 3 * w;
                unsigned char* dst = mp.s + (size_t)w_row(R.wfw, hg, w, iq >> 3, cm) * 512 + ((iq & 3) << 14) + ((iq & 4) << 16);
                const uint32_t src = sm + (me ? O_W0 : O_B3) + w * 11264 + hg * 4096;
                fence_async_g();
                if (me) { mbar_wait(bar + 8 * (BIS + 17)); next = lds32(sm + O_NEXT); }
#pragma unroll 1
                for (int i = 0; i < 3; i++) {
                    mbar_wait(bar + 8 * (BRW + 3 * me + i));
                    if (i == 0) TR(4, me);
                    pace((RW * 11 / 4 * bal) >> 8);
                    if (w == i) bulk_st(dst, src, hg < 2 ? 4096 : 3072);
                    __syncwarp();
                }
                if (lane == 0) { sts32(sm + O_NEXT, next); mbar_arrive(bar + 8 * (BIS + 17 + me)); if (EARLY == 2 - me) red_add(mp.cnt + CW + R.wfw); }
                bulk_commit(); bulk_wait<0>();
                __syncwarp();
                if (lane == 0) { if (me && EARLY == 0) red_add(mp.cnt + CW + R.wfw); mbar_arrive(bar + 8 * (BDW + me)); }
                TR(6, me);
            }
            const int n2 = R.fp >= 0 ? X.nu + 7 : X.nu;
#pragma unroll 1
            for (int j = me; j < n2 + R.nu; j += 2) {
                int dn = 0, cn = 0;
                auto turn = [&](int rd) {
                    mbar_wait(bar + 8 * rd);
                    mbar_wait(bar + 8 * (j ? BIS + j - 1 : BIS + 18));
                    next = lds32(sm + O_NEXT);
                    if (EARLY == 2 && dn && lane == 0) red_add(mp.cnt + cn);
                };
                if (j < X.nu) {
                    const int row = unit_row<0>(X, j, lane, cm);
                    const uint32_t src = sm + soff(j) + unit_off(lane);
                    dn = BD1 + j; cn = CX + (j * NH + X.k) / 48;
                    turn(BR1 + j);
                    TR(4, 2 + j);
#pragma unroll 1
                    for (int i = 0; i < 4; i++) {
                        pace((R1 * 121 / 64 * bal) >> 8);
                        if ((lane & 27) == i) tma_st2(lane == 0 || (lane == 4 && !X.sd) ? &mp.s32 : &mp.s30, src, 0, row);
                        __syncwarp();
                    }
                } else if (j < n2) {
                    const int s = j - X.nu, l6 = lane & 7;
                    const int row = stage_row(R, s, l6, cm, lane < 8);
                    const uint32_t src = sm + O_OUT + (s & 1) * STG + stage_off(s, l6);
                    const int mine = lane < 6 || (R.fp == 15 && lane < 16 && (lane & 9) == 9) ? l6 >> 1 : -1;
                    dn = BD2 + s; cn = CY + s;
                    turn(BR2 + s);
                    TR(4, 7 + s);
#pragma unroll 1
                    for (int w = 0; w < 3; w++) {
                        pace(s < 6 ? 2 * R2 : R2 / 4);
                        if (mine == w) tma_st5(s < 6 ? &mp.p16 : &mp.p2, src, 0, row, 0, 0, 0);
                        __syncwarp();
                    }
                } else {
                    const int r = j - n2, u = r * NH + R.k, ts = u / 3, cg = u - 3 * ts, tr = ts / 14, th = 7 * R.sd + tr, tw = ts - 14 * tr;
                    turn(BR3 + r);
                    TR(4, 14 + r);
#pragma unroll 1
                    for (int c = 0; c < 2; c++) {
                        if (r < 3) pace(2 * R3);
                        if (lane == 0) tma_st4(&mp.y, sm + zoff(r) + c * 8192, 32 * cg, 0, 16 * th, 4 * tw + 2 * c);
                        __syncwarp();
                    }
                }
                if (lane == 0) { sts32(sm + O_NEXT, next); mbar_arrive(bar + 8 * (BIS + j)); if (EARLY == 1 && dn) red_add(mp.cnt + cn); }
                bulk_commit(); bulk_wait<0>();
                __syncwarp();
                if (dn && lane == 0) {
                    if (EARLY == 0) red_add(mp.cnt + cn);
                    mbar_arrive(bar + 8 * dn);
                    TR(6, dn - BDW);
                }
                __syncwarp();
            }
            TR(4, 19 + me);
        }
    } else {
        asm volatile("setmaxnreg.inc.sync.aligned.u32 160;");
        const int wg = warp >> 2, wq = warp & 3;
        const Role R(__shfl_sync(0xffffffffu, lds16(sm + O_ROLE), 0));
#pragma unroll 1
        for (int it = 0; it <= wg; it++) {
            const int j = it > 0, cg = j ? wg + it - 2 : wg;
            mbar_wait(bar + 8 * (j == 0 && wg ? BWL + wg - 1 : BW + j));
            TR(wg, 24 + 2 * it);
            wgen(sm + (j ? O_W1 : O_W0), sm + O_WT, sm + (j ? O_W0 : O_B3) + cg * 11264, 4 * cg + wq, (2 * wip + j) & 3, lane, bar + 8 * (BWC + j),
                 j == 0 && wg < 2 ? bar + 8 * (BWL + wg) : 0, bar + 8 * (j ? BWC : BW), ~lds32(sm + O_EP));
            staged(bar + 8 * (BRW + 3 * j + cg), lane);
            TR(wg, 25 + 2 * it);
        }
        mbar_wait(bar + 8 * BC);
#pragma unroll 1
        for (int r = wg; r < X.nu; r += 3) {
            mbar_wait(bar + 8 * (BX + r));
            TR(wg, 1 + 2 * (r / 3));
            p1_unit(sm + xoff(r), sm + soff(r), sm + O_C, wg, wq, lane);
            staged(bar + 8 * (BR1 + r), lane);
            TR(wg, 2 + 2 * (r / 3));
        }
        uint32_t phw = 0;
        if (R.fp >= 0) {
            uint32_t Wf[48];
            const int g = lane >> 2, q = lane & 3, ck = 2 * wq + (g >> 2);
            {
                const int b = wg == 2 ? 0 : wg + 1;
                const uint32_t p = sm + O_IN + b * STG + q * 1024 + wq * 128 + ((g ^ (2 * q) ^ (4 * ((R.fp % 11) & 1))) << 4);
                mbar_wait(bar + 8 * (BWF + b));
                TR(wg, 5);
#pragma unroll 1
                for (int it = 0; it < 4096; it++) {
                    const uint32_t tag = ~lds32(sm + O_EP), m = g == 7;
                    uint32_t bad = 0;
#pragma unroll
                    for (int i = 0; i < 12; i++) {
                        uint4 v = lds128((p ^ (i >= 6 ? 544 : 0)) + (i % 6) * 4096);
                        Wf[4 * i] = v.x; Wf[4 * i + 1] = v.y; Wf[4 * i + 2] = v.z; Wf[4 * i + 3] = v.w & ~m;
                        bad |= v.w ^ tag;
                    }
                    if (!bar_any(1 + wg, 128, bad & m)) break;
                    if (wq == 0) {
                        TRC(2);
                        fence_async_s();
                        if (lane == 0) mbar_expect(bar + 8 * (BRT + 1 + wg), STG);
                        __syncwarp();
                        const int l = laneid(), fp = Role(lds16(sm + O_ROLE)).fp, fw = fp / 11, fh = fp - 11 * fw;
                        if (l < 3) tma_ld4(sm + O_IN + b * STG + l * 8192, &mp.wf, bar + 8 * (BRT + 1 + wg), 0, w_row(fw, fh >> 2, wg, l, lds32(sm + O_CM)) + 2 * (fh & 3), 0, 0);
                        __syncwarp();
                    }
                    mbar_wait_ph(bar + 8 * (BRT + 1 + wg), phw); phw ^= 1;
                }
                staged(bar + 8 * (BWE + b), lane);
            }
            const uint32_t o0 = sm + O_OUT + wg * 8192 + (2 * q) * 128 + ((ck ^ (2 * q)) << 4) + (g & 3) * 4;
            const uint32_t m = wq == 3 && g == 7 ? TAGM : 0;
            uint32_t ph = 0;
            auto landed = [&](int s, uint32_t in) {
                const int t = tid & 127;
                const uint32_t tw = ((7 ^ (t & 7)) << 4) + 12;
                const uint32_t c0 = in + (s < 6 ? t : min(t >> 3, 2) * 64 + (t & 7)) * 128 + tw, c1 = s < 6 ? in + (128 + (t & 63)) * 128 + tw : c0;
                mbar_wait(bar + 8 * (BPF + s));
#pragma unroll 1
                for (int it = 0; it < 4096; it++) {
                    if (!bar_any(1 + wg, 128, ((lds32(c0) ^ TAGX) | (lds32(c1) ^ TAGX)) & TAGM)) break;
                    fence_async_s();
                    bar_sync(7, 384);
                    if (warp == 0) {
                        TRC(0);
                        if (lane == 0) mbar_expect(bar + 8 * BRT, s < 6 ? STG : 3072);
                        __syncwarp();
                        const int l = laneid();
                        if (l < 6) tma_ld5(in + stage_off(s, l), s < 6 ? &mp.p16 : &mp.p2, bar + 8 * BRT, 0, stage_row(Role(lds16(sm + O_ROLE)), s, l, lds32(sm + O_CM), 0), 0, 0, 0);
                        __syncwarp();
                    }
                    mbar_wait_ph(bar + 8 * BRT, ph); ph ^= 1;
                }
            };
            int buf = 0;
            mbar_wait(bar + 8 * BD1);
#pragma unroll 1
            for (int s = 0; s < 6; s++) {
                landed(s, sm + O_IN + buf * STG);
                p2_step<8>(Wf, sm + O_IN + buf * STG, o0 + (s & 1) * STG, m, bar + 8 * (s >= 2 ? BD2 + s - 2 : BD1 + 1), bar + 8 * (BPE + s), lane, PP ? wg : -1, s);
                buf = buf == 2 ? 0 : buf + 1;
                staged(bar + 8 * (BR2 + s), lane);
                TR(wg, 6 + s);
            }
            landed(6, sm + O_IN);
            p2_step<1>(Wf, sm + O_IN, o0, m, bar + 8 * (BD2 + 4), bar + 8 * (BPE + 6), lane, -1, 6);
            staged(bar + 8 * (BR2 + 6), lane);
            TR(wg, 12);
        }
#pragma unroll 1
        for (int r = wg; r < R.nu; r += 3) {
            mbar_wait(bar + 8 * (BZ + r));
            TR(wg, 13 + 2 * (r / 3));
#pragma unroll 1
            for (int it = 0; it < 4096; it++) {
                if (p3_unit(sm + zoff(r), sm + O_C, wg, wq, laneid())) break;
                if (wq == 0) {
                    TRC(1);
                    fence_async_s();
                    if (lane == 0) mbar_expect(bar + 8 * (BRT + 1 + wg), SLAB);
                    __syncwarp();
                    const int l = laneid();
                    if (l < 8) tma_ld2(sm + zoff(r) + unit_off(l), l ? &mp.s30 : &mp.s32, bar + 8 * (BRT + 1 + wg), 0, unit_row<1>(Role(lds16(sm + O_ROLE)), r, l, lds32(sm + O_CM)));
                    __syncwarp();
                }
                mbar_wait_ph(bar + 8 * (BRT + 1 + wg), phw); phw ^= 1;
            }
            staged(bar + 8 * (BR3 + r), lane);
            TR(wg, 14 + 2 * (r / 3));
        }
    }
}

typedef CUresult (*EncFn)(CUtensorMap*, CUtensorMapDataType, cuuint32_t, void*, const cuuint64_t*, const cuuint64_t*, const cuuint32_t*,
                          const cuuint32_t*, CUtensorMapInterleave, CUtensorMapSwizzle, CUtensorMapL2promotion, CUtensorMapFloatOOBfill);

void enc(EncFn f, CUtensorMap* m, void* p, int rank, const cuuint64_t* dims, const cuuint64_t* strides, const cuuint32_t* box,
         CUtensorMapSwizzle sw, CUtensorMapL2promotion pr = CU_TENSOR_MAP_L2_PROMOTION_NONE) {
    cuuint32_t es[5] = {1, 1, 1, 1, 1};
    f(m, CU_TENSOR_MAP_DATA_TYPE_BFLOAT16, rank, p, dims, strides, box, es, CU_TENSOR_MAP_INTERLEAVE_NONE, sw, pr, CU_TENSOR_MAP_FLOAT_OOB_FILL_NONE);
}

}

extern "C" void kernel_launch(void* const* d_in, const int* in_sizes, int n_in, void* d_out, int out_size) {
    void* fn = nullptr; cudaDriverEntryPointQueryResult qr;
    cudaGetDriverEntryPoint("cuTensorMapEncodeTiled", &fn, cudaEnableDefault, &qr);
    EncFn f = (EncFn)fn;
    void* pS; cudaGetSymbolAddress(&pS, g_S);
    pS = (void*)(((uintptr_t)pS + (1u << 21) - 1) & ~(uintptr_t)((1u << 21) - 1));
    Maps mp;
    cudaGetSymbolAddress((void**)&mp.ctab, g_ctab); cudaGetSymbolAddress((void**)&mp.wtab, g_wtab); cudaGetSymbolAddress((void**)&mp.cnt, g_cnt);
    mp.s = (unsigned char*)pS; mp.x = (const unsigned char*)d_in[0]; mp.wraw = (const unsigned char*)d_in[1];
    { cuuint64_t d[4] = {256, NPAGE << 12, 4, 2}, s[3] = {512, 1 << 14, 1 << 18}; cuuint32_t b[4] = {256, 2, 4, 2}; enc(f, &mp.wf, pS, 4, d, s, b, CU_TENSOR_MAP_SWIZZLE_NONE); }
    {
        cuuint64_t d[3] = {96, 224, 224}, s[2] = {192, 43008};
        cuuint32_t b6[3] = {32, 8, 6}, b16[3] = {32, 8, 16};
        enc(f, &mp.x6, d_in[0], 3, d, s, b6, CU_TENSOR_MAP_SWIZZLE_64B, CU_TENSOR_MAP_L2_PROMOTION_L2_128B);
        enc(f, &mp.x16, d_in[0], 3, d, s, b16, CU_TENSOR_MAP_SWIZZLE_64B, CU_TENSOR_MAP_L2_PROMOTION_L2_128B);
    }
    { cuuint64_t d[4] = {96, 4, 224, 56}, s[3] = {192, 43008, 768}; cuuint32_t b[4] = {32, 4, 16, 2}; enc(f, &mp.y, d_out, 4, d, s, b, CU_TENSOR_MAP_SWIZZLE_64B); }
    {
        cuuint64_t d[2] = {64, NPAGE << 14}, s[1] = {128};
        cuuint32_t b32[2] = {64, 32}, b30[2] = {64, 30};
        enc(f, &mp.s32, pS, 2, d, s, b32, CU_TENSOR_MAP_SWIZZLE_128B);
        enc(f, &mp.s30, pS, 2, d, s, b30, CU_TENSOR_MAP_SWIZZLE_128B);
    }
    {
        cuuint64_t d[5] = {64, NPAGE << 14, 4, 2, 2}, s[4] = {128, 1 << 14, 1 << 18, 1 << 20};
        cuuint32_t b16[5] = {64, 2, 4, 2, 2}, b2[5] = {64, 2, 2, 1, 1};
        enc(f, &mp.p16, pS, 5, d, s, b16, CU_TENSOR_MAP_SWIZZLE_128B);
        enc(f, &mp.p2, pS, 5, d, s, b2, CU_TENSOR_MAP_SWIZZLE_128B);
    }
    { cuuint64_t d[3] = {64, 144, 49}, s[2] = {128, 18432}; cuuint32_t b[3] = {64, 3, 49}; enc(f, &mp.w, d_in[1], 3, d, s, b, CU_TENSOR_MAP_SWIZZLE_128B); }
    cudaFuncSetAttribute(fftconv_kernel, cudaFuncAttributeMaxDynamicSharedMemorySize, SMEM);
    fftconv_kernel<<<NCTA, 512, SMEM>>>(mp);
}
```

```cpp
#include <cuda_runtime.h>
#include <cuda_bf16.h>
#include <cuda.h>
#include <stdint.h>

#define TUNABLES {260, 310, 250, 280, 500, 250, 30, 1, 0, 450, 1, 1, 500, 0, 600, 4}
constexpr int c_tune[16] = TUNABLES;
template <int I> struct TuneV { static constexpr int v = c_tune[I]; };
#define TV(i) TuneV<i>::v
#define RW TV(0)
#define R1 TV(1)
#define R2 TV(2)
#define R3 TV(3)
#define CREDIT TV(4)
#define LPW TV(5)
#define NAP TV(6)
#define EARLY TV(7)
#define T0 TV(8)
#define XD TV(9)
#define XD0 0
#define LATE2 TV(10)
#define PFW TV(11)
#define CREDIT2 TV(12)
#define FORCE TV(13)
#define WD TV(14)
#define WIN TV(15)
#define SPLIT 3

namespace {

constexpr int NCTA = 132, NH = 66;
constexpr int NUH = 294;
constexpr int NFP = 121;
constexpr int BLK = 33792;
constexpr int SLAB = 242 * 128;
constexpr int WPIECE = 19456;
constexpr int STG = 24576;
constexpr int NPS = 16, NPAGE = 21;
constexpr int O_B4 = 0, O_B0 = 87040, O_B2 = O_B0 + 2 * BLK, O_B3 = O_B0 + 3 * BLK;
constexpr int O_W1 = 0, O_W0 = 2 * WPIECE, O_WT = 4 * WPIECE;
constexpr int O_IN = 33792, O_OUT = O_IN + 3 * STG, O_Z3 = O_IN + STG, O_Z4 = 124928;
constexpr int O_C = 222208, O_BAR = 230912, SMEM = 232448;
constexpr int C_P1A = 0, C_P1B = 2560, C_P3 = 7168, C_BYTES = 8704, WT_BYTES = 6912;
constexpr int BC = 0, BW = 1, BX = 3, BZ = 8, BWF = 13, BPF = 16, BCM = 23, BDW = 24, BD1 = 26, BDP = 31, BD2 = 37, BIS = 39, BI2 = 51, BRT = 58;
constexpr int BPE = 64, BWC = 70;
constexpr int BR2 = 72, BRW = 78, BWL = 84, BR1 = 86, BR3 = 91, BWE = 96;
constexpr int O_NEXT = O_BAR + 1016, O_ROLE = O_BAR + 1000, O_PT = O_BAR + 976, O_CM = O_BAR + 1008, O_EP = O_BAR + 1012;
constexpr uint32_t TAGM = 0x00010001u, TAGX = 0x00000001u, TAGZ = 0x00010000u;

constexpr uint16_t LUT_A[11] = {0x3f95, 0x3f92, 0x3f8c, 0x3f83, 0x3f6f, 0x3f53, 0x3f33, 0x3f0f, 0x3ed1, 0x3e7e, 0x3daa};
constexpr uint16_t LUT_B[11] = {0x3fe9, 0x3fe4, 0x3fdb, 0x3fcd, 0x3fbb, 0x3fa5, 0x3f8c, 0x3f60, 0x3f23, 0x3ec7, 0x3e05};
constexpr uint16_t LUT_W[12] = {0x3abb, 0x3ab9, 0x3ab3, 0x3aaa, 0x3a9d, 0x3a8d, 0x3a75, 0x3a4a, 0x3a1b, 0x39d3, 0x3955, 0};
constexpr uint16_t basis(int setb, int f, int a, int sn) {
    if (f < 0 || f > 10 || a < 0 || a > 21) return 0;
    int k = ((2 * f + 1) * (2 * a - 21) - 22 * sn + 88 * 7) % 88;
    if (k > 44) k = 88 - k;
    int neg = 0;
    if (k > 22) { k = 44 - k; neg = 1; }
    return (uint16_t)((setb ? LUT_B[k >> 1] : LUT_A[k >> 1]) | (neg << 15));
}
constexpr uint16_t neg16(uint16_t v) { return v ? (uint16_t)(v ^ 0x8000) : v; }
constexpr uint16_t wcoef(int fw, int fl, int sn, int tap) {
    if (fl > 21) return 0;
    int fh = fl >> 1, kh = tap / 7, kw = tap - 7 * kh;
    int u = (2 * fh + 1) * kh;
    if (fl & 1) u = -u;
    int k = (u + (2 * fw + 1) * kw - 11 * sn + 44 * 4) % 44;
    if (k > 22) k = 44 - k;
    int neg = 0;
    if (k > 11) { k = 22 - k; neg = 1; }
    return (uint16_t)(LUT_W[k] | (neg << 15));
}
struct alignas(128) CTab { uint16_t v[C_BYTES / 2]; };
struct alignas(128) WTab { uint16_t v[WT_BYTES / 2]; };
constexpr CTab make_ctab() {
    CTab t{};
    for (int lane = 0; lane < 32; lane++) {
        int g = lane >> 2, q = lane & 3;
        for (int r = 0; r < 18; r++) {
            int quad = r >> 2, j = r & 3;
            int set = quad < 3 ? quad : (quad == 3 ? 1 + (j >> 1) : 0);
            int sn = (j ^ (set == 0 ? g : g >> 1)) & 1;
            int t8 = quad < 3 ? 1 + (j >> 1) : 0;
            int b = 8 * t8 + 2 * q - 2;
            int fw = set == 0 ? g : (((g & 1) == set - 1) ? 8 + (g >> 1) : -1);
            int o = (C_P1A + (quad * 32 + lane) * 16 + j * 4) / 2;
            t.v[o] = basis(0, fw, b, sn); t.v[o + 1] = basis(0, fw, b + 1, sn);
        }
        for (int r = 0; r < 12; r++) {
            int o = (C_P3 + ((r >> 2) * 32 + lane) * 16 + (r & 3) * 4) / 2;
            if (r < 6) {
                int a = 6 + g + 8 * (r & 1), fh = 4 * (r >> 1) + q;
                t.v[o] = basis(0, fh, a, 0); t.v[o + 1] = basis(0, fh, a, 1);
            } else {
                int be = r < 8 ? r - 6 : (r - 8) >> 1, nu = r < 8 ? 2 : (r & 1);
                int b = 6 + 8 * be + 4 * (g & 1) + (g >> 1);
                t.v[o] = basis(1, 4 * nu + q, b, 0); t.v[o + 1] = basis(1, 4 * nu + q, b, 1);
            }
        }
    }
    for (int kc = 0; kc < 6; kc++)
        for (int nb = 0; nb < 6; nb++)
            for (int n = 0; n < 8; n++)
                for (int k = 0; k < 8; k++) {
                    int nu = kc >> 1, ds = kc & 1, im = nb & 1, fh = 4 * (nb >> 1) + (n >> 1), mi = n & 1;
                    int a = nu == 0 ? 6 + k : (nu == 1 ? 14 + k : (k < 6 ? k : -1));
                    uint16_t v = basis(0, fh, a, ds ^ im);
                    if (ds != im && (im ? mi : !mi)) v = neg16(v);
                    t.v[C_P1B / 2 + ((kc * 6 + nb) * 8 + n) * 8 + k] = v;
                }
    return t;
}
constexpr WTab make_wtab(int fw) {
    WTab t{};
    for (int nb = 0; nb < 6; nb++)
        for (int n = 0; n < 8; n++) {
            for (int tap = 0; tap < 48; tap++) t.v[(((tap >> 3) * 6 + nb) * 8 + n) * 8 + (tap & 7)] = wcoef(fw, 4 * nb + (n >> 1), n & 1, tap);
            t.v[((7 * 6 + nb) * 8 + n) * 8] = wcoef(fw, 4 * nb + (n >> 1), n & 1, 48);
        }
    return t;
}
__device__ const CTab g_ctab = make_ctab();
__device__ const WTab g_wtab[11] = {make_wtab(0), make_wtab(1), make_wtab(2), make_wtab(3), make_wtab(4), make_wtab(5),
                                    make_wtab(6), make_wtab(7), make_wtab(8), make_wtab(9), make_wtab(10)};

__device__ __align__(1024) unsigned char g_S[(size_t)(NPAGE + 1) << 21];
constexpr int CV = 32, CD = 40, CT = 64, CG = 96, CX = 2, CY = 10, CW = 18;
__device__ __align__(512) unsigned g_cnt[32 * 64];

struct Maps {
    const unsigned char* ctab; const unsigned char* wtab; const unsigned char* x; unsigned* cnt; unsigned char* s;
    const unsigned char* wraw;
    alignas(64) CUtensorMap w, x6, x16, wf, s32, s30, p16, p2, y;
};

#define TR(role, i)
#define TRL(role, i)
#define TRC(i)

__device__ __forceinline__ uint32_t s2u(const void* p) { return (uint32_t)__cvta_generic_to_shared(p); }
__device__ __forceinline__ void mbar_init(uint32_t b, int c) { asm volatile("mbarrier.init.shared::cta.b64 [%0],%1;" ::"r"(b), "r"(c) : "memory"); }
__device__ __forceinline__ void mbar_expect(uint32_t b, uint32_t tx) { asm volatile("mbarrier.arrive.expect_tx.shared::cta.b64 _,[%0],%1;" ::"r"(b), "r"(tx) : "memory"); }
__device__ __forceinline__ void mbar_arrive(uint32_t b) { asm volatile("mbarrier.arrive.shared::cta.b64 _,[%0];" ::"r"(b) : "memory"); }
__device__ __forceinline__ bool mbar_try(uint32_t b, uint32_t ph) {
    uint32_t ok;
    asm volatile("{.reg .pred p; mbarrier.try_wait.parity.shared::cta.b64 p,[%1],%2; selp.u32 %0,1,0,p;}" : "=r"(ok) : "r"(b), "r"(ph) : "memory");
    return ok;
}
__device__ __forceinline__ void mbar_wait_ph(uint32_t b, uint32_t ph) {
    if (mbar_try(b, ph)) return;
#pragma unroll 1
    for (int it = 0; it < (1 << 16); it++)
        if (mbar_try(b, ph)) return;
}
__device__ __forceinline__ void mbar_wait(uint32_t b) { mbar_wait_ph(b, 0); }
__device__ __forceinline__ void region_end(uint32_t b) {
    int it = 0;
    while (!mbar_try(b, 0) && ++it < (1 << 16)) {}
}
__device__ __forceinline__ bool mbar_test(uint32_t b) {
    uint32_t ok;
    asm volatile("{.reg .pred p; mbarrier.test_wait.parity.shared::cta.b64 p,[%1],0; selp.u32 %0,1,0,p;}" : "=r"(ok) : "r"(b) : "memory");
    return ok;
}
__device__ __forceinline__ bool elect() {
    uint32_t r;
    asm volatile("{.reg .pred p; elect.sync _|p,0xffffffff; selp.u32 %0,1,0,p;}" : "=r"(r));
    return r;
}
__device__ __forceinline__ uint32_t until(uint32_t t, int nap) {
    uint32_t now = clock();
    while ((int)(now - t) < 0) { if (nap) __nanosleep(nap); now = clock(); }
    return now;
}
__device__ __forceinline__ int bcast(int v, int l) { return __shfl_sync(0xffffffffu, v, l); }
__device__ __forceinline__ void poll(const unsigned* c, unsigned tgt) {
    unsigned v; int it = 0;
    do { asm volatile("ld.acquire.gpu.global.u32 %0,[%1];" : "=r"(v) : "l"(c) : "memory"); } while (v < tgt && ++it < (1 << 16));
}
__device__ __forceinline__ bool bar_any(int id, int n, bool v) {
    uint32_t r;
    asm volatile("{.reg .pred p,q; setp.ne.u32 p,%3,0; bar.red.or.pred q,%1,%2,p; selp.u32 %0,1,0,q;}" : "=r"(r) : "r"(id), "r"(n), "r"((uint32_t)v) : "memory");
    return __any_sync(0xffffffffu, r);
}
__device__ __forceinline__ int laneid() { int l; asm volatile("mov.u32 %0,%%laneid;" : "=r"(l)); return l; }
__device__ __forceinline__ uint32_t lds32(uint32_t a) { uint32_t v; asm volatile("ld.shared.u32 %0,[%1];" : "=r"(v) : "r"(a) : "memory"); return v; }
__device__ __forceinline__ uint32_t lds16(uint32_t a) { uint32_t v; asm volatile("ld.shared.u16 %0,[%1];" : "=r"(v) : "r"(a) : "memory"); return v; }
__device__ __forceinline__ uint32_t tagged(uint32_t v, uint32_t m, uint32_t t) { return (v & ~m) | (t & m); }
__device__ __forceinline__ void red_add(unsigned* c, unsigned v = 1) { asm volatile("red.relaxed.gpu.global.add.u32 [%0],%1;" ::"l"(c), "r"(v) : "memory"); }
__device__ __forceinline__ void pf_l2(const void* p) { asm volatile("prefetch.global.L2 [%0];" ::"l"(p)); }
__device__ __forceinline__ void fence_async_s() { asm volatile("fence.proxy.async.shared::cta;" ::: "memory"); }
__device__ __forceinline__ void fence_async_g() { asm volatile("fence.proxy.async.global;" ::: "memory"); }
__device__ __forceinline__ void bulk_ld(uint32_t dst, const void* src, uint32_t bytes, uint32_t bar) {
    asm volatile("cp.async.bulk.shared::cluster.global.mbarrier::complete_tx::bytes [%0],[%1],%2,[%3];" ::"r"(dst), "l"(src), "r"(bytes), "r"(bar) : "memory");
}
__device__ __forceinline__ void tma_ld2(uint32_t dst, const CUtensorMap* m, uint32_t bar, int c0, int c1) {
    asm volatile("cp.async.bulk.tensor.2d.shared::cluster.global.mbarrier::complete_tx::bytes [%0],[%1,{%3,%4}],[%2];" ::"r"(dst), "l"(m), "r"(bar), "r"(c0), "r"(c1) : "memory");
}
__device__ __forceinline__ void tma_ld3(uint32_t dst, const CUtensorMap* m, uint32_t bar, int c0, int c1, int c2) {
    asm volatile("cp.async.bulk.tensor.3d.shared::cluster.global.mbarrier::complete_tx::bytes [%0],[%1,{%3,%4,%5}],[%2];" ::"r"(dst), "l"(m), "r"(bar), "r"(c0), "r"(c1), "r"(c2) : "memory");
}
__device__ __forceinline__ void tma_ld4(uint32_t dst, const CUtensorMap* m, uint32_t bar, int c0, int c1, int c2, int c3) {
    asm volatile("cp.async.bulk.tensor.4d.shared::cluster.global.mbarrier::complete_tx::bytes [%0],[%1,{%3,%4,%5,%6}],[%2];" ::"r"(dst), "l"(m), "r"(bar), "r"(c0), "r"(c1), "r"(c2), "r"(c3) : "memory");
}
__device__ __forceinline__ void bulk_st(void* dst, uint32_t src, uint32_t bytes) {
    asm volatile("cp.async.bulk.global.shared::cta.bulk_group [%0],[%1],%2;" ::"l"(dst), "r"(src), "r"(bytes) : "memory");
}
__device__ __forceinline__ void tma_ld5(uint32_t dst, const CUtensorMap* m, uint32_t bar, int c0, int c1, int c2, int c3, int c4) {
    asm volatile("cp.async.bulk.tensor.5d.shared::cluster.global.mbarrier::complete_tx::bytes [%0],[%1,{%3,%4,%5,%6,%7}],[%2];" ::"r"(dst), "l"(m), "r"(bar), "r"(c0), "r"(c1), "r"(c2), "r"(c3), "r"(c4) : "memory");
}
__device__ __forceinline__ void tma_st2(const CUtensorMap* m, uint32_t src, int c0, int c1) {
    asm volatile("cp.async.bulk.tensor.2d.global.shared::cta.bulk_group [%0,{%2,%3}],[%1];" ::"l"(m), "r"(src), "r"(c0), "r"(c1) : "memory");
}
__device__ __forceinline__ void tma_st4(const CUtensorMap* m, uint32_t src, int c0, int c1, int c2, int c3) {
    asm volatile("cp.async.bulk.tensor.4d.global.shared::cta.bulk_group [%0,{%2,%3,%4,%5}],[%1];" ::"l"(m), "r"(src), "r"(c0), "r"(c1), "r"(c2), "r"(c3) : "memory");
}
__device__ __forceinline__ void tma_st5(const CUtensorMap* m, uint32_t src, int c0, int c1, int c2, int c3, int c4) {
    asm volatile("cp.async.bulk.tensor.5d.global.shared::cta.bulk_group [%0,{%2,%3,%4,%5,%6}],[%1];" ::"l"(m), "r"(src), "r"(c0), "r"(c1), "r"(c2), "r"(c3), "r"(c4) : "memory");
}
__device__ __forceinline__ void bulk_commit() { asm volatile("cp.async.bulk.commit_group;" ::: "memory"); }
template <int N> __device__ __forceinline__ void bulk_wait() { asm volatile("cp.async.bulk.wait_group %0;" ::"n"(N) : "memory"); }
template <int N> __device__ __forceinline__ void bulk_wait_read() { asm volatile("cp.async.bulk.wait_group.read %0;" ::"n"(N) : "memory"); }
__device__ __forceinline__ void bar_sync(int id, int n) { asm volatile("bar.sync %0,%1;" ::"r"(id), "r"(n) : "memory"); }

__device__ __forceinline__ uint4 lds128(uint32_t a) {
    uint4 v; asm volatile("ld.shared.v4.u32 {%0,%1,%2,%3},[%4];" : "=r"(v.x), "=r"(v.y), "=r"(v.z), "=r"(v.w) : "r"(a)); return v;
}
__device__ __forceinline__ void sts128(uint32_t a, uint32_t x, uint32_t y, uint32_t z, uint32_t w) {
    asm volatile("st.shared.v4.u32 [%0],{%1,%2,%3,%4};" ::"r"(a), "r"(x), "r"(y), "r"(z), "r"(w) : "memory");
}
__device__ __forceinline__ void sts64(uint32_t a, uint32_t x, uint32_t y) { asm volatile("st.shared.v2.u32 [%0],{%1,%2};" ::"r"(a), "r"(x), "r"(y) : "memory"); }
__device__ __forceinline__ void sts128p(uint32_t a, uint32_t x, uint32_t y, uint32_t z, uint32_t w, bool p) {
    asm volatile("{.reg .pred p; setp.ne.u32 p,%5,0; @p st.shared.v4.u32 [%0],{%1,%2,%3,%4};}" ::"r"(a), "r"(x), "r"(y), "r"(z), "r"(w), "r"((uint32_t)p) : "memory");
}
__device__ __forceinline__ void sts32(uint32_t a, uint32_t x) { asm volatile("st.shared.u32 [%0],%1;" ::"r"(a), "r"(x) : "memory"); }
__device__ __forceinline__ uint32_t pk(float lo, float hi) { uint32_t r; asm("cvt.rn.bf16x2.f32 %0,%1,%2;" : "=r"(r) : "f"(hi), "f"(lo)); return r; }

__device__ __forceinline__ uint32_t pkv(float lo, float hi) { uint32_t r; asm volatile("cvt.rn.bf16x2.f32 %0,%1,%2;" : "=r"(r) : "f"(hi), "f"(lo)); return r; }

__device__ __forceinline__ void mma16z(float* d, uint32_t a0, uint32_t a1, uint32_t a2, uint32_t a3, uint32_t b0, uint32_t b1) {
    asm("mma.sync.aligned.m16n8k16.row.col.f32.bf16.bf16.f32 {%0,%1,%2,%3},{%4,%5,%6,%7},{%8,%9},{%10,%10,%10,%10};"
        : "=f"(d[0]), "=f"(d[1]), "=f"(d[2]), "=f"(d[3]) : "r"(a0), "r"(a1), "r"(a2), "r"(a3), "r"(b0), "r"(b1), "f"(0.f));
}
__device__ __forceinline__ void mma16(float* d, uint32_t a0, uint32_t a1, uint32_t a2, uint32_t a3, uint32_t b0, uint32_t b1) {
    asm("mma.sync.aligned.m16n8k16.row.col.f32.bf16.bf16.f32 {%0,%1,%2,%3},{%4,%5,%6,%7},{%8,%9},{%0,%1,%2,%3};"
        : "+f"(d[0]), "+f"(d[1]), "+f"(d[2]), "+f"(d[3]) : "r"(a0), "r"(a1), "r"(a2), "r"(a3), "r"(b0), "r"(b1));
}
__device__ __forceinline__ void mma8(float* d, uint32_t a0, uint32_t a1, uint32_t b0) {
    asm("mma.sync.aligned.m16n8k8.row.col.f32.bf16.bf16.f32 {%0,%1,%2,%3},{%4,%5},{%6},{%0,%1,%2,%3};"
        : "+f"(d[0]), "+f"(d[1]), "+f"(d[2]), "+f"(d[3]) : "r"(a0), "r"(a1), "r"(b0));
}
__device__ __forceinline__ void wg_fence() { asm volatile("wgmma.fence.sync.aligned;" ::: "memory"); }
__device__ __forceinline__ void wg_commit() { asm volatile("wgmma.commit_group.sync.aligned;" ::: "memory"); }
template <int N> __device__ __forceinline__ void wg_wait() { asm volatile("wgmma.wait_group.sync.aligned %0;" ::"n"(N) : "memory"); }
template <int N> __device__ __forceinline__ void pin(float (&d)[N]) {
#pragma unroll
    for (int i = 0; i < N; i++) asm volatile("" : "+f"(d[i])::"memory");
}
#define ACC8(o) "+f"(d[o]), "+f"(d[o + 1]), "+f"(d[o + 2]), "+f"(d[o + 3]), "+f"(d[o + 4]), "+f"(d[o + 5]), "+f"(d[o + 6]), "+f"(d[o + 7])
#define OUT8(o) "=f"(d[o]), "=f"(d[o + 1]), "=f"(d[o + 2]), "=f"(d[o + 3]), "=f"(d[o + 4]), "=f"(d[o + 5]), "=f"(d[o + 6]), "=f"(d[o + 7])
template <int ACC> __device__ __forceinline__ void wgmma48(float (&d)[24], uint32_t a0, uint32_t a1, uint32_t a2, uint32_t a3, uint64_t desc) {
    if (ACC)
        asm volatile("wgmma.mma_async.sync.aligned.m64n48k16.f32.bf16.bf16 "
                     "{%0,%1,%2,%3,%4,%5,%6,%7,%8,%9,%10,%11,%12,%13,%14,%15,%16,%17,%18,%19,%20,%21,%22,%23},{%24,%25,%26,%27},%28,%29,1,1,0;"
                     : ACC8(0), ACC8(8), ACC8(16) : "r"(a0), "r"(a1), "r"(a2), "r"(a3), "l"(desc), "n"(ACC & 1));
    else
        asm volatile("wgmma.mma_async.sync.aligned.m64n48k16.f32.bf16.bf16 "
                     "{%0,%1,%2,%3,%4,%5,%6,%7,%8,%9,%10,%11,%12,%13,%14,%15,%16,%17,%18,%19,%20,%21,%22,%23},{%24,%25,%26,%27},%28,0,1,1,0;"
                     : OUT8(0), OUT8(8), OUT8(16) : "r"(a0), "r"(a1), "r"(a2), "r"(a3), "l"(desc));
}
template <int ACC> __device__ __forceinline__ void wgmma_p2(float (&d)[32], const uint32_t* a, uint64_t desc) {
    if (ACC)
        asm volatile("wgmma.mma_async.sync.aligned.m64n64k16.f32.bf16.bf16 "
                     "{%0,%1,%2,%3,%4,%5,%6,%7,%8,%9,%10,%11,%12,%13,%14,%15,%16,%17,%18,%19,%20,%21,%22,%23,%24,%25,%26,%27,%28,%29,%30,%31},{%32,%33,%34,%35},%36,1,1,1,0;"
                     : ACC8(0), ACC8(8), ACC8(16), ACC8(24) : "r"(a[0]), "r"(a[1]), "r"(a[2]), "r"(a[3]), "l"(desc));
    else
        asm volatile("wgmma.mma_async.sync.aligned.m64n64k16.f32.bf16.bf16 "
                     "{%0,%1,%2,%3,%4,%5,%6,%7,%8,%9,%10,%11,%12,%13,%14,%15,%16,%17,%18,%19,%20,%21,%22,%23,%24,%25,%26,%27,%28,%29,%30,%31},{%32,%33,%34,%35},%36,0,1,1,0;"
                     : OUT8(0), OUT8(8), OUT8(16), OUT8(24) : "r"(a[0]), "r"(a[1]), "r"(a[2]), "r"(a[3]), "l"(desc));
}
template <int ACC> __device__ __forceinline__ void wgmma_p2(float (&d)[4], const uint32_t* a, uint64_t desc) {
    if (ACC)
        asm volatile("wgmma.mma_async.sync.aligned.m64n8k16.f32.bf16.bf16 {%0,%1,%2,%3},{%4,%5,%6,%7},%8,1,1,1,0;"
                     : "+f"(d[0]), "+f"(d[1]), "+f"(d[2]), "+f"(d[3]) : "r"(a[0]), "r"(a[1]), "r"(a[2]), "r"(a[3]), "l"(desc));
    else
        asm volatile("wgmma.mma_async.sync.aligned.m64n8k16.f32.bf16.bf16 {%0,%1,%2,%3},{%4,%5,%6,%7},%8,0,1,1,0;"
                     : "=f"(d[0]), "=f"(d[1]), "=f"(d[2]), "=f"(d[3]) : "r"(a[0]), "r"(a[1]), "r"(a[2]), "r"(a[3]), "l"(desc));
}
__device__ __forceinline__ uint64_t desc_tab(uint32_t a) { return (uint64_t)((a & 0x3FFFF) >> 4) | ((uint64_t)(768 >> 4) << 16) | ((uint64_t)(128 >> 4) << 32); }

__device__ __forceinline__ void staged(uint32_t bar, int lane) {
    fence_async_s();
    __syncwarp();
    if (lane == 0) mbar_arrive(bar);
}

__device__ __forceinline__ void wgen(uint32_t win, uint32_t tab, uint32_t out, int c, int qq, int lane, uint32_t consumed, uint32_t chain, uint32_t gate, uint32_t tag) {
    uint32_t A[28];
    int mi = lane >> 3, rr = lane & 7;
    int L = 12 * (mi & 1) + c;
#pragma unroll
    for (int s = 0; s < 7; s++) {
        int u = s < 6 ? s / 3 : mi >> 1;
        int tap = s < 6 ? 16 * (s % 3) + 8 * (mi >> 1) + rr : 48;
        int line = 3 * tap + (L >> 3);
        uint32_t ad = win + u * WPIECE + line * 128 + (((L ^ line) & 7) << 4);
        asm volatile("ldmatrix.sync.aligned.m8n8.x4.trans.shared.b16 {%0,%1,%2,%3},[%4];"
                     : "=r"(A[4 * s]), "=r"(A[4 * s + 1]), "=r"(A[4 * s + 2]), "=r"(A[4 * s + 3]) : "r"(ad));
    }
    float d0[24], d1[24];
    uint64_t ds = desc_tab(tab);
    wg_fence();
    wgmma48<0>(d0, A[0], A[1], A[2], A[3], ds);
    wgmma48<0>(d1, A[12], A[13], A[14], A[15], ds);
    wgmma48<1>(d0, A[4], A[5], A[6], A[7], ds + 96);
    wgmma48<1>(d1, A[16], A[17], A[18], A[19], ds + 96);
    wgmma48<1>(d0, A[8], A[9], A[10], A[11], ds + 192);
    wgmma48<1>(d1, A[20], A[21], A[22], A[23], ds + 192);
    wgmma48<1>(d0, A[24], A[25], A[26], A[27], ds + 336);
    wgmma48<1>(d1, A[24], A[25], A[26], A[27], ds + 288);
    wg_commit();
    if (lane == 0) { if (chain) mbar_arrive(chain); mbar_arrive(consumed); }
    mbar_wait(gate);
    wg_wait<0>();
    pin(d0); pin(d1);
    int g = lane >> 2, q = lane & 3;
    const uint32_t p = out + q * 512 + (8 * (c & 3) + (g ^ (2 * (q ^ qq)))) * 16;
#pragma unroll
    for (int nb = 0; nb < 6; nb++)
        if (nb < 5 || q < 2)
            sts128(p + nb * 2048, pk(d0[4 * nb], d0[4 * nb + 2]), pk(d0[4 * nb + 1], d0[4 * nb + 3]), pk(d1[4 * nb], d1[4 * nb + 2]),
                   tagged(pk(d1[4 * nb + 1], d1[4 * nb + 3]), g == 7, tag));
}

__device__ __forceinline__ void p1_unit(uint32_t blk, uint32_t out, uint32_t cst, int wg, int wq, int lane) {
    int g = lane >> 2, q = lane & 3;
    uint32_t T[20];
#pragma unroll
    for (int v = 0; v < 5; v++) { uint4 x = lds128(cst + C_P1A + (v * 32 + lane) * 16); T[4 * v] = x.x; T[4 * v + 1] = x.y; T[4 * v + 2] = x.z; T[4 * v + 3] = x.w; }
    uint32_t P[6][3][4];
    const uint32_t a0 = blk + g * 512 + (2 * q + (g & 1)) * 64 + ((wq ^ q) << 4), a1 = a0 ^ 64;
    const uint32_t sel0 = (g & 1) ? 0x1054 : 0x5410, sel1 = sel0 + 0x2222;
    uint32_t vv[2][3][2][4];
    auto ldv = [&](int nu) {
        const int ro = (nu == 0 ? 6 : (nu == 1 ? 14 : 0)) * 512;
#pragma unroll
        for (int t = 0; t < 3; t++)
#pragma unroll
            for (int e = 0; e < 2; e++) {
                uint4 x = lds128((e ? a1 : a0) + t * 11264 + ro);
                vv[nu & 1][t][e][0] = x.x; vv[nu & 1][t][e][1] = x.y; vv[nu & 1][t][e][2] = x.z; vv[nu & 1][t][e][3] = x.w;
            }
    };
    ldv(0);
#pragma unroll
    for (int nu = 0; nu < 3; nu++) {
        if (nu < 2) ldv(nu + 1);
        auto& v = vv[nu & 1];
#pragma unroll
        for (int ch = 0; ch < 4; ch++) {
            const uint32_t sel = (ch & 1) ? sel1 : sel0;
            uint32_t b[2][3];
#pragma unroll
            for (int hf = 0; hf < 2; hf++)
#pragma unroll
                for (int t = 0; t < 3; t++) b[hf][t] = __byte_perm(v[t][0][(ch >> 1) + 2 * hf], v[t][1][(ch >> 1) + 2 * hf], sel);
            float d1[4];
            mma16z(d1, T[12], T[13], T[14], T[15], b[0][0], b[1][0]);
#pragma unroll
            for (int hf = 0; hf < 2; hf++) {
                float d0[4];
                mma16z(d0, T[0], T[1], T[2], T[3], b[hf][1], b[hf][2]);
                mma8(d0, T[16], T[17], b[hf][0]);
                mma16(d1, T[4 + 4 * hf], T[5 + 4 * hf], T[6 + 4 * hf], T[7 + 4 * hf], b[hf][1], b[hf][2]);
                P[(ch >> 1) + 2 * hf][nu][ch & 1] = pk(d0[0], d0[1]);
                P[(ch >> 1) + 2 * hf][nu][2 + (ch & 1)] = pk(d0[2], d0[3]);
            }
            P[4 + (ch >> 1)][nu][ch & 1] = pk(d1[0], d1[1]);
            P[4 + (ch >> 1)][nu][2 + (ch & 1)] = pk(d1[2], d1[3]);
        }
#pragma unroll
        for (int pb = 0; pb < 6; pb++) asm volatile("" : "+r"(P[pb][nu][0]), "+r"(P[pb][nu][1]), "+r"(P[pb][nu][2]), "+r"(P[pb][nu][3]));
                if (SPLIT >> nu & 1) region_end(cst + (O_BAR - O_C) + 8 * BC);
    }
    const uint64_t ds = desc_tab(cst + C_P1B);
    float dA[24], dB[24];
    auto issue = [&](int pb) {
        wg_fence();
        if (pb == 4) {
            wgmma48<0>(dA, P[pb][0][0], P[pb][0][1], P[pb][0][2], P[pb][0][3], ds);
            wgmma48<0>(dB, P[pb + 1][0][0], P[pb + 1][0][1], P[pb + 1][0][2], P[pb + 1][0][3], ds);
        } else {
            wgmma48<2>(dA, P[pb][0][0], P[pb][0][1], P[pb][0][2], P[pb][0][3], ds);
            wgmma48<2>(dB, P[pb + 1][0][0], P[pb + 1][0][1], P[pb + 1][0][2], P[pb + 1][0][3], ds);
        }
        wgmma48<1>(dA, P[pb][1][0], P[pb][1][1], P[pb][1][2], P[pb][1][3], ds + 96);
        wgmma48<1>(dB, P[pb + 1][1][0], P[pb + 1][1][1], P[pb + 1][1][2], P[pb + 1][1][3], ds + 96);
        wgmma48<1>(dA, P[pb][2][0], P[pb][2][1], P[pb][2][2], P[pb][2][3], ds + 192);
        wgmma48<1>(dB, P[pb + 1][2][0], P[pb + 1][2][1], P[pb + 1][2][2], P[pb + 1][2][3], ds + 192);
        wg_commit();
    };
    issue(4);
    bar_sync(1 + wg, 128);
    asm volatile("" : "+r"(g), "+r"(q));
    wg_wait<0>(); pin(dA); pin(dB);
    uint32_t o[12][2];
#pragma unroll
    for (int k = 0; k < 12; k++) { const int i = 4 * (k >> 1) + (k & 1); o[k][0] = pkv(dA[i], dA[i + 2]); o[k][1] = pkv(dB[i], dB[i + 2]); }
    issue(0);
    {
        const int sw = (g >> 1) & 1, r0 = 2 * ((g < 6 ? 8 + (g >> 1) : 1) * 11 + q) + sw;
        const uint32_t a0 = out + r0 * 128 + ((((4 * sw + wq) ^ r0) & 7) << 4) + 8 * (g & 1);
        const uint32_t m = wq == 3 && (g & 1) ? TAGM : 0, m0 = sw ? m : 0, m1 = m ^ m0;
#pragma unroll
        for (int k = 11; k >= 0; k--) {
            sts64((a0 ^ ((k & 2) * 72 + (k & 1) * 64)) + 1024 * (k >> 2), o[k][0], tagged(o[k][1], (k & 1) ? m1 : m0, TAGX));
            if (k == 8) __syncwarp();
        }
    }
    wg_wait<0>(); pin(dA); pin(dB);
#pragma unroll
    for (int k = 0; k < 12; k++) { const int i = 4 * (k >> 1) + (k & 1); o[k][0] = pkv(dA[i], dA[i + 2]); o[k][1] = pkv(dB[i], dB[i + 2]); }
    issue(2);
    region_end(cst + (O_BAR - O_C) + 8 * BC);
    const int r0 = 2 * (g * 11 + q) + (g & 1);
    const uint32_t ao = out + r0 * 128 + ((((4 * (g & 1) + wq) ^ r0) & 7) << 4);
    const uint32_t m = wq == 3 ? TAGM : 0, m0 = (g & 1) ? m : 0, m1 = m ^ m0;
    wg_wait<0>(); pin(dA); pin(dB);
#pragma unroll
    for (int k = 0; k < 12; k++) {
        const int i = 4 * (k >> 1) + (k & 1);
        sts128p((ao ^ ((k & 2) * 72 + (k & 1) * 64)) + 1024 * (k >> 2), o[k][0], o[k][1], pk(dA[i], dA[i + 2]),
                tagged(pk(dB[i], dB[i + 2]), (k & 1) ? m1 : m0, TAGX), k < 8 || q < 3);
    }
}

template <int NB, class F>
__device__ __forceinline__ void p2_step(const uint32_t (&Wf)[48], uint32_t in, uint32_t a0, uint32_t m, uint32_t t, uint32_t bar, int lane, int wg, int s, F meanwhile) {
    float dp[4 * NB], dm[4 * NB];
    const uint32_t lo = ((in & 0x3FFFF) >> 4) | (1u << 16);
    auto desc = [&](int o) { return (uint64_t)(lo + o) | ((uint64_t)(1024 >> 4) << 32) | (1ull << 62); };
    if (NB > 1 && (wg || s)) bar_sync(4 + wg, 256);
    wg_fence();
    wgmma_p2<0>(dp, &Wf[0], desc(0));
    wgmma_p2<0>(dm, &Wf[24], desc(4));
#pragma unroll
    for (int ks = 1; ks < 6; ks++) {
        wgmma_p2<1>(dp, &Wf[4 * ks], desc((ks >> 1) * (8192 >> 4) + (ks & 1) * 2));
        wgmma_p2<1>(dm, &Wf[24 + 4 * ks], desc((ks >> 1) * (8192 >> 4) + (ks & 1) * 2 + 4));
    }
    wg_commit();
    if (NB > 1 && (wg < 2 || s < 5)) asm volatile("bar.arrive %0,256;" ::"r"(wg == 2 ? 4 : 5 + wg) : "memory");
    meanwhile();
    mbar_wait_ph(bar + 8 * (s < 2 ? BD1 + 1 : BDP + 2 * wg + (s & 1)), s >= 2 ? ((s >> 1) & 1) ^ 1 : 0);
    wg_wait<0>();
    pin(dp); pin(dm);
    if (NB > 1 && lane == 0) mbar_arrive(bar + 8 * (BPE + s));
    uint32_t v[2 * NB];
#pragma unroll
    for (int nb = 0; nb < NB; nb++) {
        float pr = dp[4 * nb] - dp[4 * nb + 3], pi = dp[4 * nb + 1] + dp[4 * nb + 2];
        float mr = dm[4 * nb] - dm[4 * nb + 3], mi = dm[4 * nb + 1] + dm[4 * nb + 2];
        v[2 * nb] = tagged(pk(pr + mr, pi - mi), m, t);
        v[2 * nb + 1] = tagged(pk(pi + mi, mr - pr), m, t);
        if (nb & 1)
            asm volatile("stmatrix.sync.aligned.m8n8.x4.trans.shared.b16 [%0],{%1,%2,%3,%4};" ::"r"(a0 + (nb - 1) * 1024), "r"(v[2 * nb - 2]), "r"(v[2 * nb - 1]),
                         "r"(v[2 * nb]), "r"(v[2 * nb + 1]) : "memory");
    }
    if (NB == 1) asm volatile("stmatrix.sync.aligned.m8n8.x2.trans.shared.b16 [%0],{%1,%2};" ::"r"(a0), "r"(v[0]), "r"(v[1]) : "memory");
}

__device__ __forceinline__ bool p3_unit(uint32_t blk, uint32_t cst, int wg, int wq, int lane) {
    int g = lane >> 2, q = lane & 3;
    uint32_t T[12];
#pragma unroll
    for (int v = 0; v < 3; v++) { uint4 x = lds128(cst + C_P3 + (v * 32 + lane) * 16); T[4 * v] = x.x; T[4 * v + 1] = x.y; T[4 * v + 2] = x.z; T[4 * v + 3] = x.w; }
    uint32_t ad[3][2];
#pragma unroll
    for (int nu = 0; nu < 3; nu++)
#pragma unroll
        for (int ka = 0; ka < 2; ka++) {
            int r = 2 * (min(4 * nu + (g >> 1), 10) * 11 + (ka ? min(8 + q, 10) : q)) + (g & 1);
            ad[nu][ka] = blk + r * 128 + ((((2 * wq) ^ r) & 7) << 4);
        }
    uint32_t o[2][4][4], bad = 0, P[8][3][2];
#pragma unroll
    for (int nu = 0; nu < 3; nu++) {
        uint32_t z[3][2][4];
#pragma unroll
        for (int ka = 0; ka < 3; ka++)
#pragma unroll
            for (int h = 0; h < 2; h++) {
                uint4 x = lds128((ad[nu][ka >> 1] ^ (h << 4)) + (ka & 1) * 1024);
                z[ka][h][0] = x.x; z[ka][h][1] = x.y; z[ka][h][2] = x.z; z[ka][h][3] = x.w;
                if (h) bad |= x.w ^ TAGZ;
            }
#pragma unroll
        for (int ch = 0; ch < 8; ch++) {
            const uint32_t sel = (ch & 1) ? 0x7632 : 0x5410;
            float d[4];
            mma16z(d, T[0], T[1], T[2], T[3], __byte_perm(z[0][0][ch >> 1], z[0][1][ch >> 1], sel), __byte_perm(z[1][0][ch >> 1], z[1][1][ch >> 1], sel));
            mma8(d, T[4], T[5], __byte_perm(z[2][0][ch >> 1], z[2][1][ch >> 1], sel));
            P[ch][nu][0] = pk(d[0], d[1]); P[ch][nu][1] = pk(d[2], d[3]);
        }
    }
    if (bar_any(1 + wg, 128, wq == 3 && (bad & TAGM))) return false;
#pragma unroll
    for (int j = 0; j < 4; j++) {
        float d2[2][2][4];
#pragma unroll
        for (int e = 0; e < 2; e++)
#pragma unroll
            for (int be = 0; be < 2; be++) {
                const int ch = 2 * j + e;
                mma16z(d2[e][be], P[ch][0][0], P[ch][0][1], P[ch][1][0], P[ch][1][1], T[8 + 2 * be], T[9 + 2 * be]);
                mma8(d2[e][be], P[ch][2][0], P[ch][2][1], T[6 + be]);
            }
#pragma unroll
        for (int be = 0; be < 2; be++)
#pragma unroll
            for (int k = 0; k < 4; k++) o[be][k][j] = pk(d2[0][be][k], d2[1][be][k]);
    }
    const int p = 4 * g + q;
    const uint32_t a = blk + p * 64 + ((wq ^ ((p >> 1) & 3)) << 4);
#pragma unroll
    for (int be = 0; be < 2; be++)
#pragma unroll
        for (int k = 0; k < 4; k++)
            sts128(a + (2 * be + (k & 1)) * 4096 + (k >> 1) * 2048, o[be][k][0], o[be][k][1], o[be][k][2], o[be][k][3]);
    return true;
}

template <int Z> __device__ __forceinline__ int s_row(int gr, int st, int cg, int ci, unsigned cm) {
    const int sf = (ci >> 2) & 1, y = 3 * (3 * gr + cg) + ((st ^ sf) << (Z ^ (cm >> 31))), pg = y >> 2;
    const int r = (pg << 14) | ((ci & 1) << 6) | ((ci & 2) << 8) | ((y & 1) << 10) | ((y & 2) << 11);
    return r | ((((Z ? st : sf) ^ ci ^ (ci >> 1) ^ y ^ (y >> 1) ^ (cm >> pg)) & 1) << 5);
}
__device__ __forceinline__ int w_row(int fw, int hg, int cg, int io, unsigned cm) {
    const int home = fw == 5 ? hg >> 1 : fw > 5;
    const int col = fw == 5 ? 15 + (hg & 1) : 3 * (fw > 5 ? fw - 6 : fw) + hg;
    const int z = 9 * col + 3 * cg + io, pg = NPS + (z >> 5);
    const int r = (pg << 12) | ((z & 1) << 4) | ((z & 6) << 6) | ((z & 24) << 7);
    return r | (((home ^ __popc(z & 15) ^ (cm >> pg)) & 1) << 3);
}
__device__ __forceinline__ int s_tile(int t) { return ((t & 3) << 7) | ((t & 4) << 9) | ((t & 8) << 10); }
__device__ __forceinline__ int xoff(int r) { return r < 3 ? O_B0 + r * BLK : (r == 3 ? O_B4 : O_B3); }
__device__ __forceinline__ int soff(int r) { return r == 2 ? O_B2 + 2048 : xoff(r); }
__device__ __forceinline__ int zoff(int r) { return r == 0 ? O_B2 + 2048 : (r == 1 ? O_B3 : (r == 2 ? O_B4 : (r == 3 ? O_Z3 : O_Z4))); }

struct Role1 {
    int sd, k, nu;
    __device__ __forceinline__ Role1(int cta) { sd = cta >= NH; k = cta - sd * NH; nu = k < NUH - 4 * NH ? 5 : 4; }
};
struct Role {
    int sd, k, fp, wfw, nu;
    __device__ __forceinline__ Role(int v) {
        const int rho = v & 255;
        wfw = v >> 8;
        sd = rho >= NH;
        const int kk = sd ? NCTA - 1 - rho : rho;
        k = NH - 1 - kk;
        nu = k < NUH - 4 * NH ? 5 : 4;
        fp = k >= 5 + sd ? 60 * sd + k - 5 : -1;
    }
};
__device__ __forceinline__ int stage_row(const Role& R, int s, int lane, unsigned cm, int z) {
    const int ci = R.fp > 0 ? (R.fp - 1) / 15 : 0, rw = 2 * (ci ? R.fp - 15 * ci - 1 : R.fp);
    return (z ? s_row<1>(s, lane & 1, lane >> 1, ci, cm) : s_row<0>(s, lane & 1, lane >> 1, ci, cm)) + rw;
}
__device__ __forceinline__ int stage_off(int s, int lane) { return (lane >> 1) * 8192 + (lane & 1) * (s < 6 ? 4096 : 512); }
template <int Z, class RT> __device__ __forceinline__ int unit_row(const RT& R, int r, int lane, unsigned cm) {
    const int u = r * NH + R.k, ts = u / 3;
    return s_row<Z>(ts >> 4, R.sd, u - 3 * ts, lane, cm) + s_tile(ts);
}
__device__ __forceinline__ int unit_off(int lane) { return lane ? 3840 * lane + 256 : 0; }

__global__ void __launch_bounds__(512, 1) fftconv_kernel(const __grid_constant__ Maps mp) {
    extern __shared__ __align__(1024) unsigned char smraw[];
    const uint32_t sm = s2u(smraw);
    const uint32_t bar = sm + O_BAR;
    const int tid = threadIdx.x, lane = tid & 31;
    const uint32_t tstart = clock();
    int far = 0;
    if (tid < 128) {
        const int c = blockIdx.x, vp = min(c & 31, NPAGE - 2);
        const int r0 = 94 + (c & 1) + ((c >> 1) << 7);
        const int r1 = ((vp + 1) << 14) + 94 + ((c >> 5) & 1) + ((c >> 6) << 7) + (vp < NPS - 1 ? 0 : ((0xA151 >> (5 * (vp - NPS + 1))) & 31) << 9);
        unsigned* a = reinterpret_cast<unsigned*>(mp.s) + ((tid & 64 ? r1 : r0) + (tid & 32)) * 32 + lane;
        const bool on = tid < 64 || (c & 31) < NPAGE - 1;
        if (on) *a = 0;
        bar_sync(10, 128);
        TR(5, 18);
        unsigned t = 0;
        if (on) asm volatile("{.reg .u32 v; .reg .pred p;\n atom.relaxed.gpu.global.exch.b32 v,[%1],1;\n setp.eq.u32 p,v,0;\n @p mov.u32 %0,%%clock;}" : "+r"(t) : "l"(a) : "memory");
        if (lane == 0) sts32(sm + O_PT + (tid >> 3), t);
        bar_sync(10, 128);
        const uint4 tt = lds128(sm + O_PT);
        far = (((int)(tt.x - tt.y) > 0) ^ __popc(r0 & 0x1640)) & 1;
        if (tid == 64 && on)
            red_add(mp.cnt + CV + (vp >> 2), 1u << (8 * (vp & 3) + 4 * ((far ^ ((int)(tt.z - tt.w) > 0) ^ __popc(r1 & 0x1640)) & 1)));
        __syncwarp();
        TR(5, 19);
    }
    const int warp = __shfl_sync(0xffffffffu, tid >> 5, 0);
    int cta;
    asm volatile("mov.u32 %0,%%ctaid.x;" : "=r"(cta));
    const int wip = cta % 12;
    const Role1 X(cta);
    auto init_bars = [&](int gi) {
        if (lane == 0) {
            const int cnt = gi < 8 ? 1 : (gi == 8 ? 12 : 4);
#pragma unroll
            for (int i = 0; i < 8; i++) mbar_init(bar + 64 * gi + 8 * i, cnt);
            fence_async_s();
        }
        __syncwarp();
    };

    auto load_x = [&](int r) {
        const int u = r * NH + X.k, ts = u / 3, cg = u - 3 * ts, tr = ts / 14, th = 7 * X.sd + tr, tw = ts - 14 * tr;
        const uint32_t b = bar + 8 * (BX + r);
        if (lane == 0) mbar_expect(b, BLK);
        __syncwarp();
        const int t = lane >> 1, top = lane & 1;
        int w0 = 16 * tw - 8 + 8 * t; if (w0 < 0) w0 += 224;
#pragma unroll 1
        for (int i = 0; i < 3; i++) {
            until(tstart + (3 * r + i) * XD + XD0, NAP);
            if (t == i) tma_ld3(sm + xoff(r) + t * 11264 + (top ? 0 : 3072), top ? &mp.x6 : &mp.x16, b, 32 * cg, w0, top ? (th ? 16 * th - 6 : 218) : 16 * th);
            __syncwarp();
        }
    };
    auto load_w = [&](int j) {
        if (lane < 2) tma_ld3(sm + (j ? O_W1 : O_W0) + lane * WPIECE, &mp.w, bar + 8 * (BW + j), 0, 3 * (8 * (wip >> 1) + 2 * (wip & 1) + 4 * lane + j), 0);
        __syncwarp();
    };
    if (warp == 0) {
        unsigned t = 0;
        if (lane < 2) t = atomicAdd(mp.cnt + (lane ? CG + 2 * wip : CT) + far, 1u);
        bar_sync(12, 64);
        TR(5, 20);
        if (far) t = (lane ? 10 : NCTA - 1) - t;
        if (lane == 1) bulk_ld(sm + O_WT, mp.wtab + t * WT_BYTES, WT_BYTES, bar + 8 * BW);
        if (lane < 2) asm volatile("st.shared.u8 [%0],%1;" ::"r"(sm + O_ROLE + lane), "r"(t) : "memory");
        __syncwarp();
        TR(5, 21);
    } else if (warp < 4) {
    } else if (warp == 15) {
        unsigned e = 0;
        if (lane < 3) asm volatile("ld.relaxed.gpu.global.u32 %0,[%1];" : "=r"(e) : "l"(mp.cnt + 63 + 32 * lane) : "memory");
        init_bars(1);
        e = __reduce_add_sync(0xffffffffu, e);
        if (lane == 0) sts32(sm + O_EP, e & 1);
        __syncwarp();
    } else if (warp == 12) {
        init_bars(0);
        if (lane < 3) mbar_expect(bar + 8 * lane, lane == BC ? C_BYTES : 2 * 18816 + (lane == BW ? WT_BYTES : 0));
        __syncwarp();
        asm volatile("bar.arrive 12,64;" ::: "memory");
        while ((int)(clock() - tstart) < WD) {}
        TR(3, 18);
        load_w(0);
        TR(3, 19);
        if (FORCE) load_x(0);
    } else {
        if (PFW & 1) {
            const int t = tid - 224;
            if ((PFW & 4) && t >= 0 && t < 54) { int l = cta * 54 + t; if (l < 7056) pf_l2(mp.wraw + l * 128); }
            else if (t >= 64 && t < 70) { int l = cta * 5 + t - 64; if (t == 69) { if (cta < 68) pf_l2(mp.ctab + cta * 128); } else if (l < 594) pf_l2(mp.wtab + l * 128); }
            else if (t >= 96 && t < 105) asm volatile("prefetch.tensormap [%0];" ::"l"(&mp.w + (t - 96)) : "memory");
        }
        init_bars(warp < 12 ? warp + 1 : warp - 10);
        if (warp == 4) init_bars(2);
    }
    __syncthreads();

    if (warp >= 12) {
        asm volatile("setmaxnreg.dec.sync.aligned.u32 32;");
        if (warp == 14) {
            unsigned v; int it = 0;
            do {
                asm volatile("ld.acquire.gpu.global.u32 %0,[%1];" : "=r"(v) : "l"(mp.cnt + CV + ((lane >> 2) & 7)) : "memory");
                v = (v >> (8 * (lane & 3))) & 255;
            } while (__any_sync(0xffffffffu, lane < NPAGE - 1 && (v & 15) + (v >> 4) < (lane < 4 ? 5u : 4u)) && ++it < (1 << 18));
            const unsigned cm = __ballot_sync(0xffffffffu, lane < NPAGE - 1 && (v >> 4) > (v & 15)) << 1;
            if (lane == 0) { sts32(sm + O_CM, cm | (lds32(sm + O_EP) << 31)); mbar_arrive(bar + 8 * BCM); }
            __syncwarp();
            TR(5, 22);
        }
        const Role R(__shfl_sync(0xffffffffu, lds16(sm + O_ROLE), 0));

        if (warp == 12) {
            TR(3, 20);
            if (lane == 0) bulk_ld(sm + O_C, mp.ctab, C_BYTES, bar + 8 * BC);
            load_w(1);
#pragma unroll 1
            for (int r = FORCE; r < X.nu; r++) {
                if (r >= 3) mbar_wait(bar + 8 * (r == 3 ? BWC + 1 : BDW));
                load_x(r);
                TR(3, 21 + r);
            }
            if (R.fp >= 0) {
                mbar_wait(bar + 8 * BCM);
                const unsigned cm = lds32(sm + O_CM);
                if (lane < 10) mbar_expect(bar + 8 * (BWF + lane), lane < 9 ? STG : 3072);
                const int fw = R.fp / 11;
                {
                    const int fh = R.fp - 11 * fw, b = lane / 3, io = lane - 3 * b;
                    const int row = w_row(fw, fh >> 2, b ? b - 1 : 2, io, cm) + 2 * (fh & 3);
                    mbar_wait(bar + 8 * (BDW + 1));
                    poll(mp.cnt + 64 * (CW + fw), 12);
                    TR(3, 17);
                    const uint32_t t0 = clock();
#pragma unroll 1
                    for (int i = 0; i < 9; i++) {
                        if (i == 6) mbar_wait(bar + 8 * BD1);
                        until(t0 + i * LPW, NAP);
                        if (lane == i) tma_ld4(sm + O_IN + lane * 8192, &mp.wf, bar + 8 * (BWF + b), 0, row, 0, 0);
                        __syncwarp();
                    }
                    TR(3, 15);
                }
                const int v0 = stage_row(R, lane >> 3, lane & 7, cm, 0), v1 = stage_row(R, 4 + (lane >> 3), lane & 7, cm, 0);
                uint32_t dst = sm + O_IN, seen = 0;
#pragma unroll 1
                for (int s = 0; s < 7; s++) {
                    int row[6];
#pragma unroll
                    for (int i = 0; i < 6; i++) row[i] = bcast(s < 4 ? v0 : v1, 8 * s + i);
                    const CUtensorMap* m = s < 6 ? &mp.p16 : &mp.p2;
                    const uint32_t hs = s < 6 ? 4096 : 512;
                    for (int it = 0; !(seen >> s & 1) && it < (1 << 16); it++) {
                        unsigned v = 0;
                        if (lane == s || (s >= WIN && lane > s && lane < 7)) asm volatile("ld.acquire.gpu.global.u32 %0,[%1];" : "=r"(v) : "l"(mp.cnt + 64 * (CX + lane)) : "memory");
                        seen = __ballot_sync(0xffffffffu, v >= (lane < 6 ? 96u : 12u));
                    }
                    TR(5, s);
                    mbar_wait(bar + 8 * (s >= 3 ? BPE + s - 3 : BWE + s));
                    if (elect()) {
#pragma unroll
                        for (int i = 0; i < 6; i++) tma_ld5(dst + (i >> 1) * 8192 + (i & 1) * hs, m, bar + 8 * (BPF + s), 0, row[i], 0, 0, 0);
                    }
                    __syncwarp();
                    dst = dst == sm + O_IN + 2 * STG ? sm + O_IN : dst + STG;
                    TR(3, 3 + s);
                }
            }
        } else if (warp == 13) {
            mbar_wait(bar + 8 * BCM);
            if (lane < R.nu) mbar_expect(bar + 8 * (BZ + lane), SLAB);
            const int v = unit_row<1>(R, lane >> 1, 4 * (lane & 1), lds32(sm + O_CM));
            mbar_wait(bar + 8 * (BD1 + X.nu - 2)); mbar_wait(bar + 8 * (BD1 + X.nu - 1));
#pragma unroll 1
            for (int r = 0; r < R.nu; r++) {
                const int r0 = bcast(v, 2 * r), r1 = bcast(v, 2 * r + 1), gr = (r * NH + R.k) / 48;
                const uint32_t dst = sm + zoff(r), fb = bar + 8 * (BZ + r);
                if (R.fp >= 0) {
                    if (r >= 3) { mbar_wait(bar + 8 * (r == 3 ? BPE + 4 : BD2)); mbar_wait(bar + 8 * (r == 3 ? BPE + 5 : BD2 + 1)); }
                    mbar_wait(bar + 8 * (BI2 + gr));
                }
                poll(mp.cnt + 64 * (CY + gr), NFP);
                TR(5, 8 + r);
                if (elect()) {
#pragma unroll
                    for (int i = 0; i < 8; i++)
                        tma_ld2(dst + unit_off(i), i ? &mp.s30 : &mp.s32, fb, 0, (i < 4 ? r0 : r1) ^ (((i & 1) * 96) ^ ((i & 2) * 272)));
                }
                __syncwarp();
                TR(3, 10 + r);
            }
            if (R.fp >= 0) mbar_wait(bar + 8 * (BPF + 6));
            unsigned last = 0;
            if (lane == 0) last = atomicAdd(mp.cnt + CD, 1u) == NCTA - 1;
            if (__shfl_sync(0xffffffffu, last, 0)) {
                const unsigned e = lane == 31 ? lds32(sm + O_EP) ^ 1 : 0;
                if (lane >= CX) mp.cnt[64 * lane] = 0;
                mp.cnt[32 + lane] = e; mp.cnt[64 + lane] = e; mp.cnt[96 + lane] = e;
            }
        } else {
            const int me = warp & 1;
            uint32_t next = tstart + T0;
            auto pace = [&](int cost) {
                const uint32_t now = until(next, NAP);
                next = ((int)(now - next) > CREDIT ? now - CREDIT : next) + cost;
            };
            const int bal = X.nu == 5 ? 236 : 275;
            mbar_wait(bar + 8 * BCM);
            const unsigned cm = __shfl_sync(0xffffffffu, lds32(sm + O_CM), 0);
            {
                const int iq = 2 * wip + me, w = lane / 3, hg = lane - 3 * w;
                unsigned char* dst = mp.s + (size_t)w_row(R.wfw, hg, w, iq >> 3, cm) * 512 + ((iq & 3) << 14) + ((iq & 4) << 16);
                const uint32_t src = sm + (me ? O_W0 : O_B3) + w * 11264 + hg * 4096;
                fence_async_g();
                if (me) { mbar_wait(bar + 8 * BIS); next = lds32(sm + O_NEXT); }
#pragma unroll 1
                for (int i = 0; i < 3; i++) {
                    mbar_wait(bar + 8 * (BRW + 3 * me + i));
                    if (i == 0) TR(4, me);
                    pace((RW * 11 / 4 * bal) >> 8);
                    if (w == i) bulk_st(dst, src, hg < 2 ? 4096 : 3072);
                    __syncwarp();
                }
                if (lane == 0) { sts32(sm + O_NEXT, next); mbar_arrive(bar + 8 * (BIS + me)); if (EARLY == 2 - me) red_add(mp.cnt + 64 * (CW + R.wfw)); }
                bulk_commit(); bulk_wait<0>();
                __syncwarp();
                if (lane == 0) { if (me && EARLY == 0) red_add(mp.cnt + 64 * (CW + R.wfw)); mbar_arrive(bar + 8 * (BDW + me)); }
                TR(6, me);
            }
#pragma unroll 1
            for (int j = me; j < X.nu; j += 2) {
                const int row = unit_row<0>(X, j, lane, cm);
                const uint32_t src = sm + soff(j) + unit_off(lane);
                unsigned* cn = mp.cnt + 64 * (CX + (j * NH + X.k) / 48);
                mbar_wait(bar + 8 * (BR1 + j));
                mbar_wait(bar + 8 * (BIS + 1 + j));
                next = lds32(sm + O_NEXT);
                if (EARLY == 2 && lane == 0) red_add(cn);
                TR(4, 2 + j);
#pragma unroll 1
                for (int i = 0; i < 4; i++) {
                    pace((R1 * 121 / 64 * bal) >> 8);
                    if ((lane & 27) == i) tma_st2(lane == 0 || (lane == 4 && !X.sd) ? &mp.s32 : &mp.s30, src, 0, row);
                    __syncwarp();
                }
                if (lane == 0) { sts32(sm + O_NEXT, next); mbar_arrive(bar + 8 * (BIS + 2 + j)); if (EARLY == 1) red_add(cn); }
                bulk_commit(); bulk_wait_read<0>();
                __syncwarp();
                if (lane == 0) { if (EARLY == 0) red_add(cn); mbar_arrive(bar + 8 * (BD1 + j)); }
                TR(6, j + 2);
                __syncwarp();
            }
            if (R.fp >= 0) {
                const int first = (X.nu ^ me) & 1;
                int v, vx;
                { const int n = first + (lane & 30), s = n / 3, l = 2 * (n - 3 * s) + (lane & 1); v = stage_row(R, s, l, cm, 1); vx = stage_row(R, s, l, cm, 0); }
                mbar_wait(bar + 8 * (BIS + 1 + X.nu));
                next = lds32(sm + O_NEXT) + first * 2 * R2;
                uint32_t prev = 0;
                int s = 0, w = first;
#pragma unroll 1
                for (int i = 0; s < 7; i += 2) {
                    const int r0 = bcast(v, i), r1 = bcast(v, i + 1), rx = bcast(vx, i + 1);
                    const int bi = 2 * w + (s & 1);
                    const uint32_t src = sm + O_OUT + (s & 1) * STG + w * 8192, hs = s < 6 ? 4096 : 512;
                    const CUtensorMap* m = s < 6 ? &mp.p16 : &mp.p2;
                    mbar_wait_ph(bar + 8 * (BR2 + bi), (s >> 1) & 1);
                    if (s < 6) {
                        const uint32_t now = until(next, NAP);
                        next = ((int)(now - next) > CREDIT2 ? now - CREDIT2 : next) + 4 * R2;
                    }
                    if (elect()) {
                        tma_st5(m, src, 0, r0, 0, 0, 0);
                        tma_st5(m, src + hs, 0, r1, 0, 0, 0);
                        if (R.fp == 15) tma_st5(m, src + hs, 0, rx, 0, 0, 0);
                        bulk_commit();
                        bulk_wait_read<1>();
                        if (prev) mbar_arrive(prev);
                        if (w == 2) { if (LATE2) bulk_wait_read<0>(); red_add(mp.cnt + 64 * (CY + s)); mbar_arrive(bar + 8 * (BI2 + s)); }
                    }
                    __syncwarp();
                    if (w != 1) TR(4 + w, 7 + s);
                    prev = bar + 8 * (BDP + bi);
                    w += 2; if (w > 2) { w -= 3; s++; }
                }
                if (elect()) mbar_arrive(bar + 8 * (BD2 + me));
                __syncwarp();
                next = clock();
            }
#pragma unroll 1
            for (int r = me; r < R.nu; r += 2) {
                const int u = r * NH + R.k, ts = u / 3, cg = u - 3 * ts, tr = ts / 14, th = 7 * R.sd + tr, tw = ts - 14 * tr;
                mbar_wait(bar + 8 * (BR3 + r));
                if (r && r < 3) { mbar_wait(bar + 8 * (BIS + 6 + r)); next = lds32(sm + O_NEXT); }
                TR(4, 14 + r);
#pragma unroll 1
                for (int c = 0; c < 2; c++) {
                    if (r < 3) pace(2 * R3);
                    if (elect()) tma_st4(&mp.y, sm + zoff(r) + c * 8192, 32 * cg, 0, 16 * th, 4 * tw + 2 * c);
                    __syncwarp();
                }
                if (lane == 0) { sts32(sm + O_NEXT, next); mbar_arrive(bar + 8 * (BIS + 7 + r)); }
                __syncwarp();
            }
            bulk_commit(); bulk_wait_read<0>();
            TR(4, 19 + me);
        }
    } else {
        asm volatile("setmaxnreg.inc.sync.aligned.u32 160;");
        const int lane = laneid();
        const int wg = __shfl_sync(0xffffffffu, tid >> 7, 0), wq = __shfl_sync(0xffffffffu, tid >> 5, 0) & 3;
        const Role R(__shfl_sync(0xffffffffu, lds16(sm + O_ROLE), 0));
#pragma unroll 1
        for (int it = 0; it <= wg; it++) {
            const int j = it > 0, cg = j ? wg + it - 2 : wg;
            mbar_wait(bar + 8 * (j == 0 && wg ? BWL + wg - 1 : BW + j));
            TR(wg, 24 + 2 * it);
            wgen(sm + (j ? O_W1 : O_W0), sm + O_WT, sm + (j ? O_W0 : O_B3) + cg * 11264, 4 * cg + wq, (2 * wip + j) & 3, lane, bar + 8 * (BWC + j),
                 j == 0 && wg < 2 ? bar + 8 * (BWL + wg) : 0, bar + 8 * (j ? BWC : BW), ~lds32(sm + O_EP));
            staged(bar + 8 * (BRW + 3 * j + cg), lane);
            TR(wg, 25 + 2 * it);
        }
        mbar_wait(bar + 8 * BC);
#pragma unroll 1
        for (int r = wg; r < X.nu; r += 3) {
            mbar_wait(bar + 8 * (BX + r));
            TR(wg, 1 + 2 * (r / 3));
            p1_unit(sm + xoff(r), sm + soff(r), sm + O_C, wg, wq, laneid());
            staged(bar + 8 * (BR1 + r), laneid());
            TR(wg, 2 + 2 * (r / 3));
        }
        uint32_t phw = 0;
        if (R.fp >= 0) {
            const int lane = laneid();
            uint32_t Wf[48];
            const int g = lane >> 2, q = lane & 3;
            {
                const int b = wg == 2 ? 0 : wg + 1;
                const uint32_t p = sm + O_IN + b * STG + q * 1024 + wq * 128 + ((g ^ (2 * q) ^ (4 * ((R.fp % 11) & 1))) << 4);
                mbar_wait(bar + 8 * (BWF + b));
                TR(wg, 5);
#pragma unroll 1
                for (int it = 0; it < 4096; it++) {
                    const uint32_t tag = ~lds32(sm + O_EP), m = g == 7;
                    uint32_t bad = 0;
#pragma unroll
                    for (int i = 0; i < 12; i++) {
                        uint4 v = lds128((p ^ (i >= 6 ? 544 : 0)) + (i % 6) * 4096);
                        Wf[4 * i] = v.x; Wf[4 * i + 1] = v.y; Wf[4 * i + 2] = v.z; Wf[4 * i + 3] = v.w & ~m;
                        bad |= v.w ^ tag;
                    }
                    if (!bar_any(1 + wg, 128, bad & m)) break;
                    if (wq == 0) {
                        TRC(2);
                        fence_async_s();
                        if (lane == 0) mbar_expect(bar + 8 * (BRT + 1 + wg), STG);
                        __syncwarp();
                        const int l = laneid(), fp = Role(lds16(sm + O_ROLE)).fp, fw = fp / 11, fh = fp - 11 * fw;
                        if (l < 3) tma_ld4(sm + O_IN + b * STG + l * 8192, &mp.wf, bar + 8 * (BRT + 1 + wg), 0, w_row(fw, fh >> 2, wg, l, lds32(sm + O_CM)) + 2 * (fh & 3), 0, 0);
                        __syncwarp();
                    }
                    mbar_wait_ph(bar + 8 * (BRT + 1 + wg), phw); phw ^= 1;
                }
                staged(bar + 8 * (BWE + b), lane);
            }
            const int ro = (lane & 6) + ((lane >> 3) & 1);
            const uint32_t o0 = sm + O_OUT + wg * 8192 + (lane >> 4) * 1024 + ro * 128 + (((2 * wq + (lane & 1)) ^ ro) << 4);
            const uint32_t m = wq == 3 && g >= 6 ? 0x10000 : 0, tg = g == 6 ? TAGZ << 16 : TAGZ;
            uint32_t ph = 0;
            const int t = 32 * wq + lane;
            uint32_t c0 = t * 128 + ((7 ^ (t & 7)) << 4) + 12, c1 = (c0 & 8191) + 16384;
            auto stale = [&](uint32_t in) { return (((lds32(in + c0) ^ TAGX) | (lds32(in + c1) ^ TAGX)) & TAGM) != 0; };
            auto landed = [&](int s, uint32_t in) {
                mbar_wait(bar + 8 * (BPF + s));
#pragma unroll 1
                for (int it = 0; it < 4096; it++) {
                    if (!bar_any(1 + wg, 128, stale(in))) break;
                    fence_async_s();
                    bar_sync(7, 384);
                    if (wg + wq == 0) {
                        TRC(0);
                        if (lane == 0) mbar_expect(bar + 8 * BRT, s < 6 ? STG : 3072);
                        __syncwarp();
                        const int l = laneid();
                        if (l < 6) tma_ld5(in + stage_off(s, l), s < 6 ? &mp.p16 : &mp.p2, bar + 8 * BRT, 0, stage_row(Role(lds16(sm + O_ROLE)), s, l, lds32(sm + O_CM), 0), 0, 0, 0);
                        __syncwarp();
                    }
                    mbar_wait_ph(bar + 8 * BRT, ph); ph ^= 1;
                }
            };
            uint32_t in = sm + O_IN;
            bool todo = true;
            mbar_wait(bar + 8 * BD1);
#pragma unroll 1
            for (int s = 0; s < 6; s++) {
                if (todo) landed(s, in);
                const uint32_t nx = in == sm + O_IN + 2 * STG ? sm + O_IN : in + STG;
                if (s == 5) { c0 &= 8192 + 1023; c1 &= 16384 + 1023; }
                p2_step<8>(Wf, in, o0 + (s & 1) * STG, m, tg, bar, lane, wg, s,
                           [&]() { todo = !mbar_test(bar + 8 * (BPF + s + 1)) || stale(nx); });
                todo = bar_any(1 + wg, 128, todo);
                in = nx;
                staged(bar + 8 * (BR2 + 2 * wg + (s & 1)), lane);
                TR(wg, 6 + s);
            }
            if (todo) landed(6, in);
            p2_step<1>(Wf, in, o0, m, tg, bar, lane, wg, 6, []() {});
            staged(bar + 8 * (BR2 + 2 * wg), lane);
            TR(wg, 12);
        }
#pragma unroll 1
        for (int r = wg; r < R.nu; r += 3) {
            mbar_wait(bar + 8 * (BZ + r));
            TR(wg, 13 + 2 * (r / 3));
#pragma unroll 1
            for (int it = 0; it < 4096; it++) {
                if (p3_unit(sm + zoff(r), sm + O_C, wg, wq, laneid())) break;
                if (wq == 0) {
                    TRC(1);
                    fence_async_s();
                    if (laneid() == 0) mbar_expect(bar + 8 * (BRT + 1 + wg), SLAB);
                    __syncwarp();
                    const int l = laneid();
                    if (l < 8) tma_ld2(sm + zoff(r) + unit_off(l), l ? &mp.s30 : &mp.s32, bar + 8 * (BRT + 1 + wg), 0, unit_row<1>(Role(lds16(sm + O_ROLE)), r, l, lds32(sm + O_CM)));
                    __syncwarp();
                }
                mbar_wait_ph(bar + 8 * (BRT + 1 + wg), phw); phw ^= 1;
            }
            staged(bar + 8 * (BR3 + r), laneid());
            TR(wg, 14 + 2 * (r / 3));
        }
    }
}

typedef CUresult (*EncFn)(CUtensorMap*, CUtensorMapDataType, cuuint32_t, void*, const cuuint64_t*, const cuuint64_t*, const cuuint32_t*,
                          const cuuint32_t*, CUtensorMapInterleave, CUtensorMapSwizzle, CUtensorMapL2promotion, CUtensorMapFloatOOBfill);

void enc(EncFn f, CUtensorMap* m, void* p, int rank, const cuuint64_t* dims, const cuuint64_t* strides, const cuuint32_t* box,
         CUtensorMapSwizzle sw, CUtensorMapL2promotion pr = CU_TENSOR_MAP_L2_PROMOTION_NONE) {
    cuuint32_t es[5] = {1, 1, 1, 1, 1};
    f(m, CU_TENSOR_MAP_DATA_TYPE_BFLOAT16, rank, p, dims, strides, box, es, CU_TENSOR_MAP_INTERLEAVE_NONE, sw, pr, CU_TENSOR_MAP_FLOAT_OOB_FILL_NONE);
}

}

extern "C" void kernel_launch(void* const* d_in, const int* in_sizes, int n_in, void* d_out, int out_size) {
    void* fn = nullptr; cudaDriverEntryPointQueryResult qr;
    cudaGetDriverEntryPoint("cuTensorMapEncodeTiled", &fn, cudaEnableDefault, &qr);
    EncFn f = (EncFn)fn;
    void* pS; cudaGetSymbolAddress(&pS, g_S);
    pS = (void*)(((uintptr_t)pS + (1u << 21) - 1) & ~(uintptr_t)((1u << 21) - 1));
    Maps mp;
    cudaGetSymbolAddress((void**)&mp.ctab, g_ctab); cudaGetSymbolAddress((void**)&mp.wtab, g_wtab); cudaGetSymbolAddress((void**)&mp.cnt, g_cnt);
    mp.s = (unsigned char*)pS; mp.x = (const unsigned char*)d_in[0]; mp.wraw = (const unsigned char*)d_in[1];
    { cuuint64_t d[4] = {256, NPAGE << 12, 4, 2}, s[3] = {512, 1 << 14, 1 << 18}; cuuint32_t b[4] = {256, 2, 4, 2}; enc(f, &mp.wf, pS, 4, d, s, b, CU_TENSOR_MAP_SWIZZLE_NONE); }
    {
        cuuint64_t d[3] = {96, 224, 224}, s[2] = {192, 43008};
        cuuint32_t b6[3] = {32, 8, 6}, b16[3] = {32, 8, 16};
        enc(f, &mp.x6, d_in[0], 3, d, s, b6, CU_TENSOR_MAP_SWIZZLE_64B, CU_TENSOR_MAP_L2_PROMOTION_L2_128B);
        enc(f, &mp.x16, d_in[0], 3, d, s, b16, CU_TENSOR_MAP_SWIZZLE_64B, CU_TENSOR_MAP_L2_PROMOTION_L2_128B);
    }
    { cuuint64_t d[4] = {96, 4, 224, 56}, s[3] = {192, 43008, 768}; cuuint32_t b[4] = {32, 4, 16, 2}; enc(f, &mp.y, d_out, 4, d, s, b, CU_TENSOR_MAP_SWIZZLE_64B); }
    {
        cuuint64_t d[2] = {64, NPAGE << 14}, s[1] = {128};
        cuuint32_t b32[2] = {64, 32}, b30[2] = {64, 30};
        enc(f, &mp.s32, pS, 2, d, s, b32, CU_TENSOR_MAP_SWIZZLE_128B);
        enc(f, &mp.s30, pS, 2, d, s, b30, CU_TENSOR_MAP_SWIZZLE_128B);
    }
    {
        cuuint64_t d[5] = {64, NPAGE << 14, 4, 2, 2}, s[4] = {128, 1 << 14, 1 << 18, 1 << 20};
        cuuint32_t b16[5] = {64, 2, 4, 2, 2}, b2[5] = {64, 2, 2, 1, 1};
        enc(f, &mp.p16, pS, 5, d, s, b16, CU_TENSOR_MAP_SWIZZLE_128B);
        enc(f, &mp.p2, pS, 5, d, s, b2, CU_TENSOR_MAP_SWIZZLE_128B);
    }
    { cuuint64_t d[3] = {64, 144, 49}, s[2] = {128, 18432}; cuuint32_t b[3] = {64, 3, 49}; enc(f, &mp.w, d_in[1], 3, d, s, b, CU_TENSOR_MAP_SWIZZLE_128B); }
    cudaFuncSetAttribute(fftconv_kernel, cudaFuncAttributeMaxDynamicSharedMemorySize, SMEM);
    fftconv_kernel<<<NCTA, 512, SMEM>>>(mp);
}
```

```cpp
#include <cuda_runtime.h>
#include <cuda_bf16.h>
#include <cuda.h>
#include <stdint.h>

#define TUNABLES {260, 310, 250, 280, 500, 250, 30, 1, 1600, 600, 1, 2000, 500, 0, 0, 4}
constexpr int c_tune[16] = TUNABLES;
template <int I> struct TuneV { static constexpr int v = c_tune[I]; };
#define TV(i) TuneV<i>::v
#define RW TV(0)
#define R1 TV(1)
#define R2 TV(2)
#define R3 TV(3)
#define CREDIT TV(4)
#define LPW TV(5)
#define NAP TV(6)
#define EARLY TV(7)
#define T0 0
#define XD TV(9)
#define XD0 TV(8)
#define LATE2 TV(10)
#define PFW 1
#define VT TV(11)
#define CREDIT2 TV(12)
#define W1AT TV(13)
#define X0N TV(14)
#define WIN TV(15)
#define SPLIT 3

namespace {

constexpr int NCTA = 132, NH = 66;
constexpr int NUH = 294;
constexpr int NFP = 121;
constexpr int BLK = 33792;
constexpr int SLAB = 242 * 128;
constexpr int WPIECE = 19456;
constexpr int STG = 24576;
constexpr int NPS = 16, NPAGE = 21;
constexpr int O_B4 = 0, O_B0 = 87040, O_B2 = O_B0 + 2 * BLK, O_B3 = O_B0 + 3 * BLK;
constexpr int O_W1 = 0, O_W0 = 2 * WPIECE, O_WT = 4 * WPIECE;
constexpr int O_IN = 33792, O_OUT = O_IN + 3 * STG, O_Z3 = O_IN + STG, O_Z4 = 124928;
constexpr int O_C = 222208, O_BAR = 230912, SMEM = 232448;
constexpr int C_P1A = 0, C_P1B = 2560, C_P3 = 7168, C_BYTES = 8704, WT_BYTES = 6912;
constexpr int BC = 0, BW = 1, BX = 3, BZ = 8, BWF = 13, BPF = 16, BCM = 23, BDW = 24, BD1 = 26, BDP = 31, BD2 = 37, BIS = 39, BI2 = 51, BRT = 58, BRL = 62;
constexpr int BPE = 64, BWC = 70;
constexpr int BR2 = 72, BRW = 78, BWL = 84, BR1 = 86, BR3 = 91, BWE = 96;
constexpr int O_NEXT = O_BAR + 1016, O_ROLE = O_BAR + 1000, O_PT = O_BAR + 976, O_CM = O_BAR + 1008, O_PERM = O_BAR + 944;
constexpr uint32_t TAGM = 0x00010001u, TAGX = 0x00000001u, TAGZ = 0x00010000u;

constexpr uint16_t LUT_A[11] = {0x3f95, 0x3f92, 0x3f8c, 0x3f83, 0x3f6f, 0x3f53, 0x3f33, 0x3f0f, 0x3ed1, 0x3e7e, 0x3daa};
constexpr uint16_t LUT_B[11] = {0x3fe9, 0x3fe4, 0x3fdb, 0x3fcd, 0x3fbb, 0x3fa5, 0x3f8c, 0x3f60, 0x3f23, 0x3ec7, 0x3e05};
constexpr uint16_t LUT_W[12] = {0x3abb, 0x3ab9, 0x3ab3, 0x3aaa, 0x3a9d, 0x3a8d, 0x3a75, 0x3a4a, 0x3a1b, 0x39d3, 0x3955, 0};
constexpr uint16_t basis(int setb, int f, int a, int sn) {
    if (f < 0 || f > 10 || a < 0 || a > 21) return 0;
    int k = ((2 * f + 1) * (2 * a - 21) - 22 * sn + 88 * 7) % 88;
    if (k > 44) k = 88 - k;
    int neg = 0;
    if (k > 22) { k = 44 - k; neg = 1; }
    return (uint16_t)((setb ? LUT_B[k >> 1] : LUT_A[k >> 1]) | (neg << 15));
}
constexpr uint16_t neg16(uint16_t v) { return v ? (uint16_t)(v ^ 0x8000) : v; }
constexpr uint16_t wcoef(int fw, int fl, int sn, int tap) {
    if (fl > 21) return 0;
    int fh = fl >> 1, kh = tap / 7, kw = tap - 7 * kh;
    int u = (2 * fh + 1) * kh;
    if (fl & 1) u = -u;
    int k = (u + (2 * fw + 1) * kw - 11 * sn + 44 * 4) % 44;
    if (k > 22) k = 44 - k;
    int neg = 0;
    if (k > 11) { k = 22 - k; neg = 1; }
    return (uint16_t)(LUT_W[k] | (neg << 15));
}
struct alignas(128) CTab { uint16_t v[C_BYTES / 2]; };
struct alignas(128) WTab { uint16_t v[WT_BYTES / 2]; };
constexpr CTab make_ctab() {
    CTab t{};
    for (int lane = 0; lane < 32; lane++) {
        int g = lane >> 2, q = lane & 3;
        for (int r = 0; r < 18; r++) {
            int quad = r >> 2, j = r & 3;
            int set = quad < 3 ? quad : (quad == 3 ? 1 + (j >> 1) : 0);
            int sn = (j ^ (set == 0 ? g : g >> 1)) & 1;
            int t8 = quad < 3 ? 1 + (j >> 1) : 0;
            int b = 8 * t8 + 2 * q - 2;
            int fw = set == 0 ? g : (((g & 1) == set - 1) ? 8 + (g >> 1) : -1);
            int o = (C_P1A + (quad * 32 + lane) * 16 + j * 4) / 2;
            t.v[o] = basis(0, fw, b, sn); t.v[o + 1] = basis(0, fw, b + 1, sn);
        }
        for (int r = 0; r < 12; r++) {
            int o = (C_P3 + ((r >> 2) * 32 + lane) * 16 + (r & 3) * 4) / 2;
            if (r < 6) {
                int a = 6 + g + 8 * (r & 1), fh = 4 * (r >> 1) + q;
                t.v[o] = basis(0, fh, a, 0); t.v[o + 1] = basis(0, fh, a, 1);
            } else {
                int be = r < 8 ? r - 6 : (r - 8) >> 1, nu = r < 8 ? 2 : (r & 1);
                int b = 6 + 8 * be + 4 * (g & 1) + (g >> 1);
                t.v[o] = basis(1, 4 * nu + q, b, 0); t.v[o + 1] = basis(1, 4 * nu + q, b, 1);
            }
        }
    }
    for (int kc = 0; kc < 6; kc++)
        for (int nb = 0; nb < 6; nb++)
            for (int n = 0; n < 8; n++)
                for (int k = 0; k < 8; k++) {
                    int nu = kc >> 1, ds = kc & 1, im = nb & 1, fh = 4 * (nb >> 1) + (n >> 1), mi = n & 1;
                    int a = nu == 0 ? 6 + k : (nu == 1 ? 14 + k : (k < 6 ? k : -1));
                    uint16_t v = basis(0, fh, a, ds ^ im);
                    if (ds != im && (im ? mi : !mi)) v = neg16(v);
                    t.v[C_P1B / 2 + ((kc * 6 + nb) * 8 + n) * 8 + k] = v;
                }
    return t;
}
constexpr WTab make_wtab(int fw) {
    WTab t{};
    for (int nb = 0; nb < 6; nb++)
        for (int n = 0; n < 8; n++) {
            for (int tap = 0; tap < 48; tap++) t.v[(((tap >> 3) * 6 + nb) * 8 + n) * 8 + (tap & 7)] = wcoef(fw, 4 * nb + (n >> 1), n & 1, tap);
            t.v[((7 * 6 + nb) * 8 + n) * 8] = wcoef(fw, 4 * nb + (n >> 1), n & 1, 48);
        }
    return t;
}
__device__ const CTab g_ctab = make_ctab();
__device__ const WTab g_wtab[11] = {make_wtab(0), make_wtab(1), make_wtab(2), make_wtab(3), make_wtab(4), make_wtab(5),
                                    make_wtab(6), make_wtab(7), make_wtab(8), make_wtab(9), make_wtab(10)};

__device__ __align__(1024) unsigned char g_S[(size_t)(NPAGE + 1) << 21];
constexpr int CT = 0, CX = 2, CY = 10, CW = 18, CD = 29, CV = 32;
__device__ __align__(512) unsigned g_cnt[40 * 64];

struct Maps {
    const unsigned char* ctab; const unsigned char* wtab; const unsigned char* x; unsigned* cnt; unsigned char* s;
    const unsigned char* wraw;
    alignas(64) CUtensorMap w, x22, x6, x16, wf, s32, s30, p16, p2, y;
};

#define TR(role, i)
#define TRL(role, i)
#define TRC(i)

__device__ __forceinline__ uint32_t s2u(const void* p) { return (uint32_t)__cvta_generic_to_shared(p); }
__device__ __forceinline__ void mbar_init(uint32_t b, int c) { asm volatile("mbarrier.init.shared::cta.b64 [%0],%1;" ::"r"(b), "r"(c) : "memory"); }
__device__ __forceinline__ void mbar_expect(uint32_t b, uint32_t tx) { asm volatile("mbarrier.arrive.expect_tx.shared::cta.b64 _,[%0],%1;" ::"r"(b), "r"(tx) : "memory"); }
__device__ __forceinline__ void mbar_arrive(uint32_t b) { asm volatile("mbarrier.arrive.shared::cta.b64 _,[%0];" ::"r"(b) : "memory"); }
__device__ __forceinline__ bool mbar_try(uint32_t b, uint32_t ph) {
    uint32_t ok;
    asm volatile("{.reg .pred p; mbarrier.try_wait.parity.shared::cta.b64 p,[%1],%2; selp.u32 %0,1,0,p;}" : "=r"(ok) : "r"(b), "r"(ph) : "memory");
    return ok;
}
__device__ __forceinline__ void mbar_wait_ph(uint32_t b, uint32_t ph) {
    if (mbar_try(b, ph)) return;
#pragma unroll 1
    for (int it = 0; it < (1 << 16); it++)
        if (mbar_try(b, ph)) return;
}
__device__ __forceinline__ void mbar_wait(uint32_t b) { mbar_wait_ph(b, 0); }
__device__ __forceinline__ void region_end(uint32_t b) {
    int it = 0;
    while (!mbar_try(b, 0) && ++it < (1 << 16)) {}
}
__device__ __forceinline__ bool mbar_test(uint32_t b) {
    uint32_t ok;
    asm volatile("{.reg .pred p; mbarrier.test_wait.parity.shared::cta.b64 p,[%1],0; selp.u32 %0,1,0,p;}" : "=r"(ok) : "r"(b) : "memory");
    return ok;
}
__device__ __forceinline__ bool elect() {
    uint32_t r;
    asm volatile("{.reg .pred p; elect.sync _|p,0xffffffff; selp.u32 %0,1,0,p;}" : "=r"(r));
    return r;
}
__device__ __forceinline__ uint32_t until(uint32_t t, int nap) {
    uint32_t now = clock();
    while ((int)(now - t) < 0) { if (nap) __nanosleep(nap); now = clock(); }
    return now;
}
__device__ __forceinline__ int bcast(int v, int l) { return __shfl_sync(0xffffffffu, v, l); }
__device__ __forceinline__ void poll(const unsigned* c, unsigned tgt) {
    unsigned v; int it = 0;
    do { asm volatile("ld.acquire.gpu.global.u32 %0,[%1];" : "=r"(v) : "l"(c) : "memory"); } while (v < tgt && ++it < (1 << 16));
}
__device__ __forceinline__ bool bar_any(int id, int n, bool v) {
    uint32_t r;
    asm volatile("{.reg .pred p,q; setp.ne.u32 p,%3,0; bar.red.or.pred q,%1,%2,p; selp.u32 %0,1,0,q;}" : "=r"(r) : "r"(id), "r"(n), "r"((uint32_t)v) : "memory");
    return __any_sync(0xffffffffu, r);
}
__device__ __forceinline__ int laneid() { int l; asm volatile("mov.u32 %0,%%laneid;" : "=r"(l)); return l; }
__device__ __forceinline__ uint32_t lds32(uint32_t a) { uint32_t v; asm volatile("ld.shared.u32 %0,[%1];" : "=r"(v) : "r"(a) : "memory"); return v; }
__device__ __forceinline__ uint32_t lds8(uint32_t a) { uint32_t v; asm volatile("ld.shared.u8 %0,[%1];" : "=r"(v) : "r"(a) : "memory"); return v; }
__device__ __forceinline__ uint32_t tagged(uint32_t v, uint32_t m, uint32_t t) { return (v & ~m) | (t & m); }
__device__ __forceinline__ void red_add(unsigned* c, unsigned v = 1) { asm volatile("red.relaxed.gpu.global.add.u32 [%0],%1;" ::"l"(c), "r"(v) : "memory"); }
__device__ __forceinline__ void pf_l2(const void* p) { asm volatile("prefetch.global.L2 [%0];" ::"l"(p)); }
__device__ __forceinline__ void fence_async_s() { asm volatile("fence.proxy.async.shared::cta;" ::: "memory"); }
__device__ __forceinline__ void fence_async_g() { asm volatile("fence.proxy.async.global;" ::: "memory"); }
__device__ __forceinline__ void bulk_ld(uint32_t dst, const void* src, uint32_t bytes, uint32_t bar) {
    asm volatile("cp.async.bulk.shared::cluster.global.mbarrier::complete_tx::bytes [%0],[%1],%2,[%3];" ::"r"(dst), "l"(src), "r"(bytes), "r"(bar) : "memory");
}
__device__ __forceinline__ void tma_ld2(uint32_t dst, const CUtensorMap* m, uint32_t bar, int c0, int c1) {
    asm volatile("cp.async.bulk.tensor.2d.shared::cluster.global.mbarrier::complete_tx::bytes [%0],[%1,{%3,%4}],[%2];" ::"r"(dst), "l"(m), "r"(bar), "r"(c0), "r"(c1) : "memory");
}
__device__ __forceinline__ void tma_ld3(uint32_t dst, const CUtensorMap* m, uint32_t bar, int c0, int c1, int c2) {
    asm volatile("cp.async.bulk.tensor.3d.shared::cluster.global.mbarrier::complete_tx::bytes [%0],[%1,{%3,%4,%5}],[%2];" ::"r"(dst), "l"(m), "r"(bar), "r"(c0), "r"(c1), "r"(c2) : "memory");
}
__device__ __forceinline__ void tma_ld4(uint32_t dst, const CUtensorMap* m, uint32_t bar, int c0, int c1, int c2, int c3) {
    asm volatile("cp.async.bulk.tensor.4d.shared::cluster.global.mbarrier::complete_tx::bytes [%0],[%1,{%3,%4,%5,%6}],[%2];" ::"r"(dst), "l"(m), "r"(bar), "r"(c0), "r"(c1), "r"(c2), "r"(c3) : "memory");
}
__device__ __forceinline__ void bulk_st(void* dst, uint32_t src, uint32_t bytes) {
    asm volatile("cp.async.bulk.global.shared::cta.bulk_group [%0],[%1],%2;" ::"l"(dst), "r"(src), "r"(bytes) : "memory");
}
__device__ __forceinline__ void tma_ld5(uint32_t dst, const CUtensorMap* m, uint32_t bar, int c0, int c1, int c2, int c3, int c4) {
    asm volatile("cp.async.bulk.tensor.5d.shared::cluster.global.mbarrier::complete_tx::bytes [%0],[%1,{%3,%4,%5,%6,%7}],[%2];" ::"r"(dst), "l"(m), "r"(bar), "r"(c0), "r"(c1), "r"(c2), "r"(c3), "r"(c4) : "memory");
}
__device__ __forceinline__ void tma_st2(const CUtensorMap* m, uint32_t src, int c0, int c1) {
    asm volatile("cp.async.bulk.tensor.2d.global.shared::cta.bulk_group [%0,{%2,%3}],[%1];" ::"l"(m), "r"(src), "r"(c0), "r"(c1) : "memory");
}
__device__ __forceinline__ void tma_st4(const CUtensorMap* m, uint32_t src, int c0, int c1, int c2, int c3) {
    asm volatile("cp.async.bulk.tensor.4d.global.shared::cta.bulk_group [%0,{%2,%3,%4,%5}],[%1];" ::"l"(m), "r"(src), "r"(c0), "r"(c1), "r"(c2), "r"(c3) : "memory");
}
__device__ __forceinline__ void tma_st5(const CUtensorMap* m, uint32_t src, int c0, int c1, int c2, int c3, int c4) {
    asm volatile("cp.async.bulk.tensor.5d.global.shared::cta.bulk_group [%0,{%2,%3,%4,%5,%6}],[%1];" ::"l"(m), "r"(src), "r"(c0), "r"(c1), "r"(c2), "r"(c3), "r"(c4) : "memory");
}
__device__ __forceinline__ void bulk_commit() { asm volatile("cp.async.bulk.commit_group;" ::: "memory"); }
template <int N> __device__ __forceinline__ void bulk_wait() { asm volatile("cp.async.bulk.wait_group %0;" ::"n"(N) : "memory"); }
template <int N> __device__ __forceinline__ void bulk_wait_read() { asm volatile("cp.async.bulk.wait_group.read %0;" ::"n"(N) : "memory"); }
__device__ __forceinline__ void bar_sync(int id, int n) { asm volatile("bar.sync %0,%1;" ::"r"(id), "r"(n) : "memory"); }

__device__ __forceinline__ uint4 lds128(uint32_t a) {
    uint4 v; asm volatile("ld.shared.v4.u32 {%0,%1,%2,%3},[%4];" : "=r"(v.x), "=r"(v.y), "=r"(v.z), "=r"(v.w) : "r"(a)); return v;
}
__device__ __forceinline__ void sts128(uint32_t a, uint32_t x, uint32_t y, uint32_t z, uint32_t w) {
    asm volatile("st.shared.v4.u32 [%0],{%1,%2,%3,%4};" ::"r"(a), "r"(x), "r"(y), "r"(z), "r"(w) : "memory");
}
__device__ __forceinline__ void sts64(uint32_t a, uint32_t x, uint32_t y) { asm volatile("st.shared.v2.u32 [%0],{%1,%2};" ::"r"(a), "r"(x), "r"(y) : "memory"); }
__device__ __forceinline__ void sts128p(uint32_t a, uint32_t x, uint32_t y, uint32_t z, uint32_t w, bool p) {
    asm volatile("{.reg .pred p; setp.ne.u32 p,%5,0; @p st.shared.v4.u32 [%0],{%1,%2,%3,%4};}" ::"r"(a), "r"(x), "r"(y), "r"(z), "r"(w), "r"((uint32_t)p) : "memory");
}
__device__ __forceinline__ void sts32(uint32_t a, uint32_t x) { asm volatile("st.shared.u32 [%0],%1;" ::"r"(a), "r"(x) : "memory"); }
__device__ __forceinline__ uint32_t pk(float lo, float hi) { uint32_t r; asm("cvt.rn.bf16x2.f32 %0,%1,%2;" : "=r"(r) : "f"(hi), "f"(lo)); return r; }

__device__ __forceinline__ uint32_t pkv(float lo, float hi) { uint32_t r; asm volatile("cvt.rn.bf16x2.f32 %0,%1,%2;" : "=r"(r) : "f"(hi), "f"(lo)); return r; }

__device__ __forceinline__ void mma16z(float* d, uint32_t a0, uint32_t a1, uint32_t a2, uint32_t a3, uint32_t b0, uint32_t b1) {
    asm("mma.sync.aligned.m16n8k16.row.col.f32.bf16.bf16.f32 {%0,%1,%2,%3},{%4,%5,%6,%7},{%8,%9},{%10,%10,%10,%10};"
        : "=f"(d[0]), "=f"(d[1]), "=f"(d[2]), "=f"(d[3]) : "r"(a0), "r"(a1), "r"(a2), "r"(a3), "r"(b0), "r"(b1), "f"(0.f));
}
__device__ __forceinline__ void mma16(float* d, uint32_t a0, uint32_t a1, uint32_t a2, uint32_t a3, uint32_t b0, uint32_t b1) {
    asm("mma.sync.aligned.m16n8k16.row.col.f32.bf16.bf16.f32 {%0,%1,%2,%3},{%4,%5,%6,%7},{%8,%9},{%0,%1,%2,%3};"
        : "+f"(d[0]), "+f"(d[1]), "+f"(d[2]), "+f"(d[3]) : "r"(a0), "r"(a1), "r"(a2), "r"(a3), "r"(b0), "r"(b1));
}
__device__ __forceinline__ void mma8(float* d, uint32_t a0, uint32_t a1, uint32_t b0) {
    asm("mma.sync.aligned.m16n8k8.row.col.f32.bf16.bf16.f32 {%0,%1,%2,%3},{%4,%5},{%6},{%0,%1,%2,%3};"
        : "+f"(d[0]), "+f"(d[1]), "+f"(d[2]), "+f"(d[3]) : "r"(a0), "r"(a1), "r"(b0));
}
__device__ __forceinline__ void wg_fence() { asm volatile("wgmma.fence.sync.aligned;" ::: "memory"); }
__device__ __forceinline__ void wg_commit() { asm volatile("wgmma.commit_group.sync.aligned;" ::: "memory"); }
template <int N> __device__ __forceinline__ void wg_wait() { asm volatile("wgmma.wait_group.sync.aligned %0;" ::"n"(N) : "memory"); }
template <int N> __device__ __forceinline__ void pin(float (&d)[N]) {
#pragma unroll
    for (int i = 0; i < N; i++) asm volatile("" : "+f"(d[i])::"memory");
}
#define ACC8(o) "+f"(d[o]), "+f"(d[o + 1]), "+f"(d[o + 2]), "+f"(d[o + 3]), "+f"(d[o + 4]), "+f"(d[o + 5]), "+f"(d[o + 6]), "+f"(d[o + 7])
#define OUT8(o) "=f"(d[o]), "=f"(d[o + 1]), "=f"(d[o + 2]), "=f"(d[o + 3]), "=f"(d[o + 4]), "=f"(d[o + 5]), "=f"(d[o + 6]), "=f"(d[o + 7])
template <int ACC> __device__ __forceinline__ void wgmma48(float (&d)[24], uint32_t a0, uint32_t a1, uint32_t a2, uint32_t a3, uint64_t desc) {
    if (ACC)
        asm volatile("wgmma.mma_async.sync.aligned.m64n48k16.f32.bf16.bf16 "
                     "{%0,%1,%2,%3,%4,%5,%6,%7,%8,%9,%10,%11,%12,%13,%14,%15,%16,%17,%18,%19,%20,%21,%22,%23},{%24,%25,%26,%27},%28,%29,1,1,0;"
                     : ACC8(0), ACC8(8), ACC8(16) : "r"(a0), "r"(a1), "r"(a2), "r"(a3), "l"(desc), "n"(ACC & 1));
    else
        asm volatile("wgmma.mma_async.sync.aligned.m64n48k16.f32.bf16.bf16 "
                     "{%0,%1,%2,%3,%4,%5,%6,%7,%8,%9,%10,%11,%12,%13,%14,%15,%16,%17,%18,%19,%20,%21,%22,%23},{%24,%25,%26,%27},%28,0,1,1,0;"
                     : OUT8(0), OUT8(8), OUT8(16) : "r"(a0), "r"(a1), "r"(a2), "r"(a3), "l"(desc));
}
template <int ACC> __device__ __forceinline__ void wgmma_p2(float (&d)[32], const uint32_t* a, uint64_t desc) {
    if (ACC)
        asm volatile("wgmma.mma_async.sync.aligned.m64n64k16.f32.bf16.bf16 "
                     "{%0,%1,%2,%3,%4,%5,%6,%7,%8,%9,%10,%11,%12,%13,%14,%15,%16,%17,%18,%19,%20,%21,%22,%23,%24,%25,%26,%27,%28,%29,%30,%31},{%32,%33,%34,%35},%36,1,1,1,0;"
                     : ACC8(0), ACC8(8), ACC8(16), ACC8(24) : "r"(a[0]), "r"(a[1]), "r"(a[2]), "r"(a[3]), "l"(desc));
    else
        asm volatile("wgmma.mma_async.sync.aligned.m64n64k16.f32.bf16.bf16 "
                     "{%0,%1,%2,%3,%4,%5,%6,%7,%8,%9,%10,%11,%12,%13,%14,%15,%16,%17,%18,%19,%20,%21,%22,%23,%24,%25,%26,%27,%28,%29,%30,%31},{%32,%33,%34,%35},%36,0,1,1,0;"
                     : OUT8(0), OUT8(8), OUT8(16), OUT8(24) : "r"(a[0]), "r"(a[1]), "r"(a[2]), "r"(a[3]), "l"(desc));
}
template <int ACC> __device__ __forceinline__ void wgmma_p2(float (&d)[4], const uint32_t* a, uint64_t desc) {
    if (ACC)
        asm volatile("wgmma.mma_async.sync.aligned.m64n8k16.f32.bf16.bf16 {%0,%1,%2,%3},{%4,%5,%6,%7},%8,1,1,1,0;"
                     : "+f"(d[0]), "+f"(d[1]), "+f"(d[2]), "+f"(d[3]) : "r"(a[0]), "r"(a[1]), "r"(a[2]), "r"(a[3]), "l"(desc));
    else
        asm volatile("wgmma.mma_async.sync.aligned.m64n8k16.f32.bf16.bf16 {%0,%1,%2,%3},{%4,%5,%6,%7},%8,0,1,1,0;"
                     : "=f"(d[0]), "=f"(d[1]), "=f"(d[2]), "=f"(d[3]) : "r"(a[0]), "r"(a[1]), "r"(a[2]), "r"(a[3]), "l"(desc));
}
__device__ __forceinline__ uint64_t desc_tab(uint32_t a) { return (uint64_t)((a & 0x3FFFF) >> 4) | ((uint64_t)(768 >> 4) << 16) | ((uint64_t)(128 >> 4) << 32); }

__device__ __forceinline__ void staged(uint32_t bar, int lane) {
    fence_async_s();
    __syncwarp();
    if (lane == 0) mbar_arrive(bar);
}

__device__ __forceinline__ void wgen(uint32_t win, uint32_t tab, uint32_t out, int c, int qq, int lane, uint32_t consumed, uint32_t chain, uint32_t gate, uint32_t cma) {
    uint32_t A[28];
    int mi = lane >> 3, rr = lane & 7;
    int L = 12 * (mi & 1) + c;
#pragma unroll
    for (int s = 0; s < 7; s++) {
        int u = s < 6 ? s / 3 : mi >> 1;
        int tap = s < 6 ? 16 * (s % 3) + 8 * (mi >> 1) + rr : 48;
        int line = 3 * tap + (L >> 3);
        uint32_t ad = win + u * WPIECE + line * 128 + (((L ^ line) & 7) << 4);
        asm volatile("ldmatrix.sync.aligned.m8n8.x4.trans.shared.b16 {%0,%1,%2,%3},[%4];"
                     : "=r"(A[4 * s]), "=r"(A[4 * s + 1]), "=r"(A[4 * s + 2]), "=r"(A[4 * s + 3]) : "r"(ad));
    }
    float d0[24], d1[24];
    uint64_t ds = desc_tab(tab);
    wg_fence();
    wgmma48<0>(d0, A[0], A[1], A[2], A[3], ds);
    wgmma48<0>(d1, A[12], A[13], A[14], A[15], ds);
    wgmma48<1>(d0, A[4], A[5], A[6], A[7], ds + 96);
    wgmma48<1>(d1, A[16], A[17], A[18], A[19], ds + 96);
    wgmma48<1>(d0, A[8], A[9], A[10], A[11], ds + 192);
    wgmma48<1>(d1, A[20], A[21], A[22], A[23], ds + 192);
    wgmma48<1>(d0, A[24], A[25], A[26], A[27], ds + 336);
    wgmma48<1>(d1, A[24], A[25], A[26], A[27], ds + 288);
    wg_commit();
    if (lane == 0) { if (chain) mbar_arrive(chain); mbar_arrive(consumed); }
    mbar_wait(gate);
    const uint32_t tag = ~lds32(cma) >> 31;
    wg_wait<0>();
    pin(d0); pin(d1);
    int g = lane >> 2, q = lane & 3;
    const uint32_t p = out + q * 512 + (8 * (c & 3) + (g ^ (2 * (q ^ qq)))) * 16;
#pragma unroll
    for (int nb = 0; nb < 6; nb++)
        if (nb < 5 || q < 2)
            sts128(p + nb * 2048, pk(d0[4 * nb], d0[4 * nb + 2]), pk(d0[4 * nb + 1], d0[4 * nb + 3]), pk(d1[4 * nb], d1[4 * nb + 2]),
                   tagged(pk(d1[4 * nb + 1], d1[4 * nb + 3]), g == 7, tag));
}

__device__ __forceinline__ void p1_unit(uint32_t blk, uint32_t out, uint32_t cst, int wg, int wq, int lane) {
    int g = lane >> 2, q = lane & 3;
    uint32_t T[20];
#pragma unroll
    for (int v = 0; v < 5; v++) { uint4 x = lds128(cst + C_P1A + (v * 32 + lane) * 16); T[4 * v] = x.x; T[4 * v + 1] = x.y; T[4 * v + 2] = x.z; T[4 * v + 3] = x.w; }
    uint32_t P[6][3][4];
    const uint32_t a0 = blk + g * 512 + (2 * q + (g & 1)) * 64 + ((wq ^ q) << 4), a1 = a0 ^ 64;
    const uint32_t sel0 = (g & 1) ? 0x1054 : 0x5410, sel1 = sel0 + 0x2222;
    uint32_t vv[2][3][2][4];
    auto ldv = [&](int nu) {
        const int ro = (nu == 0 ? 6 : (nu == 1 ? 14 : 0)) * 512;
#pragma unroll
        for (int t = 0; t < 3; t++)
#pragma unroll
            for (int e = 0; e < 2; e++) {
                uint4 x = lds128((e ? a1 : a0) + t * 11264 + ro);
                vv[nu & 1][t][e][0] = x.x; vv[nu & 1][t][e][1] = x.y; vv[nu & 1][t][e][2] = x.z; vv[nu & 1][t][e][3] = x.w;
            }
    };
    ldv(0);
#pragma unroll
    for (int nu = 0; nu < 3; nu++) {
        if (nu < 2) ldv(nu + 1);
        auto& v = vv[nu & 1];
#pragma unroll
        for (int ch = 0; ch < 4; ch++) {
            const uint32_t sel = (ch & 1) ? sel1 : sel0;
            uint32_t b[2][3];
#pragma unroll
            for (int hf = 0; hf < 2; hf++)
#pragma unroll
                for (int t = 0; t < 3; t++) b[hf][t] = __byte_perm(v[t][0][(ch >> 1) + 2 * hf], v[t][1][(ch >> 1) + 2 * hf], sel);
            float d1[4];
            mma16z(d1, T[12], T[13], T[14], T[15], b[0][0], b[1][0]);
#pragma unroll
            for (int hf = 0; hf < 2; hf++) {
                float d0[4];
                mma16z(d0, T[0], T[1], T[2], T[3], b[hf][1], b[hf][2]);
                mma8(d0, T[16], T[17], b[hf][0]);
                mma16(d1, T[4 + 4 * hf], T[5 + 4 * hf], T[6 + 4 * hf], T[7 + 4 * hf], b[hf][1], b[hf][2]);
                P[(ch >> 1) + 2 * hf][nu][ch & 1] = pk(d0[0], d0[1]);
                P[(ch >> 1) + 2 * hf][nu][2 + (ch & 1)] = pk(d0[2], d0[3]);
            }
            P[4 + (ch >> 1)][nu][ch & 1] = pk(d1[0], d1[1]);
            P[4 + (ch >> 1)][nu][2 + (ch & 1)] = pk(d1[2], d1[3]);
        }
#pragma unroll
        for (int pb = 0; pb < 6; pb++) asm volatile("" : "+r"(P[pb][nu][0]), "+r"(P[pb][nu][1]), "+r"(P[pb][nu][2]), "+r"(P[pb][nu][3]));
                if (SPLIT >> nu & 1) region_end(cst + (O_BAR - O_C) + 8 * BC);
    }
    const uint64_t ds = desc_tab(cst + C_P1B);
    float dA[24], dB[24];
    auto issue = [&](int pb) {
        wg_fence();
        if (pb == 4) {
            wgmma48<0>(dA, P[pb][0][0], P[pb][0][1], P[pb][0][2], P[pb][0][3], ds);
            wgmma48<0>(dB, P[pb + 1][0][0], P[pb + 1][0][1], P[pb + 1][0][2], P[pb + 1][0][3], ds);
        } else {
            wgmma48<2>(dA, P[pb][0][0], P[pb][0][1], P[pb][0][2], P[pb][0][3], ds);
            wgmma48<2>(dB, P[pb + 1][0][0], P[pb + 1][0][1], P[pb + 1][0][2], P[pb + 1][0][3], ds);
        }
        wgmma48<1>(dA, P[pb][1][0], P[pb][1][1], P[pb][1][2], P[pb][1][3], ds + 96);
        wgmma48<1>(dB, P[pb + 1][1][0], P[pb + 1][1][1], P[pb + 1][1][2], P[pb + 1][1][3], ds + 96);
        wgmma48<1>(dA, P[pb][2][0], P[pb][2][1], P[pb][2][2], P[pb][2][3], ds + 192);
        wgmma48<1>(dB, P[pb + 1][2][0], P[pb + 1][2][1], P[pb + 1][2][2], P[pb + 1][2][3], ds + 192);
        wg_commit();
    };
    issue(4);
    bar_sync(1 + wg, 128);
    asm volatile("" : "+r"(g), "+r"(q));
    wg_wait<0>(); pin(dA); pin(dB);
    uint32_t o[12][2];
#pragma unroll
    for (int k = 0; k < 12; k++) { const int i = 4 * (k >> 1) + (k & 1); o[k][0] = pkv(dA[i], dA[i + 2]); o[k][1] = pkv(dB[i], dB[i + 2]); }
    issue(0);
    {
        const int sw = (g >> 1) & 1, r0 = 2 * (lds8(cst + (O_PERM - O_C) + (g < 6 ? 8 + (g >> 1) : 1)) * 11 + q) + sw;
        const uint32_t a0 = out + r0 * 128 + ((((4 * sw + wq) ^ r0) & 7) << 4) + 8 * (g & 1);
        const uint32_t m = wq == 3 && (g & 1) ? TAGM : 0, m0 = sw ? m : 0, m1 = m ^ m0;
#pragma unroll
        for (int k = 11; k >= 0; k--) {
            sts64((a0 ^ ((k & 2) * 72 + (k & 1) * 64)) + 1024 * (k >> 2), o[k][0], tagged(o[k][1], (k & 1) ? m1 : m0, TAGX));
            if (k == 8) __syncwarp();
        }
    }
    wg_wait<0>(); pin(dA); pin(dB);
#pragma unroll
    for (int k = 0; k < 12; k++) { const int i = 4 * (k >> 1) + (k & 1); o[k][0] = pkv(dA[i], dA[i + 2]); o[k][1] = pkv(dB[i], dB[i + 2]); }
    issue(2);
    region_end(cst + (O_BAR - O_C) + 8 * BC);
    const int r0 = 2 * (lds8(cst + (O_PERM - O_C) + g) * 11 + q) + (g & 1);
    const uint32_t ao = out + r0 * 128 + ((((4 * (g & 1) + wq) ^ r0) & 7) << 4);
    const uint32_t m = wq == 3 ? TAGM : 0, m0 = (g & 1) ? m : 0, m1 = m ^ m0;
    wg_wait<0>(); pin(dA); pin(dB);
#pragma unroll
    for (int k = 0; k < 12; k++) {
        const int i = 4 * (k >> 1) + (k & 1);
        sts128p((ao ^ ((k & 2) * 72 + (k & 1) * 64)) + 1024 * (k >> 2), o[k][0], o[k][1], pk(dA[i], dA[i + 2]),
                tagged(pk(dB[i], dB[i + 2]), (k & 1) ? m1 : m0, TAGX), k < 8 || q < 3);
    }
}

template <int NB, class F>
__device__ __forceinline__ void p2_step(const uint32_t (&Wf)[48], uint32_t in, uint32_t a0, uint32_t m, uint32_t t, uint32_t bar, int lane, int wg, int s, F meanwhile) {
    float dp[4 * NB], dm[4 * NB];
    const uint32_t lo = ((in & 0x3FFFF) >> 4) | (1u << 16);
    auto desc = [&](int o) { return (uint64_t)(lo + o) | ((uint64_t)(1024 >> 4) << 32) | (1ull << 62); };
    if (NB > 1 && (wg || s > 1)) bar_sync(4 + wg, 256);
    wg_fence();
    wgmma_p2<0>(dp, &Wf[0], desc(0));
    wgmma_p2<0>(dm, &Wf[24], desc(4));
#pragma unroll
    for (int ks = 1; ks < 6; ks++) {
        wgmma_p2<1>(dp, &Wf[4 * ks], desc((ks >> 1) * (8192 >> 4) + (ks & 1) * 2));
        wgmma_p2<1>(dm, &Wf[24 + 4 * ks], desc((ks >> 1) * (8192 >> 4) + (ks & 1) * 2 + 4));
    }
    wg_commit();
    if (NB > 1 && (wg < 2 || s < 6)) asm volatile("bar.arrive %0,256;" ::"r"(wg == 2 ? 4 : 5 + wg) : "memory");
    meanwhile();
    mbar_wait_ph(bar + 8 * (s < 2 ? BD1 + 1 : BDP + 2 * wg + (s & 1)), s >= 2 ? ((s >> 1) & 1) ^ 1 : 0);
    wg_wait<0>();
    pin(dp); pin(dm);
    if (s < 6 && lane == 0) mbar_arrive(bar + 8 * (BPE + s));
    uint32_t v[2 * NB];
#pragma unroll
    for (int nb = 0; nb < NB; nb++) {
        float pr = dp[4 * nb] - dp[4 * nb + 3], pi = dp[4 * nb + 1] + dp[4 * nb + 2];
        float mr = dm[4 * nb] - dm[4 * nb + 3], mi = dm[4 * nb + 1] + dm[4 * nb + 2];
        v[2 * nb] = tagged(pk(pr + mr, pi - mi), m, t);
        v[2 * nb + 1] = tagged(pk(pi + mi, mr - pr), m, t);
        if (nb & 1)
            asm volatile("stmatrix.sync.aligned.m8n8.x4.trans.shared.b16 [%0],{%1,%2,%3,%4};" ::"r"(a0 + (nb - 1) * 1024), "r"(v[2 * nb - 2]), "r"(v[2 * nb - 1]),
                         "r"(v[2 * nb]), "r"(v[2 * nb + 1]) : "memory");
    }
    if (NB == 1) asm volatile("stmatrix.sync.aligned.m8n8.x2.trans.shared.b16 [%0],{%1,%2};" ::"r"(a0), "r"(v[0]), "r"(v[1]) : "memory");
}

__device__ __forceinline__ bool p3_unit(uint32_t blk, uint32_t cst, int wg, int wq, int lane) {
    int g = lane >> 2, q = lane & 3;
    uint32_t T[12];
#pragma unroll
    for (int v = 0; v < 3; v++) { uint4 x = lds128(cst + C_P3 + (v * 32 + lane) * 16); T[4 * v] = x.x; T[4 * v + 1] = x.y; T[4 * v + 2] = x.z; T[4 * v + 3] = x.w; }
    uint32_t ad[3][2];
#pragma unroll
    for (int nu = 0; nu < 3; nu++) {
        const int pos = lds8(cst + (O_PERM - O_C) + min(4 * nu + (g >> 1), 10));
#pragma unroll
        for (int ka = 0; ka < 2; ka++) {
            int r = 2 * (pos * 11 + (ka ? min(8 + q, 10) : q)) + (g & 1);
            ad[nu][ka] = blk + r * 128 + ((((2 * wq) ^ r) & 7) << 4);
        }
    }
    uint32_t o[2][4][4], bad = 0, P[8][3][2];
#pragma unroll
    for (int nu = 0; nu < 3; nu++) {
        uint32_t z[3][2][4];
#pragma unroll
        for (int ka = 0; ka < 3; ka++)
#pragma unroll
            for (int h = 0; h < 2; h++) {
                uint4 x = lds128((ad[nu][ka >> 1] ^ (h << 4)) + (ka & 1) * 1024);
                z[ka][h][0] = x.x; z[ka][h][1] = x.y; z[ka][h][2] = x.z; z[ka][h][3] = x.w;
                if (h) bad |= x.w ^ TAGZ;
            }
#pragma unroll
        for (int ch = 0; ch < 8; ch++) {
            const uint32_t sel = (ch & 1) ? 0x7632 : 0x5410;
            float d[4];
            mma16z(d, T[0], T[1], T[2], T[3], __byte_perm(z[0][0][ch >> 1], z[0][1][ch >> 1], sel), __byte_perm(z[1][0][ch >> 1], z[1][1][ch >> 1], sel));
            mma8(d, T[4], T[5], __byte_perm(z[2][0][ch >> 1], z[2][1][ch >> 1], sel));
            P[ch][nu][0] = pk(d[0], d[1]); P[ch][nu][1] = pk(d[2], d[3]);
        }
    }
    if (bar_any(1 + wg, 128, wq == 3 && (bad & TAGM))) return false;
#pragma unroll
    for (int j = 0; j < 4; j++) {
        float d2[2][2][4];
#pragma unroll
        for (int e = 0; e < 2; e++)
#pragma unroll
            for (int be = 0; be < 2; be++) {
                const int ch = 2 * j + e;
                mma16z(d2[e][be], P[ch][0][0], P[ch][0][1], P[ch][1][0], P[ch][1][1], T[8 + 2 * be], T[9 + 2 * be]);
                mma8(d2[e][be], P[ch][2][0], P[ch][2][1], T[6 + be]);
            }
#pragma unroll
        for (int be = 0; be < 2; be++)
#pragma unroll
            for (int k = 0; k < 4; k++) o[be][k][j] = pk(d2[0][be][k], d2[1][be][k]);
    }
    const int p = 4 * g + q;
    const uint32_t a = blk + p * 64 + ((wq ^ ((p >> 1) & 3)) << 4);
#pragma unroll
    for (int be = 0; be < 2; be++)
#pragma unroll
        for (int k = 0; k < 4; k++)
            sts128(a + (2 * be + (k & 1)) * 4096 + (k >> 1) * 2048, o[be][k][0], o[be][k][1], o[be][k][2], o[be][k][3]);
    return true;
}

template <int Z> __device__ __forceinline__ int s_row(int gr, int st, int cg, int ci, unsigned cm) {
    const int sf = (ci >> 2) & 1, y = 3 * (3 * gr + cg) + ((st ^ sf) << (Z ^ (cm >> 31))), pg = y >> 2;
    const int r = (pg << 14) | ((ci & 1) << 6) | ((ci & 2) << 8) | ((y & 1) << 10) | ((y & 2) << 11);
    return r | ((((Z ? st : sf) ^ ci ^ (ci >> 1) ^ y ^ (y >> 1) ^ (cm >> pg)) & 1) << 5);
}
__device__ __forceinline__ int w_row(int fw, int hg, int cg, int io, unsigned cm) {
    const int home = fw == 5 ? hg >> 1 : fw > 5;
    const int col = fw == 5 ? 15 + (hg & 1) : 3 * (fw > 5 ? fw - 6 : fw) + hg;
    const int z = 9 * col + 3 * cg + io, pg = NPS + (z >> 5);
    const int r = (pg << 12) | ((z & 1) << 4) | ((z & 6) << 6) | ((z & 24) << 7);
    return r | (((home ^ __popc(z & 15) ^ (cm >> pg)) & 1) << 3);
}
__device__ __forceinline__ int s_tile(int t) { return ((t & 3) << 7) | ((t & 4) << 9) | ((t & 8) << 10); }
__device__ __forceinline__ int xoff(int r) { return r < 3 ? O_B0 + r * BLK : (r == 3 ? O_B4 : O_B3); }
__device__ __forceinline__ int soff(int r) { return r == 2 ? O_B2 + 2048 : xoff(r); }
__device__ __forceinline__ int zoff(int r) { return r == 0 ? O_B2 + 2048 : (r == 1 ? O_B3 : (r == 2 ? O_B4 : (r == 3 ? O_Z3 : O_Z4))); }

struct Role1 {
    int sd, k, nu;
    __device__ __forceinline__ Role1(int cta) { sd = cta >= NH; k = cta - sd * NH; nu = k < NUH - 4 * NH ? 5 : 4; }
};
struct Role {
    int sd, k, fp, nu;
    __device__ __forceinline__ Role(int rho) {
        sd = rho >= NH;
        const int kk = sd ? NCTA - 1 - rho : rho;
        k = NH - 1 - kk;
        nu = k < NUH - 4 * NH ? 5 : 4;
        fp = k >= 5 + sd ? 60 * sd + k - 5 : -1;
    }
};
__device__ __forceinline__ int stage_row(const Role& R, int s, int lane, unsigned cm, int z) {
    const int ci = R.fp > 0 ? (R.fp - 1) / 15 : 0, rw = 2 * (ci ? R.fp - 15 * ci - 1 : R.fp);
    return (z ? s_row<1>(s, lane & 1, lane >> 1, ci, cm) : s_row<0>(s, lane & 1, lane >> 1, ci, cm)) + rw + (s ? 0 : s_tile(14));
}
__device__ __forceinline__ int stage_off(int s, int lane) { return (lane >> 1) * 8192 + (lane & 1) * (s ? 4096 : 512); }
template <int Z, class RT> __device__ __forceinline__ int unit_row(const RT& R, int r, int lane, unsigned cm) {
    const int u = r * NH + R.k, ts = u / 3;
    return s_row<Z>((ts + 14) >> 4, R.sd, u - 3 * ts, lane, cm) + s_tile(ts + 14);
}
__device__ __forceinline__ int unit_off(int lane) { return lane ? 3840 * lane + 256 : 0; }

__global__ void __launch_bounds__(512, 1) fftconv_kernel(const __grid_constant__ Maps mp) {
    extern __shared__ __align__(1024) unsigned char smraw[];
    const uint32_t sm = s2u(smraw);
    const uint32_t bar = sm + O_BAR;
    const int tid = threadIdx.x, lane = tid & 31;
    const uint32_t tstart = clock();
    int xc = 0, xw = 0, xh = 0, xp = -1;
    uint32_t xd = 0;
    const CUtensorMap* xm = nullptr;
    if (tid >= 384 && tid < 416) {
        const int c = blockIdx.x;
        if (elect()) {
            const int ip = c % 12, pr = 3 * (8 * (ip >> 1) + 2 * (ip & 1));
#pragma unroll
            for (int i = 0; i < 8; i++) mbar_init(bar + 8 * i, 1);
            mbar_expect(bar + 8 * BW, 2 * 18816 + WT_BYTES);
            TR(3, 18);
            tma_ld3(sm + O_W0, &mp.w, bar + 8 * BW, 0, pr, 0);
            tma_ld3(sm + O_W0 + WPIECE, &mp.w, bar + 8 * BW, 0, pr + 12, 0);
            bulk_ld(sm + O_WT, mp.wtab + (c / 12) * WT_BYTES, WT_BYTES, bar + 8 * BW);
            if (W1AT < 0) {
                mbar_expect(bar + 8 * (BW + 1), 2 * 18816);
                tma_ld3(sm + O_W1, &mp.w, bar + 8 * (BW + 1), 0, pr + 3, 0);
                tma_ld3(sm + O_W1 + WPIECE, &mp.w, bar + 8 * (BW + 1), 0, pr + 15, 0);
            }
            mbar_expect(bar + 8 * BC, C_BYTES);
            bulk_ld(sm + O_C, mp.ctab, C_BYTES, bar + 8 * BC);
            TR(3, 19);
        }
        __syncwarp();
        asm volatile("bar.arrive 9,512;\n bar.arrive 0,384;" ::: "memory");
        const Role1 X(c);
        if (lane < 3 + X.nu && lane >= (W1AT < 0 ? BX : BW + 1)) mbar_expect(bar + 8 * lane, lane >= BX ? BLK : 2 * 18816);
        const int p = lane & 15, top = lane >> 4, r = p / 3, t = p - 3 * r;
        const int u = r * NH + X.k, ts = u / 3, tr = ts / 14, th = 7 * X.sd + tr, tw = ts - 14 * tr;
        xc = 32 * (u - 3 * ts) + (r << 8);
        xw = t || tw ? 16 * tw - 8 + 8 * t : 216;
        xh = th ? 16 * th - 6 : (top ? 218 : 0);
        xd = sm + xoff(r) + t * 11264 + (th || top ? 0 : 3072);
        xm = th ? &mp.x22 : (top ? &mp.x6 : &mp.x16);
        xp = top && th ? -1 : p;
        __syncwarp();
        if (xp >= 0 && xp < X0N) tma_ld3(xd, xm, bar + 8 * BX + (xc >> 8) * 8, xc & 255, xw, xh);
        __syncwarp();
        TR(3, 20);
    }
    if (tid < 128) {
        const int c = blockIdx.x, vp = min(c & 31, NPAGE - 2);
        const int r0 = 94 + (c & 1) + ((c >> 1) << 7);
        const int r1 = ((vp + 1) << 14) + 94 + ((c >> 5) & 1) + ((c >> 6) << 7) + (vp < NPS - 1 ? 0 : ((0xA151 >> (5 * (vp - NPS + 1))) & 31) << 9);
        unsigned* a = reinterpret_cast<unsigned*>(mp.s) + ((tid & 64 ? r1 : r0) + (tid & 32)) * 32 + lane;
        const bool on = tid < 64 || (c & 31) < NPAGE - 1;
        if (on) *a = 0;
        bar_sync(10, 128);
        TR(5, 18);
        unsigned t = 0;
        if (on) asm volatile("{.reg .u32 v; .reg .pred p;\n atom.relaxed.gpu.global.exch.b32 v,[%1],1;\n setp.eq.u32 p,v,0;\n @p mov.u32 %0,%%clock;}" : "+r"(t) : "l"(a) : "memory");
        if (lane == 0) sts32(sm + O_PT + (tid >> 3), t);
        bar_sync(10, 128);
        const uint4 tt = lds128(sm + O_PT);
        const int far = (((int)(tt.x - tt.y) > 0) ^ __popc(r0 & 0x1640)) & 1;
        TR(5, 19);
        if (lane == 0 && (tid == 32 || (tid == 64 && on))) {
            const int i = tid == 32 ? 20 + c / 12 : vp, v = tid == 32 ? far : (far ^ ((int)(tt.z - tt.w) > 0) ^ __popc(r1 & 0x1640)) & 1;
            red_add(mp.cnt + 64 * (CV + (i & 7)), 1u << ((i & 24) + 4 * v));
        }
        if (tid == 0) sts32(sm + O_ROLE, far);
        __syncwarp();
        bar_sync(9, 512);
        if (tid == 0) mbar_arrive(bar + 8 * (BRL + 1));
        __syncwarp();
    }
    const int warp = __shfl_sync(0xffffffffu, tid >> 5, 0);
    int cta;
    asm volatile("mov.u32 %0,%%ctaid.x;" : "=r"(cta));
    const int wip = cta % 12;
    const Role1 X(cta);
    if (warp == 12) bar_sync(11, 384);
    else if (warp >= 4) {
        if (elect()) {
            const int gi = warp - 3, cnt = gi < 8 ? 1 : (gi == 8 ? 12 : 4);
#pragma unroll
            for (int i = 0; i < 8; i++) mbar_init(bar + 64 * gi + 8 * i, cnt);
            if (warp == 13) {
#pragma unroll
                for (int i = 0; i < 8; i++) mbar_init(bar + 64 * 9 + 8 * i, 4);
            }
        }
        __syncwarp();
        if (lane == 0) TRL(7, 4 + warp);
        asm volatile("bar.arrive 9,512;\n bar.arrive 11,384;" ::: "memory");
        bar_sync(0, 384);
        if (warp == 14) TR(7, 3);
        if (PFW & 1) {
            const int t = tid - 224;
            if (t >= 97 && t < 106) asm volatile("prefetch.tensormap [%0];" ::"l"(&mp.w + (t - 96)) : "memory");
        }
    }

    if (warp >= 12) {
        asm volatile("setmaxnreg.dec.sync.aligned.u32 32;");
        if (warp == 12) {
            auto load_w = [&](int j) {
                if (lane < 2) tma_ld3(sm + (j ? O_W1 : O_W0) + lane * WPIECE, &mp.w, bar + 8 * (BW + j), 0, 3 * (8 * (wip >> 1) + 2 * (wip & 1) + 4 * lane + j), 0);
                __syncwarp();
            };
            TR(7, 4);
            uint32_t due = tstart + XD0;
#pragma unroll 1
            for (int i = X0N; i < 3 * X.nu; i++) {
                if (W1AT >= 0 && i == max(W1AT, X0N)) load_w(1);
                if (i == 9 || i == 12) mbar_wait(bar + 8 * (i == 9 ? BWC + 1 : BDW));
                until(due, 0);
                due += XD;
                if (xp == i) tma_ld3(xd, xm, bar + 8 * BX + (xc >> 8) * 8, xc & 255, xw, xh);
                __syncwarp();
                if (i % 3 == 2) TR(3, 21 + i / 3);
            }
        } else if (warp == 13) {
            mbar_wait(bar + 8 * (BRL + 1));
            if (lane == 0) {
                const unsigned far = lds32(sm + O_ROLE), t = atomicAdd(mp.cnt + 64 * (CT + far), 1u);
                sts32(sm + O_ROLE, far ? NCTA - 1 - t : t);
                mbar_arrive(bar + 8 * BRL);
            }
            __syncwarp();
            TR(5, 20);
        } else if (warp == 14) {
            TR(7, 5);
            unsigned vote = 0;
            until(tstart + VT, 0);
            for (int it = 0; __any_sync(0xffffffffu, lane < 31 && (vote & 15) + (vote >> 4) < (lane < 4 ? 5u : (lane < 20 ? 4u : 12u))) && it < (1 << 16); it++)
                asm volatile("ld.acquire.gpu.global.u8 %0,[%1];" : "=r"(vote) : "l"(reinterpret_cast<unsigned char*>(mp.cnt + 64 * (CV + (lane & 7))) + (lane >> 3)) : "memory");
            const unsigned cm = (__ballot_sync(0xffffffffu, lane < 20 && (vote >> 4) > (vote & 15)) << 1) | __ballot_sync(0xffffffffu, lane == 31 && vote);
            const unsigned gm = 0x7ff00000u, lo = __ballot_sync(0xffffffffu, vote < 64) & gm, hi = __ballot_sync(0xffffffffu, vote >= 144) & gm, mid = gm ^ lo ^ hi;
            const unsigned below = (1u << lane) - 1;
            const int pos = vote < 64 ? __popc(lo & below) : (vote < 144 ? __popc(lo) + __popc(mid & below) : 11 - __popc(hi) + __popc(hi & below));
            if (lane >= 20 && lane < 31) asm volatile("st.shared.u8 [%0],%1;" ::"r"(sm + O_PERM + lane - 20), "r"(pos) : "memory");
            __syncwarp();
            if (lane == 0) { sts32(sm + O_CM, cm); mbar_arrive(bar + 8 * BCM); }
            __syncwarp();
            TR(5, 22);
        }
        auto role = [&]() { mbar_wait(bar + 8 * BRL); return Role(bcast(lds32(sm + O_ROLE), 0)); };

        if (warp == 12) {
            const Role R = role();
            if (R.fp >= 0) {
                mbar_wait(bar + 8 * BCM);
                const unsigned cm = lds32(sm + O_CM);
                if (lane < 7) mbar_expect(bar + 8 * (BPF + lane), lane ? STG : 3072);
                mbar_wait(bar + 8 * (BIS + 2));
                const int v0 = stage_row(R, lane >> 3, lane & 7, cm, 0), v1 = stage_row(R, 4 + (lane >> 3), lane & 7, cm, 0);
                uint32_t dst = sm + O_IN, seen = 0;
#pragma unroll 1
                for (int s = 0; s < 7; s++) {
                    int row[6];
#pragma unroll
                    for (int i = 0; i < 6; i++) row[i] = bcast(s < 4 ? v0 : v1, 8 * s + i);
                    const CUtensorMap* m = s ? &mp.p16 : &mp.p2;
                    const uint32_t hs = s ? 4096 : 512;
                    for (int it = 0; !(seen >> s & 1) && it < (1 << 16); it++) {
                        unsigned v = 0;
                        if (lane == s || (s >= WIN && lane > s && lane < 7)) asm volatile("ld.acquire.gpu.global.u32 %0,[%1];" : "=r"(v) : "l"(mp.cnt + 64 * (CX + lane)) : "memory");
                        seen = __ballot_sync(0xffffffffu, v >= (lane ? 96u : 12u));
                    }
                    TR(5, s);
                    mbar_wait(bar + 8 * (s >= 3 ? BPE + s - 3 : BWE + s));
                    if (elect()) {
#pragma unroll
                        for (int i = 0; i < 6; i++) tma_ld5(dst + (i >> 1) * 8192 + (i & 1) * hs, m, bar + 8 * (BPF + s), 0, row[i], 0, 0, 0);
                    }
                    __syncwarp();
                    dst = dst == sm + O_IN + 2 * STG ? sm + O_IN : dst + STG;
                    TR(3, 3 + s);
                }
            }
        } else if (warp == 13) {
            const Role R = role();
            mbar_wait(bar + 8 * BCM);
            if (R.fp >= 0) {
                const unsigned cm = lds32(sm + O_CM);
                if (lane < 3) mbar_expect(bar + 8 * (BWF + lane), STG);
                const int fw = R.fp / 11;
                {
                    const int fh = R.fp - 11 * fw, b = lane / 3, io = lane - 3 * b;
                    const int row = w_row(fw, fh >> 2, b ? b - 1 : 2, io, cm) + 2 * (fh & 3);
                    mbar_wait(bar + 8 * (BDW + 1));
                    poll(mp.cnt + 64 * (CW + fw), 12);
                    TR(3, 17);
                    const uint32_t t0 = clock();
#pragma unroll 1
                    for (int i = 0; i < 9; i++) {
                        if (i == 6) mbar_wait(bar + 8 * BD1);
                        until(t0 + i * LPW, NAP);
                        if (lane == i) tma_ld4(sm + O_IN + lane * 8192, &mp.wf, bar + 8 * (BWF + b), 0, row, 0, 0);
                        __syncwarp();
                    }
                    TR(3, 15);
                }
            }
            if (lane < R.nu) mbar_expect(bar + 8 * (BZ + lane), SLAB);
            const int v = unit_row<1>(R, lane >> 1, 4 * (lane & 1), lds32(sm + O_CM));
            mbar_wait(bar + 8 * (BD1 + X.nu - 2)); mbar_wait(bar + 8 * (BD1 + X.nu - 1));
#pragma unroll 1
            for (int r = 0; r < R.nu; r++) {
                const int r0 = bcast(v, 2 * r), r1 = bcast(v, 2 * r + 1), gr = (r * NH + R.k + 42) / 48;
                const uint32_t dst = sm + zoff(r), fb = bar + 8 * (BZ + r);
                if (R.fp >= 0) {
                    if (r >= 3) { mbar_wait(bar + 8 * (r == 3 ? BPE + 4 : BD2)); mbar_wait(bar + 8 * (r == 3 ? BPE + 5 : BD2 + 1)); }
                    mbar_wait(bar + 8 * (BI2 + gr));
                }
                poll(mp.cnt + 64 * (CY + gr), NFP);
                TR(5, 8 + r);
                if (elect()) {
#pragma unroll
                    for (int i = 0; i < 8; i++)
                        tma_ld2(dst + unit_off(i), i ? &mp.s30 : &mp.s32, fb, 0, (i < 4 ? r0 : r1) ^ (((i & 1) * 96) ^ ((i & 2) * 272)));
                }
                __syncwarp();
                TR(3, 10 + r);
            }
            if (R.fp >= 0) mbar_wait(bar + 8 * (BPF + 6));
            unsigned last = 0;
            if (lane == 0) last = atomicAdd(mp.cnt + 64 * CD, 1u) == NCTA - 1;
            if (__shfl_sync(0xffffffffu, last, 0)) {
                mp.cnt[64 * lane] = 0;
                if (lane < 8) mp.cnt[64 * (CV + lane)] = lane == 7 ? ((lds32(sm + O_CM) >> 31) ^ 1) << 24 : 0;
            }
        } else {
            const int me = warp & 1;
            uint32_t next = tstart + T0;
            auto pace = [&](int cost) {
                const uint32_t now = until(next, NAP);
                next = ((int)(now - next) > CREDIT ? now - CREDIT : next) + cost;
            };
            const int bal = X.nu == 5 ? 236 : 275;
            mbar_wait(bar + 8 * BCM);
            const unsigned cm = __shfl_sync(0xffffffffu, lds32(sm + O_CM), 0);
            {
                const int iq = 2 * wip + me, w = lane / 3, hg = lane - 3 * w, wfw = lds8(sm + O_PERM + cta / 12);
                unsigned char* dst = mp.s + (size_t)w_row(wfw, hg, w, iq >> 3, cm) * 512 + ((iq & 3) << 14) + ((iq & 4) << 16);
                const uint32_t src = sm + (me ? O_W0 : O_B3) + w * 11264 + hg * 4096;
                fence_async_g();
                if (me) { mbar_wait(bar + 8 * BIS); next = lds32(sm + O_NEXT); }
#pragma unroll 1
                for (int i = 0; i < 3; i++) {
                    mbar_wait(bar + 8 * (BRW + 3 * me + i));
                    if (i == 0) TR(4, me);
                    pace((RW * 11 / 4 * bal) >> 8);
                    if (w == i) bulk_st(dst, src, hg < 2 ? 4096 : 3072);
                    __syncwarp();
                }
                if (lane == 0) { sts32(sm + O_NEXT, next); mbar_arrive(bar + 8 * (BIS + me)); if (EARLY == 2 - me) red_add(mp.cnt + 64 * (CW + wfw)); }
                bulk_commit(); bulk_wait<0>();
                __syncwarp();
                if (lane == 0) { if (me && EARLY == 0) red_add(mp.cnt + 64 * (CW + wfw)); mbar_arrive(bar + 8 * (BDW + me)); }
                TR(6, me);
            }
#pragma unroll 1
            for (int j = me; j < X.nu; j += 2) {
                const int row = unit_row<0>(X, j, lane, cm);
                const uint32_t src = sm + soff(j) + unit_off(lane);
                unsigned* cn = mp.cnt + 64 * (CX + (j * NH + X.k + 42) / 48);
                mbar_wait(bar + 8 * (BR1 + j));
                mbar_wait(bar + 8 * (BIS + 1 + j));
                next = lds32(sm + O_NEXT);
                if (EARLY == 2 && lane == 0) red_add(cn);
                TR(4, 2 + j);
#pragma unroll 1
                for (int i = 0; i < 4; i++) {
                    pace((R1 * 121 / 64 * bal) >> 8);
                    if ((lane & 27) == i) tma_st2(lane == 0 || (lane == 4 && !X.sd) ? &mp.s32 : &mp.s30, src, 0, row);
                    __syncwarp();
                }
                if (lane == 0) { sts32(sm + O_NEXT, next); mbar_arrive(bar + 8 * (BIS + 2 + j)); if (EARLY == 1) red_add(cn); }
                bulk_commit(); bulk_wait_read<0>();
                __syncwarp();
                if (lane == 0) { if (EARLY == 0) red_add(cn); mbar_arrive(bar + 8 * (BD1 + j)); }
                TR(6, j + 2);
                __syncwarp();
            }
            const Role R = role();
            if (R.fp >= 0) {
                const int first = (X.nu ^ me) & 1;
                int v, vx;
                { const int n = first + (lane & 30), s = n / 3, l = 2 * (n - 3 * s) + (lane & 1); v = stage_row(R, s, l, cm, 1); vx = stage_row(R, s, l, cm, 0); }
                mbar_wait(bar + 8 * (BIS + 1 + X.nu));
                next = lds32(sm + O_NEXT) + (first ^ 1) * 2 * R2;
                uint32_t prev = 0;
                int s = 0, w = first;
#pragma unroll 1
                for (int i = 0; s < 7; i += 2) {
                    const int r0 = bcast(v, i), r1 = bcast(v, i + 1), rx = bcast(vx, i + 1);
                    const int bi = 2 * w + (s & 1);
                    const uint32_t src = sm + O_OUT + (s & 1) * STG + w * 8192, hs = s ? 4096 : 512;
                    const CUtensorMap* m = s ? &mp.p16 : &mp.p2;
                    mbar_wait_ph(bar + 8 * (BR2 + bi), (s >> 1) & 1);
                    if (s) {
                        const uint32_t now = until(next, NAP);
                        next = ((int)(now - next) > CREDIT2 ? now - CREDIT2 : next) + 4 * R2;
                    }
                    if (elect()) {
                        tma_st5(m, src, 0, r0, 0, 0, 0);
                        tma_st5(m, src + hs, 0, r1, 0, 0, 0);
                        if (R.fp == 15) tma_st5(m, src + hs, 0, rx, 0, 0, 0);
                        bulk_commit();
                        bulk_wait_read<1>();
                        if (prev) mbar_arrive(prev);
                        if (w == 2) { if (LATE2) bulk_wait_read<0>(); red_add(mp.cnt + 64 * (CY + s)); mbar_arrive(bar + 8 * (BI2 + s)); }
                    }
                    __syncwarp();
                    if (w != 1) TR(4 + w, 7 + s);
                    prev = bar + 8 * (BDP + bi);
                    w += 2; if (w > 2) { w -= 3; s++; }
                }
                if (elect()) { bulk_wait_read<0>(); mbar_arrive(bar + 8 * (BD2 + me)); }
                __syncwarp();
                next = clock();
            }
#pragma unroll 1
            for (int r = me; r < R.nu; r += 2) {
                const int u = r * NH + R.k, ts = u / 3, cg = u - 3 * ts, tr = ts / 14, th = 7 * R.sd + tr, tw = ts - 14 * tr;
                mbar_wait(bar + 8 * (BR3 + r));
                if (r && r < 3) { mbar_wait(bar + 8 * (BIS + 6 + r)); next = lds32(sm + O_NEXT); }
                TR(4, 14 + r);
#pragma unroll 1
                for (int c = 0; c < 2; c++) {
                    if (r < 3) pace(2 * R3);
                    if (elect()) tma_st4(&mp.y, sm + zoff(r) + c * 8192, 32 * cg, 0, 16 * th, 4 * tw + 2 * c);
                    __syncwarp();
                }
                if (lane == 0) { sts32(sm + O_NEXT, next); mbar_arrive(bar + 8 * (BIS + 7 + r)); }
                __syncwarp();
            }
            bulk_commit(); bulk_wait_read<0>();
            TR(4, 19 + me);
        }
    } else {
        asm volatile("setmaxnreg.inc.sync.aligned.u32 160;");
        const int lane = laneid();
        const int wg = __shfl_sync(0xffffffffu, tid >> 7, 0), wq = __shfl_sync(0xffffffffu, tid >> 5, 0) & 3;
#pragma unroll 1
        for (int it = 0; it <= wg; it++) {
            const int j = it > 0, cg = j ? wg + it - 2 : wg;
            mbar_wait(bar + 8 * (j == 0 && wg ? BWL + wg - 1 : BW + j));
            TR(wg, 24 + 2 * it);
            wgen(sm + (j ? O_W1 : O_W0), sm + O_WT, sm + (j ? O_W0 : O_B3) + cg * 11264, 4 * cg + wq, (2 * wip + j) & 3, lane, bar + 8 * (BWC + j),
                 j == 0 && wg < 2 ? bar + 8 * (BWL + wg) : 0, bar + 8 * (j ? BWC : BCM), sm + O_CM);
            staged(bar + 8 * (BRW + 3 * j + cg), lane);
            TR(wg, 25 + 2 * it);
        }
        mbar_wait(bar + 8 * BC);
#pragma unroll 1
        for (int r = wg; r < X.nu; r += 3) {
            mbar_wait(bar + 8 * (BX + r));
            TR(wg, 1 + 2 * (r / 3));
            p1_unit(sm + xoff(r), sm + soff(r), sm + O_C, wg, wq, laneid());
            staged(bar + 8 * (BR1 + r), laneid());
            TR(wg, 2 + 2 * (r / 3));
        }
        mbar_wait(bar + 8 * BRL);
        const Role R(__shfl_sync(0xffffffffu, lds32(sm + O_ROLE), 0));
        uint32_t phw = 0;
        if (R.fp >= 0) {
            const int lane = laneid();
            uint32_t Wf[48];
            const int g = lane >> 2, q = lane & 3;
            {
                const int b = wg == 2 ? 0 : wg + 1;
                const uint32_t p = sm + O_IN + b * STG + q * 1024 + wq * 128 + ((g ^ (2 * q) ^ (4 * ((R.fp % 11) & 1))) << 4);
                mbar_wait(bar + 8 * (BWF + b));
                TR(wg, 5);
#pragma unroll 1
                for (int it = 0; it < 4096; it++) {
                    const uint32_t tag = ~lds32(sm + O_CM) >> 31, m = g == 7;
                    uint32_t bad = 0;
#pragma unroll
                    for (int i = 0; i < 12; i++) {
                        uint4 v = lds128((p ^ (i >= 6 ? 544 : 0)) + (i % 6) * 4096);
                        Wf[4 * i] = v.x; Wf[4 * i + 1] = v.y; Wf[4 * i + 2] = v.z; Wf[4 * i + 3] = v.w & ~m;
                        bad |= v.w ^ tag;
                    }
                    if (!bar_any(1 + wg, 128, bad & m)) break;
                    if (wq == 0) {
                        TRC(2);
                        fence_async_s();
                        if (lane == 0) mbar_expect(bar + 8 * (BRT + 1 + wg), STG);
                        __syncwarp();
                        const int l = laneid(), fp = Role(lds32(sm + O_ROLE)).fp, fw = fp / 11, fh = fp - 11 * fw;
                        if (l < 3) tma_ld4(sm + O_IN + b * STG + l * 8192, &mp.wf, bar + 8 * (BRT + 1 + wg), 0, w_row(fw, fh >> 2, wg, l, lds32(sm + O_CM)) + 2 * (fh & 3), 0, 0);
                        __syncwarp();
                    }
                    mbar_wait_ph(bar + 8 * (BRT + 1 + wg), phw); phw ^= 1;
                }
                staged(bar + 8 * (BWE + b), lane);
            }
            const int ro = (lane & 6) + ((lane >> 3) & 1);
            const uint32_t o0 = sm + O_OUT + wg * 8192 + (lane >> 4) * 1024 + ro * 128 + (((2 * wq + (lane & 1)) ^ ro) << 4);
            const uint32_t m = wq == 3 && g >= 6 ? 0x10000 : 0, tg = g == 6 ? TAGZ << 16 : TAGZ;
            uint32_t ph = 0;
            const int t = 32 * wq + lane;
            uint32_t c0 = t * 128 + ((7 ^ (t & 7)) << 4) + 12, c1 = (c0 & 8191) + 16384;
            auto stale = [&](uint32_t in) { return (((lds32(in + c0) ^ TAGX) | (lds32(in + c1) ^ TAGX)) & TAGM) != 0; };
            auto landed = [&](int s, uint32_t in) {
                mbar_wait(bar + 8 * (BPF + s));
#pragma unroll 1
                for (int it = 0; it < 4096; it++) {
                    if (!bar_any(1 + wg, 128, stale(in))) break;
                    fence_async_s();
                    bar_sync(7, 384);
                    if (wg + wq == 0) {
                        TRC(0);
                        if (lane == 0) mbar_expect(bar + 8 * BRT, s ? STG : 3072);
                        __syncwarp();
                        const int l = laneid();
                        if (l < 6) tma_ld5(in + stage_off(s, l), s ? &mp.p16 : &mp.p2, bar + 8 * BRT, 0, stage_row(Role(lds32(sm + O_ROLE)), s, l, lds32(sm + O_CM), 0), 0, 0, 0);
                        __syncwarp();
                    }
                    mbar_wait_ph(bar + 8 * BRT, ph); ph ^= 1;
                }
            };
            mbar_wait(bar + 8 * BD1);
            c0 &= 8192 + 1023; c1 &= 16384 + 1023;
            landed(0, sm + O_IN);
            p2_step<1>(Wf, sm + O_IN, o0, m, tg, bar, lane, wg, 0, []() {});
            staged(bar + 8 * (BR2 + 2 * wg), lane);
            TR(wg, 6);
            c0 |= (t & 56) << 7; c1 |= (t & 56) << 7;
            uint32_t in = sm + O_IN + STG;
            bool todo = true;
#pragma unroll 1
            for (int s = 1; s < 7; s++) {
                if (todo) landed(s, in);
                const uint32_t nx = in == sm + O_IN + 2 * STG ? sm + O_IN : in + STG;
                p2_step<8>(Wf, in, o0 + (s & 1) * STG, m, tg, bar, lane, wg, s, [&]() { todo = !mbar_test(bar + 8 * (BPF + s + 1)) || stale(nx); });
                todo = bar_any(1 + wg, 128, todo);
                in = nx;
                staged(bar + 8 * (BR2 + 2 * wg + (s & 1)), lane);
                TR(wg, 6 + s);
            }
        }
#pragma unroll 1
        for (int r = wg; r < R.nu; r += 3) {
            mbar_wait(bar + 8 * (BZ + r));
            TR(wg, 13 + 2 * (r / 3));
#pragma unroll 1
            for (int it = 0; it < 4096; it++) {
                if (p3_unit(sm + zoff(r), sm + O_C, wg, wq, laneid())) break;
                if (wq == 0) {
                    TRC(1);
                    fence_async_s();
                    if (laneid() == 0) mbar_expect(bar + 8 * (BRT + 1 + wg), SLAB);
                    __syncwarp();
                    const int l = laneid();
                    if (l < 8) tma_ld2(sm + zoff(r) + unit_off(l), l ? &mp.s30 : &mp.s32, bar + 8 * (BRT + 1 + wg), 0, unit_row<1>(Role(lds32(sm + O_ROLE)), r, l, lds32(sm + O_CM)));
                    __syncwarp();
                }
                mbar_wait_ph(bar + 8 * (BRT + 1 + wg), phw); phw ^= 1;
            }
            staged(bar + 8 * (BR3 + r), laneid());
            TR(wg, 14 + 2 * (r / 3));
        }
    }
}

typedef CUresult (*EncFn)(CUtensorMap*, CUtensorMapDataType, cuuint32_t, void*, const cuuint64_t*, const cuuint64_t*, const cuuint32_t*,
                          const cuuint32_t*, CUtensorMapInterleave, CUtensorMapSwizzle, CUtensorMapL2promotion, CUtensorMapFloatOOBfill);

void enc(EncFn f, CUtensorMap* m, void* p, int rank, const cuuint64_t* dims, const cuuint64_t* strides, const cuuint32_t* box,
         CUtensorMapSwizzle sw, CUtensorMapL2promotion pr = CU_TENSOR_MAP_L2_PROMOTION_NONE) {
    cuuint32_t es[5] = {1, 1, 1, 1, 1};
    f(m, CU_TENSOR_MAP_DATA_TYPE_BFLOAT16, rank, p, dims, strides, box, es, CU_TENSOR_MAP_INTERLEAVE_NONE, sw, pr, CU_TENSOR_MAP_FLOAT_OOB_FILL_NONE);
}

}

extern "C" void kernel_launch(void* const* d_in, const int* in_sizes, int n_in, void* d_out, int out_size) {
    void* fn = nullptr; cudaDriverEntryPointQueryResult qr;
    cudaGetDriverEntryPoint("cuTensorMapEncodeTiled", &fn, cudaEnableDefault, &qr);
    EncFn f = (EncFn)fn;
    void* pS; cudaGetSymbolAddress(&pS, g_S);
    pS = (void*)(((uintptr_t)pS + (1u << 21) - 1) & ~(uintptr_t)((1u << 21) - 1));
    Maps mp;
    cudaGetSymbolAddress((void**)&mp.ctab, g_ctab); cudaGetSymbolAddress((void**)&mp.wtab, g_wtab); cudaGetSymbolAddress((void**)&mp.cnt, g_cnt);
    mp.s = (unsigned char*)pS; mp.x = (const unsigned char*)d_in[0]; mp.wraw = (const unsigned char*)d_in[1];
    { cuuint64_t d[4] = {256, NPAGE << 12, 4, 2}, s[3] = {512, 1 << 14, 1 << 18}; cuuint32_t b[4] = {256, 2, 4, 2}; enc(f, &mp.wf, pS, 4, d, s, b, CU_TENSOR_MAP_SWIZZLE_NONE); }
    {
        cuuint64_t d[3] = {96, 224, 224}, s[2] = {192, 43008};
        cuuint32_t b6[3] = {32, 8, 6}, b16[3] = {32, 8, 16}, b22[3] = {32, 8, 22};
        enc(f, &mp.x22, d_in[0], 3, d, s, b22, CU_TENSOR_MAP_SWIZZLE_64B, CU_TENSOR_MAP_L2_PROMOTION_L2_128B);
        enc(f, &mp.x6, d_in[0], 3, d, s, b6, CU_TENSOR_MAP_SWIZZLE_64B, CU_TENSOR_MAP_L2_PROMOTION_L2_128B);
        enc(f, &mp.x16, d_in[0], 3, d, s, b16, CU_TENSOR_MAP_SWIZZLE_64B, CU_TENSOR_MAP_L2_PROMOTION_L2_128B);
    }
    { cuuint64_t d[4] = {96, 4, 224, 56}, s[3] = {192, 43008, 768}; cuuint32_t b[4] = {32, 4, 16, 2}; enc(f, &mp.y, d_out, 4, d, s, b, CU_TENSOR_MAP_SWIZZLE_64B); }
    {
        cuuint64_t d[2] = {64, NPAGE << 14}, s[1] = {128};
        cuuint32_t b32[2] = {64, 32}, b30[2] = {64, 30};
        enc(f, &mp.s32, pS, 2, d, s, b32, CU_TENSOR_MAP_SWIZZLE_128B);
        enc(f, &mp.s30, pS, 2, d, s, b30, CU_TENSOR_MAP_SWIZZLE_128B);
    }
    {
        cuuint64_t d[5] = {64, NPAGE << 14, 4, 2, 2}, s[4] = {128, 1 << 14, 1 << 18, 1 << 20};
        cuuint32_t b16[5] = {64, 2, 4, 2, 2}, b2[5] = {64, 2, 2, 1, 1};
        enc(f, &mp.p16, pS, 5, d, s, b16, CU_TENSOR_MAP_SWIZZLE_128B);
        enc(f, &mp.p2, pS, 5, d, s, b2, CU_TENSOR_MAP_SWIZZLE_128B);
    }
    { cuuint64_t d[3] = {64, 144, 49}, s[2] = {128, 18432}; cuuint32_t b[3] = {64, 3, 49}; enc(f, &mp.w, d_in[1], 3, d, s, b, CU_TENSOR_MAP_SWIZZLE_128B); }
    cudaFuncSetAttribute(fftconv_kernel, cudaFuncAttributeMaxDynamicSharedMemorySize, SMEM);
    fftconv_kernel<<<NCTA, 512, SMEM>>>(mp);
}
```

```cpp
#include <cuda_runtime.h>
#include <cuda_bf16.h>
#include <cuda.h>
#include <stdint.h>

#define TUNABLES {260, 285, 250, 280, 500, 250, 30, 1, 1600, 600, 1, 2000, 1500, 0, 0, 0, 340, 236, 0, 0}
constexpr int c_tune[24] = TUNABLES;
template <int I> struct TuneV { static constexpr int v = c_tune[I]; };
#define TV(i) TuneV<i>::v
#define RW TV(0)
#define R1 TV(1)
#define R2 TV(2)
#define R3 TV(3)
#define CREDIT TV(4)
#define LPW TV(5)
#define NAP TV(6)
#define EARLY TV(7)
#define T0 0
#define XD TV(9)
#define XD0 TV(8)
#define LATE2 TV(10)
#define PFW 1
#define VT TV(11)
#define CREDIT2 TV(12)
#define W1AT TV(13)
#define X0N TV(14)
#define WIN TV(15)
#define R1A TV(16)
#define BAL TV(17)
#define SPLIT 3

namespace {

constexpr int NCTA = 132, NH = 66;
constexpr int NUH = 294;
constexpr int NFP = 121;
constexpr int BLK = 33792;
constexpr int SLAB = 242 * 128;
constexpr int WPIECE = 19456;
constexpr int STG = 24576;
constexpr int NPS = 16, NPAGE = 21;
constexpr int O_B4 = 0, O_B0 = 87040, O_B2 = O_B0 + 2 * BLK, O_B3 = O_B0 + 3 * BLK;
constexpr int O_W1 = 0, O_W0 = 2 * WPIECE, O_WT = 4 * WPIECE;
constexpr int O_IN = 33792, O_OUT = O_IN + 3 * STG, O_Z3 = O_IN, O_S0 = O_OUT + 4096, O_Z4 = 124928;
constexpr int O_C = 222208, O_BAR = 230912, SMEM = 232448;
constexpr int C_P1A = 0, C_P1B = 2560, C_P3 = 7168, C_BYTES = 8704, WT_BYTES = 6912;
constexpr int BC = 0, BW = 1, BX = 3, BZ = 8, BWF = 13, BPF = 16, BCM = 23, BDW = 24, BD1 = 26, BDP = 31, BD2 = 37, BIS = 39, BI2 = 51, BRT = 58, BRL = 62;
constexpr int BPE = 64, BWC = 70;
constexpr int BR2 = 72, BRW = 78, BWL = 84, BR1 = 86, BR3 = 91, BWE = 96;
constexpr int O_NEXT = O_BAR + 1016, O_ROLE = O_BAR + 1000, O_PT = O_BAR + 976, O_CM = O_BAR + 1008, O_PERM = O_BAR + 944;
constexpr uint32_t TAGM = 0x00010001u, TAGX = 0x00000001u, TAGZ = 0x00010000u;

constexpr uint16_t LUT_A[11] = {0x3f95, 0x3f92, 0x3f8c, 0x3f83, 0x3f6f, 0x3f53, 0x3f33, 0x3f0f, 0x3ed1, 0x3e7e, 0x3daa};
constexpr uint16_t LUT_B[11] = {0x3fe9, 0x3fe4, 0x3fdb, 0x3fcd, 0x3fbb, 0x3fa5, 0x3f8c, 0x3f60, 0x3f23, 0x3ec7, 0x3e05};
constexpr uint16_t LUT_W[12] = {0x3abb, 0x3ab9, 0x3ab3, 0x3aaa, 0x3a9d, 0x3a8d, 0x3a75, 0x3a4a, 0x3a1b, 0x39d3, 0x3955, 0};
constexpr uint16_t basis(int setb, int f, int a, int sn) {
    if (f < 0 || f > 10 || a < 0 || a > 21) return 0;
    int k = ((2 * f + 1) * (2 * a - 21) - 22 * sn + 88 * 7) % 88;
    if (k > 44) k = 88 - k;
    int neg = 0;
    if (k > 22) { k = 44 - k; neg = 1; }
    return (uint16_t)((setb ? LUT_B[k >> 1] : LUT_A[k >> 1]) | (neg << 15));
}
constexpr uint16_t neg16(uint16_t v) { return v ? (uint16_t)(v ^ 0x8000) : v; }
constexpr uint16_t wcoef(int fw, int fl, int sn, int tap) {
    if (fl > 21) return 0;
    int fh = fl >> 1, kh = tap / 7, kw = tap - 7 * kh;
    int u = (2 * fh + 1) * kh;
    if (fl & 1) u = -u;
    int k = (u + (2 * fw + 1) * kw - 11 * sn + 44 * 4) % 44;
    if (k > 22) k = 44 - k;
    int neg = 0;
    if (k > 11) { k = 22 - k; neg = 1; }
    return (uint16_t)(LUT_W[k] | (neg << 15));
}
struct alignas(128) CTab { uint16_t v[C_BYTES / 2]; };
struct alignas(128) WTab { uint16_t v[WT_BYTES / 2]; };
constexpr CTab make_ctab() {
    CTab t{};
    for (int lane = 0; lane < 32; lane++) {
        int g = lane >> 2, q = lane & 3;
        for (int r = 0; r < 18; r++) {
            int quad = r >> 2, j = r & 3;
            int set = quad < 3 ? quad : (quad == 3 ? 1 + (j >> 1) : 0);
            int sn = (j ^ (set == 0 ? g : g >> 1)) & 1;
            int t8 = quad < 3 ? 1 + (j >> 1) : 0;
            int b = 8 * t8 + 2 * q - 2;
            int fw = set == 0 ? g : (((g & 1) == set - 1) ? 8 + (g >> 1) : -1);
            int o = (C_P1A + (quad * 32 + lane) * 16 + j * 4) / 2;
            t.v[o] = basis(0, fw, b, sn); t.v[o + 1] = basis(0, fw, b + 1, sn);
        }
        for (int r = 0; r < 12; r++) {
            int o = (C_P3 + ((r >> 2) * 32 + lane) * 16 + (r & 3) * 4) / 2;
            if (r < 6) {
                int a = 6 + g + 8 * (r & 1), fh = 4 * (r >> 1) + q;
                t.v[o] = basis(0, fh, a, 0); t.v[o + 1] = basis(0, fh, a, 1);
            } else {
                int be = r < 8 ? r - 6 : (r - 8) >> 1, nu = r < 8 ? 2 : (r & 1);
                int b = 6 + 8 * be + 4 * (g & 1) + (g >> 1);
                t.v[o] = basis(1, 4 * nu + q, b, 0); t.v[o + 1] = basis(1, 4 * nu + q, b, 1);
            }
        }
    }
    for (int kc = 0; kc < 6; kc++)
        for (int nb = 0; nb < 6; nb++)
            for (int n = 0; n < 8; n++)
                for (int k = 0; k < 8; k++) {
                    int nu = kc >> 1, ds = kc & 1, im = nb & 1, fh = 4 * (nb >> 1) + (n >> 1), mi = n & 1;
                    int a = nu == 0 ? 6 + k : (nu == 1 ? 14 + k : (k < 6 ? k : -1));
                    uint16_t v = basis(0, fh, a, ds ^ im);
                    if (ds != im && (im ? mi : !mi)) v = neg16(v);
                    t.v[C_P1B / 2 + ((kc * 6 + nb) * 8 + n) * 8 + k] = v;
                }
    return t;
}
constexpr WTab make_wtab(int fw) {
    WTab t{};
    for (int nb = 0; nb < 6; nb++)
        for (int n = 0; n < 8; n++) {
            for (int tap = 0; tap < 48; tap++) t.v[(((tap >> 3) * 6 + nb) * 8 + n) * 8 + (tap & 7)] = wcoef(fw, 4 * nb + (n >> 1), n & 1, tap);
            t.v[((7 * 6 + nb) * 8 + n) * 8] = wcoef(fw, 4 * nb + (n >> 1), n & 1, 48);
        }
    return t;
}
__device__ const CTab g_ctab = make_ctab();
__device__ const WTab g_wtab[11] = {make_wtab(0), make_wtab(1), make_wtab(2), make_wtab(3), make_wtab(4), make_wtab(5),
                                    make_wtab(6), make_wtab(7), make_wtab(8), make_wtab(9), make_wtab(10)};

__device__ __align__(1024) unsigned char g_S[(size_t)(NPAGE + 1) << 21];
constexpr int CT = 0, CX = 2, CY = 10, CW = 18, CD = 29, CV = 32;
__device__ __align__(512) unsigned g_cnt[40 * 64];

struct Maps {
    const unsigned char* ctab; const unsigned char* wtab; const unsigned char* x; unsigned* cnt; unsigned char* s;
    const unsigned char* wraw;
    alignas(64) CUtensorMap w, x22, x6, x16, wf, s32, s30, p16, p2, y;
};

#define TR(role, i)
#define TRL(role, i)
#define TRC(i)

__device__ __forceinline__ uint32_t s2u(const void* p) { return (uint32_t)__cvta_generic_to_shared(p); }
__device__ __forceinline__ void mbar_init(uint32_t b, int c) { asm volatile("mbarrier.init.shared::cta.b64 [%0],%1;" ::"r"(b), "r"(c) : "memory"); }
__device__ __forceinline__ void mbar_expect(uint32_t b, uint32_t tx) { asm volatile("mbarrier.arrive.expect_tx.shared::cta.b64 _,[%0],%1;" ::"r"(b), "r"(tx) : "memory"); }
__device__ __forceinline__ void mbar_arrive(uint32_t b) { asm volatile("mbarrier.arrive.shared::cta.b64 _,[%0];" ::"r"(b) : "memory"); }
__device__ __forceinline__ bool mbar_try(uint32_t b, uint32_t ph) {
    uint32_t ok;
    asm volatile("{.reg .pred p; mbarrier.try_wait.parity.shared::cta.b64 p,[%1],%2; selp.u32 %0,1,0,p;}" : "=r"(ok) : "r"(b), "r"(ph) : "memory");
    return ok;
}
__device__ __forceinline__ void mbar_wait_ph(uint32_t b, uint32_t ph) {
    if (mbar_try(b, ph)) return;
#pragma unroll 1
    for (int it = 0; it < (1 << 16); it++)
        if (mbar_try(b, ph)) return;
}
__device__ __forceinline__ void mbar_wait(uint32_t b) { mbar_wait_ph(b, 0); }
__device__ __forceinline__ void region_end(uint32_t b) {
    int it = 0;
    while (!mbar_try(b, 0) && ++it < (1 << 16)) {}
}
__device__ __forceinline__ bool mbar_test(uint32_t b) {
    uint32_t ok;
    asm volatile("{.reg .pred p; mbarrier.test_wait.parity.shared::cta.b64 p,[%1],0; selp.u32 %0,1,0,p;}" : "=r"(ok) : "r"(b) : "memory");
    return ok;
}
__device__ __forceinline__ bool elect() {
    uint32_t r;
    asm volatile("{.reg .pred p; elect.sync _|p,0xffffffff; selp.u32 %0,1,0,p;}" : "=r"(r));
    return r;
}
__device__ __forceinline__ uint32_t until(uint32_t t, int nap) {
    uint32_t now = clock();
    while ((int)(now - t) < 0) { if (nap) __nanosleep(nap); now = clock(); }
    return now;
}
__device__ __forceinline__ int bcast(int v, int l) { return __shfl_sync(0xffffffffu, v, l); }
__device__ __forceinline__ void poll(const unsigned* c, unsigned tgt) {
    unsigned v; int it = 0;
    do { asm volatile("ld.acquire.gpu.global.u32 %0,[%1];" : "=r"(v) : "l"(c) : "memory"); } while (v < tgt && ++it < (1 << 16));
}
__device__ __forceinline__ bool bar_any(int id, int n, bool v) {
    uint32_t r;
    asm volatile("{.reg .pred p,q; setp.ne.u32 p,%3,0; bar.red.or.pred q,%1,%2,p; selp.u32 %0,1,0,q;}" : "=r"(r) : "r"(id), "r"(n), "r"((uint32_t)v) : "memory");
    return __any_sync(0xffffffffu, r);
}
__device__ __forceinline__ int laneid() { int l; asm volatile("mov.u32 %0,%%laneid;" : "=r"(l)); return l; }
__device__ __forceinline__ uint32_t lds32(uint32_t a) { uint32_t v; asm volatile("ld.shared.u32 %0,[%1];" : "=r"(v) : "r"(a) : "memory"); return v; }
__device__ __forceinline__ uint32_t lds8(uint32_t a) { uint32_t v; asm volatile("ld.shared.u8 %0,[%1];" : "=r"(v) : "r"(a) : "memory"); return v; }
__device__ __forceinline__ uint32_t tagged(uint32_t v, uint32_t m, uint32_t t) { return (v & ~m) | (t & m); }
__device__ __forceinline__ void red_add(unsigned* c, unsigned v = 1) { asm volatile("red.relaxed.gpu.global.add.u32 [%0],%1;" ::"l"(c), "r"(v) : "memory"); }
__device__ __forceinline__ void pf_l2(const void* p) { asm volatile("prefetch.global.L2 [%0];" ::"l"(p)); }
__device__ __forceinline__ void fence_async_s() { asm volatile("fence.proxy.async.shared::cta;" ::: "memory"); }
__device__ __forceinline__ void fence_async_g() { asm volatile("fence.proxy.async.global;" ::: "memory"); }
__device__ __forceinline__ void bulk_ld(uint32_t dst, const void* src, uint32_t bytes, uint32_t bar) {
    asm volatile("cp.async.bulk.shared::cluster.global.mbarrier::complete_tx::bytes [%0],[%1],%2,[%3];" ::"r"(dst), "l"(src), "r"(bytes), "r"(bar) : "memory");
}
__device__ __forceinline__ void tma_ld2(uint32_t dst, const CUtensorMap* m, uint32_t bar, int c0, int c1) {
    asm volatile("cp.async.bulk.tensor.2d.shared::cluster.global.mbarrier::complete_tx::bytes [%0],[%1,{%3,%4}],[%2];" ::"r"(dst), "l"(m), "r"(bar), "r"(c0), "r"(c1) : "memory");
}
__device__ __forceinline__ void tma_ld3(uint32_t dst, const CUtensorMap* m, uint32_t bar, int c0, int c1, int c2) {
    asm volatile("cp.async.bulk.tensor.3d.shared::cluster.global.mbarrier::complete_tx::bytes [%0],[%1,{%3,%4,%5}],[%2];" ::"r"(dst), "l"(m), "r"(bar), "r"(c0), "r"(c1), "r"(c2) : "memory");
}
__device__ __forceinline__ void tma_ld4(uint32_t dst, const CUtensorMap* m, uint32_t bar, int c0, int c1, int c2, int c3) {
    asm volatile("cp.async.bulk.tensor.4d.shared::cluster.global.mbarrier::complete_tx::bytes [%0],[%1,{%3,%4,%5,%6}],[%2];" ::"r"(dst), "l"(m), "r"(bar), "r"(c0), "r"(c1), "r"(c2), "r"(c3) : "memory");
}
__device__ __forceinline__ void bulk_st(void* dst, uint32_t src, uint32_t bytes) {
    asm volatile("cp.async.bulk.global.shared::cta.bulk_group [%0],[%1],%2;" ::"l"(dst), "r"(src), "r"(bytes) : "memory");
}
__device__ __forceinline__ void tma_ld5(uint32_t dst, const CUtensorMap* m, uint32_t bar, int c0, int c1, int c2, int c3, int c4) {
    asm volatile("cp.async.bulk.tensor.5d.shared::cluster.global.mbarrier::complete_tx::bytes [%0],[%1,{%3,%4,%5,%6,%7}],[%2];" ::"r"(dst), "l"(m), "r"(bar), "r"(c0), "r"(c1), "r"(c2), "r"(c3), "r"(c4) : "memory");
}
__device__ __forceinline__ void tma_st2(const CUtensorMap* m, uint32_t src, int c0, int c1) {
    asm volatile("cp.async.bulk.tensor.2d.global.shared::cta.bulk_group [%0,{%2,%3}],[%1];" ::"l"(m), "r"(src), "r"(c0), "r"(c1) : "memory");
}
__device__ __forceinline__ void tma_st4(const CUtensorMap* m, uint32_t src, int c0, int c1, int c2, int c3) {
    asm volatile("cp.async.bulk.tensor.4d.global.shared::cta.bulk_group [%0,{%2,%3,%4,%5}],[%1];" ::"l"(m), "r"(src), "r"(c0), "r"(c1), "r"(c2), "r"(c3) : "memory");
}
__device__ __forceinline__ void tma_st5(const CUtensorMap* m, uint32_t src, int c0, int c1, int c2, int c3, int c4) {
    asm volatile("cp.async.bulk.tensor.5d.global.shared::cta.bulk_group [%0,{%2,%3,%4,%5,%6}],[%1];" ::"l"(m), "r"(src), "r"(c0), "r"(c1), "r"(c2), "r"(c3), "r"(c4) : "memory");
}
__device__ __forceinline__ void bulk_commit() { asm volatile("cp.async.bulk.commit_group;" ::: "memory"); }
template <int N> __device__ __forceinline__ void bulk_wait() { asm volatile("cp.async.bulk.wait_group %0;" ::"n"(N) : "memory"); }
template <int N> __device__ __forceinline__ void bulk_wait_read() { asm volatile("cp.async.bulk.wait_group.read %0;" ::"n"(N) : "memory"); }
__device__ __forceinline__ void bar_sync(int id, int n) { asm volatile("bar.sync %0,%1;" ::"r"(id), "r"(n) : "memory"); }

__device__ __forceinline__ uint4 lds128(uint32_t a) {
    uint4 v; asm volatile("ld.shared.v4.u32 {%0,%1,%2,%3},[%4];" : "=r"(v.x), "=r"(v.y), "=r"(v.z), "=r"(v.w) : "r"(a)); return v;
}
__device__ __forceinline__ void sts128(uint32_t a, uint32_t x, uint32_t y, uint32_t z, uint32_t w) {
    asm volatile("st.shared.v4.u32 [%0],{%1,%2,%3,%4};" ::"r"(a), "r"(x), "r"(y), "r"(z), "r"(w) : "memory");
}
__device__ __forceinline__ void sts64(uint32_t a, uint32_t x, uint32_t y) { asm volatile("st.shared.v2.u32 [%0],{%1,%2};" ::"r"(a), "r"(x), "r"(y) : "memory"); }
__device__ __forceinline__ void sts128p(uint32_t a, uint32_t x, uint32_t y, uint32_t z, uint32_t w, bool p) {
    asm volatile("{.reg .pred p; setp.ne.u32 p,%5,0; @p st.shared.v4.u32 [%0],{%1,%2,%3,%4};}" ::"r"(a), "r"(x), "r"(y), "r"(z), "r"(w), "r"((uint32_t)p) : "memory");
}
__device__ __forceinline__ void sts32(uint32_t a, uint32_t x) { asm volatile("st.shared.u32 [%0],%1;" ::"r"(a), "r"(x) : "memory"); }
__device__ __forceinline__ uint32_t pk(float lo, float hi) { uint32_t r; asm("cvt.rn.bf16x2.f32 %0,%1,%2;" : "=r"(r) : "f"(hi), "f"(lo)); return r; }

__device__ __forceinline__ uint32_t pkv(float lo, float hi) { uint32_t r; asm volatile("cvt.rn.bf16x2.f32 %0,%1,%2;" : "=r"(r) : "f"(hi), "f"(lo)); return r; }

__device__ __forceinline__ void mma16z(float* d, uint32_t a0, uint32_t a1, uint32_t a2, uint32_t a3, uint32_t b0, uint32_t b1) {
    asm("mma.sync.aligned.m16n8k16.row.col.f32.bf16.bf16.f32 {%0,%1,%2,%3},{%4,%5,%6,%7},{%8,%9},{%10,%10,%10,%10};"
        : "=f"(d[0]), "=f"(d[1]), "=f"(d[2]), "=f"(d[3]) : "r"(a0), "r"(a1), "r"(a2), "r"(a3), "r"(b0), "r"(b1), "f"(0.f));
}
__device__ __forceinline__ void mma16(float* d, uint32_t a0, uint32_t a1, uint32_t a2, uint32_t a3, uint32_t b0, uint32_t b1) {
    asm("mma.sync.aligned.m16n8k16.row.col.f32.bf16.bf16.f32 {%0,%1,%2,%3},{%4,%5,%6,%7},{%8,%9},{%0,%1,%2,%3};"
        : "+f"(d[0]), "+f"(d[1]), "+f"(d[2]), "+f"(d[3]) : "r"(a0), "r"(a1), "r"(a2), "r"(a3), "r"(b0), "r"(b1));
}
__device__ __forceinline__ void mma8(float* d, uint32_t a0, uint32_t a1, uint32_t b0) {
    asm("mma.sync.aligned.m16n8k8.row.col.f32.bf16.bf16.f32 {%0,%1,%2,%3},{%4,%5},{%6},{%0,%1,%2,%3};"
        : "+f"(d[0]), "+f"(d[1]), "+f"(d[2]), "+f"(d[3]) : "r"(a0), "r"(a1), "r"(b0));
}
__device__ __forceinline__ void wg_fence() { asm volatile("wgmma.fence.sync.aligned;" ::: "memory"); }
__device__ __forceinline__ void wg_commit() { asm volatile("wgmma.commit_group.sync.aligned;" ::: "memory"); }
template <int N> __device__ __forceinline__ void wg_wait() { asm volatile("wgmma.wait_group.sync.aligned %0;" ::"n"(N) : "memory"); }
template <int N> __device__ __forceinline__ void pin(float (&d)[N]) {
#pragma unroll
    for (int i = 0; i < N; i++) asm volatile("" : "+f"(d[i])::"memory");
}
#define ACC8(o) "+f"(d[o]), "+f"(d[o + 1]), "+f"(d[o + 2]), "+f"(d[o + 3]), "+f"(d[o + 4]), "+f"(d[o + 5]), "+f"(d[o + 6]), "+f"(d[o + 7])
#define OUT8(o) "=f"(d[o]), "=f"(d[o + 1]), "=f"(d[o + 2]), "=f"(d[o + 3]), "=f"(d[o + 4]), "=f"(d[o + 5]), "=f"(d[o + 6]), "=f"(d[o + 7])
template <int ACC> __device__ __forceinline__ void wgmma48(float (&d)[24], uint32_t a0, uint32_t a1, uint32_t a2, uint32_t a3, uint64_t desc) {
    if (ACC)
        asm volatile("wgmma.mma_async.sync.aligned.m64n48k16.f32.bf16.bf16 "
                     "{%0,%1,%2,%3,%4,%5,%6,%7,%8,%9,%10,%11,%12,%13,%14,%15,%16,%17,%18,%19,%20,%21,%22,%23},{%24,%25,%26,%27},%28,%29,1,1,0;"
                     : ACC8(0), ACC8(8), ACC8(16) : "r"(a0), "r"(a1), "r"(a2), "r"(a3), "l"(desc), "n"(ACC & 1));
    else
        asm volatile("wgmma.mma_async.sync.aligned.m64n48k16.f32.bf16.bf16 "
                     "{%0,%1,%2,%3,%4,%5,%6,%7,%8,%9,%10,%11,%12,%13,%14,%15,%16,%17,%18,%19,%20,%21,%22,%23},{%24,%25,%26,%27},%28,0,1,1,0;"
                     : OUT8(0), OUT8(8), OUT8(16) : "r"(a0), "r"(a1), "r"(a2), "r"(a3), "l"(desc));
}
template <int ACC> __device__ __forceinline__ void wgmma_p2(float (&d)[32], const uint32_t* a, uint64_t desc) {
    if (ACC)
        asm volatile("wgmma.mma_async.sync.aligned.m64n64k16.f32.bf16.bf16 "
                     "{%0,%1,%2,%3,%4,%5,%6,%7,%8,%9,%10,%11,%12,%13,%14,%15,%16,%17,%18,%19,%20,%21,%22,%23,%24,%25,%26,%27,%28,%29,%30,%31},{%32,%33,%34,%35},%36,1,1,1,0;"
                     : ACC8(0), ACC8(8), ACC8(16), ACC8(24) : "r"(a[0]), "r"(a[1]), "r"(a[2]), "r"(a[3]), "l"(desc));
    else
        asm volatile("wgmma.mma_async.sync.aligned.m64n64k16.f32.bf16.bf16 "
                     "{%0,%1,%2,%3,%4,%5,%6,%7,%8,%9,%10,%11,%12,%13,%14,%15,%16,%17,%18,%19,%20,%21,%22,%23,%24,%25,%26,%27,%28,%29,%30,%31},{%32,%33,%34,%35},%36,0,1,1,0;"
                     : OUT8(0), OUT8(8), OUT8(16), OUT8(24) : "r"(a[0]), "r"(a[1]), "r"(a[2]), "r"(a[3]), "l"(desc));
}
template <int ACC> __device__ __forceinline__ void wgmma_p2(float (&d)[4], const uint32_t* a, uint64_t desc) {
    if (ACC)
        asm volatile("wgmma.mma_async.sync.aligned.m64n8k16.f32.bf16.bf16 {%0,%1,%2,%3},{%4,%5,%6,%7},%8,1,1,1,0;"
                     : "+f"(d[0]), "+f"(d[1]), "+f"(d[2]), "+f"(d[3]) : "r"(a[0]), "r"(a[1]), "r"(a[2]), "r"(a[3]), "l"(desc));
    else
        asm volatile("wgmma.mma_async.sync.aligned.m64n8k16.f32.bf16.bf16 {%0,%1,%2,%3},{%4,%5,%6,%7},%8,0,1,1,0;"
                     : "=f"(d[0]), "=f"(d[1]), "=f"(d[2]), "=f"(d[3]) : "r"(a[0]), "r"(a[1]), "r"(a[2]), "r"(a[3]), "l"(desc));
}
__device__ __forceinline__ uint64_t desc_tab(uint32_t a) { return (uint64_t)((a & 0x3FFFF) >> 4) | ((uint64_t)(768 >> 4) << 16) | ((uint64_t)(128 >> 4) << 32); }

__device__ __forceinline__ void staged(uint32_t bar, int lane) {
    fence_async_s();
    __syncwarp();
    if (lane == 0) mbar_arrive(bar);
}

__device__ __forceinline__ void wgen(uint32_t win, uint32_t tab, uint32_t out, int c, int qq, int lane, uint32_t consumed, uint32_t chain, uint32_t gate, uint32_t cma) {
    uint32_t A[28];
    int mi = lane >> 3, rr = lane & 7;
    int L = 12 * (mi & 1) + c;
#pragma unroll
    for (int s = 0; s < 7; s++) {
        int u = s < 6 ? s / 3 : mi >> 1;
        int tap = s < 6 ? 16 * (s % 3) + 8 * (mi >> 1) + rr : 48;
        int line = 3 * tap + (L >> 3);
        uint32_t ad = win + u * WPIECE + line * 128 + (((L ^ line) & 7) << 4);
        asm volatile("ldmatrix.sync.aligned.m8n8.x4.trans.shared.b16 {%0,%1,%2,%3},[%4];"
                     : "=r"(A[4 * s]), "=r"(A[4 * s + 1]), "=r"(A[4 * s + 2]), "=r"(A[4 * s + 3]) : "r"(ad));
    }
    float d0[24], d1[24];
    uint64_t ds = desc_tab(tab);
    wg_fence();
    wgmma48<0>(d0, A[0], A[1], A[2], A[3], ds);
    wgmma48<0>(d1, A[12], A[13], A[14], A[15], ds);
    wgmma48<1>(d0, A[4], A[5], A[6], A[7], ds + 96);
    wgmma48<1>(d1, A[16], A[17], A[18], A[19], ds + 96);
    wgmma48<1>(d0, A[8], A[9], A[10], A[11], ds + 192);
    wgmma48<1>(d1, A[20], A[21], A[22], A[23], ds + 192);
    wgmma48<1>(d0, A[24], A[25], A[26], A[27], ds + 336);
    wgmma48<1>(d1, A[24], A[25], A[26], A[27], ds + 288);
    wg_commit();
    if (lane == 0) { if (chain) mbar_arrive(chain); mbar_arrive(consumed); }
    mbar_wait(gate);
    const uint32_t tag = ~lds32(cma) >> 31;
    wg_wait<0>();
    pin(d0); pin(d1);
    int g = lane >> 2, q = lane & 3;
    const uint32_t p = out + q * 512 + (8 * (c & 3) + (g ^ (2 * (q ^ qq)))) * 16;
#pragma unroll
    for (int nb = 0; nb < 6; nb++)
        if (nb < 5 || q < 2)
            sts128(p + nb * 2048, pk(d0[4 * nb], d0[4 * nb + 2]), pk(d0[4 * nb + 1], d0[4 * nb + 3]), pk(d1[4 * nb], d1[4 * nb + 2]),
                   tagged(pk(d1[4 * nb + 1], d1[4 * nb + 3]), g == 7, tag));
}

__device__ __forceinline__ void p1_unit(uint32_t blk, uint32_t out, uint32_t cst, int wg, int wq, int lane) {
    int g = lane >> 2, q = lane & 3;
    uint32_t T[20];
#pragma unroll
    for (int v = 0; v < 5; v++) { uint4 x = lds128(cst + C_P1A + (v * 32 + lane) * 16); T[4 * v] = x.x; T[4 * v + 1] = x.y; T[4 * v + 2] = x.z; T[4 * v + 3] = x.w; }
    uint32_t P[6][3][4];
    const uint32_t a0 = blk + g * 512 + (2 * q + (g & 1)) * 64 + ((wq ^ q) << 4), a1 = a0 ^ 64;
    const uint32_t sel0 = (g & 1) ? 0x1054 : 0x5410, sel1 = sel0 + 0x2222;
    uint32_t vv[2][3][2][4];
    auto ldv = [&](int nu) {
        const int ro = (nu == 0 ? 6 : (nu == 1 ? 14 : 0)) * 512;
#pragma unroll
        for (int t = 0; t < 3; t++)
#pragma unroll
            for (int e = 0; e < 2; e++) {
                uint4 x = lds128((e ? a1 : a0) + t * 11264 + ro);
                vv[nu & 1][t][e][0] = x.x; vv[nu & 1][t][e][1] = x.y; vv[nu & 1][t][e][2] = x.z; vv[nu & 1][t][e][3] = x.w;
            }
    };
    ldv(0);
#pragma unroll
    for (int nu = 0; nu < 3; nu++) {
        if (nu < 2) ldv(nu + 1);
        auto& v = vv[nu & 1];
#pragma unroll
        for (int ch = 0; ch < 4; ch++) {
            const uint32_t sel = (ch & 1) ? sel1 : sel0;
            uint32_t b[2][3];
#pragma unroll
            for (int hf = 0; hf < 2; hf++)
#pragma unroll
                for (int t = 0; t < 3; t++) b[hf][t] = __byte_perm(v[t][0][(ch >> 1) + 2 * hf], v[t][1][(ch >> 1) + 2 * hf], sel);
            float d1[4];
            mma16z(d1, T[12], T[13], T[14], T[15], b[0][0], b[1][0]);
#pragma unroll
            for (int hf = 0; hf < 2; hf++) {
                float d0[4];
                mma16z(d0, T[0], T[1], T[2], T[3], b[hf][1], b[hf][2]);
                mma8(d0, T[16], T[17], b[hf][0]);
                mma16(d1, T[4 + 4 * hf], T[5 + 4 * hf], T[6 + 4 * hf], T[7 + 4 * hf], b[hf][1], b[hf][2]);
                P[(ch >> 1) + 2 * hf][nu][ch & 1] = pk(d0[0], d0[1]);
                P[(ch >> 1) + 2 * hf][nu][2 + (ch & 1)] = pk(d0[2], d0[3]);
            }
            P[4 + (ch >> 1)][nu][ch & 1] = pk(d1[0], d1[1]);
            P[4 + (ch >> 1)][nu][2 + (ch & 1)] = pk(d1[2], d1[3]);
        }
#pragma unroll
        for (int pb = 0; pb < 6; pb++) asm volatile("" : "+r"(P[pb][nu][0]), "+r"(P[pb][nu][1]), "+r"(P[pb][nu][2]), "+r"(P[pb][nu][3]));
                if (SPLIT >> nu & 1) region_end(cst + (O_BAR - O_C) + 8 * BC);
    }
    const uint64_t ds = desc_tab(cst + C_P1B);
    float dA[24], dB[24];
    auto issue = [&](int pb) {
        wg_fence();
        if (pb == 4) {
            wgmma48<0>(dA, P[pb][0][0], P[pb][0][1], P[pb][0][2], P[pb][0][3], ds);
            wgmma48<0>(dB, P[pb + 1][0][0], P[pb + 1][0][1], P[pb + 1][0][2], P[pb + 1][0][3], ds);
        } else {
            wgmma48<2>(dA, P[pb][0][0], P[pb][0][1], P[pb][0][2], P[pb][0][3], ds);
            wgmma48<2>(dB, P[pb + 1][0][0], P[pb + 1][0][1], P[pb + 1][0][2], P[pb + 1][0][3], ds);
        }
        wgmma48<1>(dA, P[pb][1][0], P[pb][1][1], P[pb][1][2], P[pb][1][3], ds + 96);
        wgmma48<1>(dB, P[pb + 1][1][0], P[pb + 1][1][1], P[pb + 1][1][2], P[pb + 1][1][3], ds + 96);
        wgmma48<1>(dA, P[pb][2][0], P[pb][2][1], P[pb][2][2], P[pb][2][3], ds + 192);
        wgmma48<1>(dB, P[pb + 1][2][0], P[pb + 1][2][1], P[pb + 1][2][2], P[pb + 1][2][3], ds + 192);
        wg_commit();
    };
    issue(4);
    bar_sync(1 + wg, 128);
    asm volatile("" : "+r"(g), "+r"(q));
    wg_wait<0>(); pin(dA); pin(dB);
    uint32_t o[12][2];
#pragma unroll
    for (int k = 0; k < 12; k++) { const int i = 4 * (k >> 1) + (k & 1); o[k][0] = pkv(dA[i], dA[i + 2]); o[k][1] = pkv(dB[i], dB[i + 2]); }
    issue(0);
    {
        const int sw = (g >> 1) & 1, r0 = 2 * (lds8(cst + (O_PERM - O_C) + (g < 6 ? 8 + (g >> 1) : 1)) * 11 + q) + sw;
        const uint32_t a0 = out + r0 * 128 + ((((4 * sw + wq) ^ r0) & 7) << 4) + 8 * (g & 1);
        const uint32_t m = wq == 3 && (g & 1) ? TAGM : 0, m0 = sw ? m : 0, m1 = m ^ m0;
#pragma unroll
        for (int k = 11; k >= 0; k--) {
            sts64((a0 ^ ((k & 2) * 72 + (k & 1) * 64)) + 1024 * (k >> 2), o[k][0], tagged(o[k][1], (k & 1) ? m1 : m0, TAGX));
            if (k == 8) __syncwarp();
        }
    }
    wg_wait<0>(); pin(dA); pin(dB);
#pragma unroll
    for (int k = 0; k < 12; k++) { const int i = 4 * (k >> 1) + (k & 1); o[k][0] = pkv(dA[i], dA[i + 2]); o[k][1] = pkv(dB[i], dB[i + 2]); }
    issue(2);
    region_end(cst + (O_BAR - O_C) + 8 * BC);
    const int r0 = 2 * (lds8(cst + (O_PERM - O_C) + g) * 11 + q) + (g & 1);
    const uint32_t ao = out + r0 * 128 + ((((4 * (g & 1) + wq) ^ r0) & 7) << 4);
    const uint32_t m = wq == 3 ? TAGM : 0, m0 = (g & 1) ? m : 0, m1 = m ^ m0;
    wg_wait<0>(); pin(dA); pin(dB);
#pragma unroll
    for (int k = 0; k < 12; k++) {
        const int i = 4 * (k >> 1) + (k & 1);
        sts128p((ao ^ ((k & 2) * 72 + (k & 1) * 64)) + 1024 * (k >> 2), o[k][0], o[k][1], pk(dA[i], dA[i + 2]),
                tagged(pk(dB[i], dB[i + 2]), (k & 1) ? m1 : m0, TAGX), k < 8 || q < 3);
    }
}

template <int NB, class F>
__device__ __forceinline__ void p2_step(const uint32_t (&Wf)[48], uint32_t in, uint32_t a0, uint32_t m, uint32_t t, uint32_t bar, int lane, int wg, int s, F meanwhile) {
    float dp[4 * NB], dm[4 * NB];
    const uint32_t lo = ((in & 0x3FFFF) >> 4) | (1u << 16);
    auto desc = [&](int o) { return (uint64_t)(lo + o) | ((uint64_t)(1024 >> 4) << 32) | (1ull << 62); };
    if (NB > 1 && (wg || s > 1)) bar_sync(4 + wg, 256);
    wg_fence();
    wgmma_p2<0>(dp, &Wf[0], desc(0));
    wgmma_p2<0>(dm, &Wf[24], desc(4));
#pragma unroll
    for (int ks = 1; ks < 6; ks++) {
        wgmma_p2<1>(dp, &Wf[4 * ks], desc((ks >> 1) * NB * 64 + (ks & 1) * 2));
        wgmma_p2<1>(dm, &Wf[24 + 4 * ks], desc((ks >> 1) * NB * 64 + (ks & 1) * 2 + 4));
    }
    wg_commit();
    if (NB > 1 && (wg < 2 || s < 6)) asm volatile("bar.arrive %0,256;" ::"r"(wg == 2 ? 4 : 5 + wg) : "memory");
    meanwhile();
    mbar_wait_ph(bar + 8 * (s < 2 ? BD1 + 1 : BDP + 2 * wg + (s & 1)), s >= 2 ? ((s >> 1) & 1) ^ 1 : 0);
    wg_wait<0>();
    pin(dp); pin(dm);
    if (NB > 1 && s < 6 && lane == 0) mbar_arrive(bar + 8 * (BPE + s));
    uint32_t v[2 * NB];
#pragma unroll
    for (int nb = 0; nb < NB; nb++) {
        float pr = dp[4 * nb] - dp[4 * nb + 3], pi = dp[4 * nb + 1] + dp[4 * nb + 2];
        float mr = dm[4 * nb] - dm[4 * nb + 3], mi = dm[4 * nb + 1] + dm[4 * nb + 2];
        v[2 * nb] = tagged(pk(pr + mr, pi - mi), m, t);
        v[2 * nb + 1] = tagged(pk(pi + mi, mr - pr), m, t);
        if (nb & 1)
            asm volatile("stmatrix.sync.aligned.m8n8.x4.trans.shared.b16 [%0],{%1,%2,%3,%4};" ::"r"(a0 + (nb - 1) * 1024), "r"(v[2 * nb - 2]), "r"(v[2 * nb - 1]),
                         "r"(v[2 * nb]), "r"(v[2 * nb + 1]) : "memory");
    }
    if (NB == 1) asm volatile("stmatrix.sync.aligned.m8n8.x2.trans.shared.b16 [%0],{%1,%2};" ::"r"(a0), "r"(v[0]), "r"(v[1]) : "memory");
}

__device__ __forceinline__ bool p3_unit(uint32_t blk, uint32_t cst, int wg, int wq, int lane) {
    int g = lane >> 2, q = lane & 3;
    uint32_t T[12];
#pragma unroll
    for (int v = 0; v < 3; v++) { uint4 x = lds128(cst + C_P3 + (v * 32 + lane) * 16); T[4 * v] = x.x; T[4 * v + 1] = x.y; T[4 * v + 2] = x.z; T[4 * v + 3] = x.w; }
    uint32_t ad[3][2];
#pragma unroll
    for (int nu = 0; nu < 3; nu++) {
        const int pos = lds8(cst + (O_PERM - O_C) + min(4 * nu + (g >> 1), 10));
#pragma unroll
        for (int ka = 0; ka < 2; ka++) {
            int r = 2 * (pos * 11 + (ka ? min(8 + q, 10) : q)) + (g & 1);
            ad[nu][ka] = blk + r * 128 + ((((2 * wq) ^ r) & 7) << 4);
        }
    }
    uint32_t o[2][4][4], bad = 0, P[8][3][2];
#pragma unroll
    for (int nu = 0; nu < 3; nu++) {
        uint32_t z[3][2][4];
#pragma unroll
        for (int ka = 0; ka < 3; ka++)
#pragma unroll
            for (int h = 0; h < 2; h++) {
                uint4 x = lds128((ad[nu][ka >> 1] ^ (h << 4)) + (ka & 1) * 1024);
                z[ka][h][0] = x.x; z[ka][h][1] = x.y; z[ka][h][2] = x.z; z[ka][h][3] = x.w;
                if (h) bad |= x.w ^ TAGZ;
            }
#pragma unroll
        for (int ch = 0; ch < 8; ch++) {
            const uint32_t sel = (ch & 1) ? 0x7632 : 0x5410;
            float d[4];
            mma16z(d, T[0], T[1], T[2], T[3], __byte_perm(z[0][0][ch >> 1], z[0][1][ch >> 1], sel), __byte_perm(z[1][0][ch >> 1], z[1][1][ch >> 1], sel));
            mma8(d, T[4], T[5], __byte_perm(z[2][0][ch >> 1], z[2][1][ch >> 1], sel));
            P[ch][nu][0] = pk(d[0], d[1]); P[ch][nu][1] = pk(d[2], d[3]);
        }
    }
    if (bar_any(1 + wg, 128, wq == 3 && (bad & TAGM))) return false;
#pragma unroll
    for (int j = 0; j < 4; j++) {
        float d2[2][2][4];
#pragma unroll
        for (int e = 0; e < 2; e++)
#pragma unroll
            for (int be = 0; be < 2; be++) {
                const int ch = 2 * j + e;
                mma16z(d2[e][be], P[ch][0][0], P[ch][0][1], P[ch][1][0], P[ch][1][1], T[8 + 2 * be], T[9 + 2 * be]);
                mma8(d2[e][be], P[ch][2][0], P[ch][2][1], T[6 + be]);
            }
#pragma unroll
        for (int be = 0; be < 2; be++)
#pragma unroll
            for (int k = 0; k < 4; k++) o[be][k][j] = pk(d2[0][be][k], d2[1][be][k]);
    }
    const int p = 4 * g + q;
    const uint32_t a = blk + p * 64 + ((wq ^ ((p >> 1) & 3)) << 4);
#pragma unroll
    for (int be = 0; be < 2; be++)
#pragma unroll
        for (int k = 0; k < 4; k++)
            sts128(a + (2 * be + (k & 1)) * 4096 + (k >> 1) * 2048, o[be][k][0], o[be][k][1], o[be][k][2], o[be][k][3]);
    return true;
}

template <int Z> __device__ __forceinline__ int s_row(int gr, int st, int cg, int ci, unsigned cm) {
    const int sf = (ci >> 2) & 1, y = 3 * (3 * gr + cg) + ((st ^ sf) << (Z ^ (cm >> 31))), pg = y >> 2;
    const int r = (pg << 14) | ((ci & 1) << 6) | ((ci & 2) << 8) | ((y & 1) << 10) | ((y & 2) << 11);
    return r | ((((Z ? st : sf) ^ ci ^ (ci >> 1) ^ y ^ (y >> 1) ^ (cm >> pg)) & 1) << 5);
}
__device__ __forceinline__ int w_row(int fw, int hg, int cg, int io, unsigned cm) {
    const int home = fw == 5 ? hg >> 1 : fw > 5;
    const int col = fw == 5 ? 15 + (hg & 1) : 3 * (fw > 5 ? fw - 6 : fw) + hg;
    const int z = 9 * col + 3 * cg + io, pg = NPS + (z >> 5);
    const int r = (pg << 12) | ((z & 1) << 4) | ((z & 6) << 6) | ((z & 24) << 7);
    return r | (((home ^ __popc(z & 15) ^ (cm >> pg)) & 1) << 3);
}
__device__ __forceinline__ int s_tile(int t) { return ((t & 3) << 7) | ((t & 4) << 9) | ((t & 8) << 10); }
__device__ __forceinline__ int xoff(int r) { return r < 3 ? O_B0 + r * BLK : (r == 3 ? O_B4 : O_B3); }
__device__ __forceinline__ int soff(int r) { return r == 2 ? O_B2 + 2048 : xoff(r); }
__device__ __forceinline__ int zoff(int r) { return r == 0 ? O_B2 + 2048 : (r == 1 ? O_B3 : (r == 2 ? O_B4 : (r == 3 ? O_Z3 : O_Z4))); }

struct Role1 {
    int sd, k, nu;
    __device__ __forceinline__ Role1(int cta) {
        sd = cta >= NH; k = cta - sd * NH;
        if (k < 60) k = (k >> 1) + ((k & 1) ? 0 : 30);
        nu = k < NUH - 4 * NH ? 5 : 4;
    }
};
struct Role {
    int sd, k, fp, nu;
    __device__ __forceinline__ Role(int rho) {
        sd = rho >= NH;
        const int kk = sd ? NCTA - 1 - rho : rho;
        k = NH - 1 - kk;
        nu = k < NUH - 4 * NH ? 5 : 4;
        fp = k >= 5 + sd ? 60 * sd + k - 5 : -1;
    }
};
__device__ __forceinline__ int stage_row(const Role& R, int s, int lane, unsigned cm, int z) {
    const int ci = R.fp > 0 ? (R.fp - 1) / 15 : 0, rw = 2 * (ci ? R.fp - 15 * ci - 1 : R.fp);
    return (z ? s_row<1>(s, lane & 1, lane >> 1, ci, cm) : s_row<0>(s, lane & 1, lane >> 1, ci, cm)) + rw + (s ? 0 : s_tile(14));
}
__device__ __forceinline__ int stage_off(int s, int lane) { return (lane >> 1) * 8192 + (lane & 1) * (s ? 4096 : 512); }
template <int Z, class RT> __device__ __forceinline__ int unit_row(const RT& R, int r, int lane, unsigned cm) {
    const int u = r * NH + R.k, ts = u / 3;
    return s_row<Z>((ts + 14) >> 4, R.sd, u - 3 * ts, lane, cm) + s_tile(ts + 14);
}
__device__ __forceinline__ int unit_off(int lane) { return lane ? 3840 * lane + 256 : 0; }

__global__ void __launch_bounds__(512, 1) fftconv_kernel(const __grid_constant__ Maps mp) {
    extern __shared__ __align__(1024) unsigned char smraw[];
    const uint32_t sm = s2u(smraw);
    const uint32_t bar = sm + O_BAR;
    const int tid = threadIdx.x, lane = tid & 31;
    const uint32_t tstart = clock();
    int xc = 0, xw = 0, xh = 0, xp = -1;
    uint32_t xd = 0;
    const CUtensorMap* xm = nullptr;
    if (tid >= 384 && tid < 416) {
        const int c = blockIdx.x;
        if (elect()) {
            const int ip = c % 12, pr = 3 * (8 * (ip >> 1) + 2 * (ip & 1));
#pragma unroll
            for (int i = 0; i < 8; i++) mbar_init(bar + 8 * i, 1);
            mbar_expect(bar + 8 * BW, 2 * 18816 + WT_BYTES);
            TR(3, 18);
            tma_ld3(sm + O_W0, &mp.w, bar + 8 * BW, 0, pr, 0);
            tma_ld3(sm + O_W0 + WPIECE, &mp.w, bar + 8 * BW, 0, pr + 12, 0);
            bulk_ld(sm + O_WT, mp.wtab + (c / 12) * WT_BYTES, WT_BYTES, bar + 8 * BW);
            if (W1AT < 0) {
                mbar_expect(bar + 8 * (BW + 1), 2 * 18816);
                tma_ld3(sm + O_W1, &mp.w, bar + 8 * (BW + 1), 0, pr + 3, 0);
                tma_ld3(sm + O_W1 + WPIECE, &mp.w, bar + 8 * (BW + 1), 0, pr + 15, 0);
            }
            mbar_expect(bar + 8 * BC, C_BYTES);
            bulk_ld(sm + O_C, mp.ctab, C_BYTES, bar + 8 * BC);
            TR(3, 19);
        }
        __syncwarp();
        asm volatile("bar.arrive 9,512;\n bar.arrive 0,384;" ::: "memory");
        const Role1 X(c);
        if (lane < 3 + X.nu && lane >= (W1AT < 0 ? BX : BW + 1)) mbar_expect(bar + 8 * lane, lane >= BX ? BLK : 2 * 18816);
        const int p = lane & 15, top = lane >> 4, r = p / 3, t = p - 3 * r;
        const int u = r * NH + X.k, ts = u / 3, tr = ts / 14, th = 7 * X.sd + tr, tw = ts - 14 * tr;
        xc = 32 * (u - 3 * ts) + (r << 8);
        xw = t || tw ? 16 * tw - 8 + 8 * t : 216;
        xh = th ? 16 * th - 6 : (top ? 218 : 0);
        xd = sm + xoff(r) + t * 11264 + (th || top ? 0 : 3072);
        xm = th ? &mp.x22 : (top ? &mp.x6 : &mp.x16);
        xp = top && th ? -1 : p;
        __syncwarp();
        if (xp >= 0 && xp < X0N) tma_ld3(xd, xm, bar + 8 * BX + (xc >> 8) * 8, xc & 255, xw, xh);
        __syncwarp();
        TR(3, 20);
    }
    if (tid < 128) {
        const int c = blockIdx.x, vp = min(c & 31, NPAGE - 2);
        const int r0 = 94 + (c & 1) + ((c >> 1) << 7);
        const int r1 = ((vp + 1) << 14) + 94 + ((c >> 5) & 1) + ((c >> 6) << 7) + (vp < NPS - 1 ? 0 : ((0xA151 >> (5 * (vp - NPS + 1))) & 31) << 9);
        unsigned* a = reinterpret_cast<unsigned*>(mp.s) + ((tid & 64 ? r1 : r0) + (tid & 32)) * 32 + lane;
        const bool on = tid < 64 || (c & 31) < NPAGE - 1;
        if (on) *a = 0;
        bar_sync(10, 128);
        TR(5, 18);
        unsigned t = 0;
        if (on) asm volatile("{.reg .u32 v; .reg .pred p;\n atom.relaxed.gpu.global.exch.b32 v,[%1],1;\n setp.eq.u32 p,v,0;\n @p mov.u32 %0,%%clock;}" : "+r"(t) : "l"(a) : "memory");
        if (lane == 0) sts32(sm + O_PT + (tid >> 3), t);
        bar_sync(10, 128);
        const uint4 tt = lds128(sm + O_PT);
        const int far = (((int)(tt.x - tt.y) > 0) ^ __popc(r0 & 0x1640)) & 1;
        TR(5, 19);
        if (lane == 0 && (tid == 32 || (tid == 64 && on))) {
            const int i = tid == 32 ? 20 + c / 12 : vp, v = tid == 32 ? far : (far ^ ((int)(tt.z - tt.w) > 0) ^ __popc(r1 & 0x1640)) & 1;
            red_add(mp.cnt + 64 * (CV + (i & 7)), 1u << ((i & 24) + 4 * v));
        }
        if (tid == 0) sts32(sm + O_ROLE, far);
        __syncwarp();
        bar_sync(9, 512);
        if (tid == 0) mbar_arrive(bar + 8 * (BRL + 1));
        __syncwarp();
    }
    const int warp = __shfl_sync(0xffffffffu, tid >> 5, 0);
    int cta;
    asm volatile("mov.u32 %0,%%ctaid.x;" : "=r"(cta));
    const int wip = cta % 12;
    const Role1 X(cta);
    if (warp == 12) bar_sync(11, 384);
    else if (warp >= 4) {
        if (elect()) {
            const int gi = warp - 3, cnt = gi < 8 ? 1 : (gi == 8 ? 12 : 4);
#pragma unroll
            for (int i = 0; i < 8; i++) mbar_init(bar + 64 * gi + 8 * i, cnt);
            if (warp == 13) {
#pragma unroll
                for (int i = 0; i < 8; i++) mbar_init(bar + 64 * 9 + 8 * i, 4);
            }
        }
        __syncwarp();
        if (lane == 0) TRL(7, 4 + warp);
        asm volatile("bar.arrive 9,512;\n bar.arrive 11,384;" ::: "memory");
        bar_sync(0, 384);
        if (warp == 14) TR(7, 3);
        if (PFW & 1) {
            const int t = tid - 224;
            if (t >= 97 && t < 106) asm volatile("prefetch.tensormap [%0];" ::"l"(&mp.w + (t - 96)) : "memory");
        }
    }

    if (warp >= 12) {
        asm volatile("setmaxnreg.dec.sync.aligned.u32 32;");
        if (warp == 12) {
            auto load_w = [&](int j) {
                if (lane < 2) tma_ld3(sm + (j ? O_W1 : O_W0) + lane * WPIECE, &mp.w, bar + 8 * (BW + j), 0, 3 * (8 * (wip >> 1) + 2 * (wip & 1) + 4 * lane + j), 0);
                __syncwarp();
            };
            TR(7, 4);
            uint32_t due = tstart + XD0;
#pragma unroll 1
            for (int i = X0N; i < 3 * X.nu; i++) {
                if (W1AT >= 0 && i == max(W1AT, X0N)) load_w(1);
                if (i == 9 || i == 12) mbar_wait(bar + 8 * (i == 9 ? BWC + 1 : BDW));
                until(due, 0);
                due += XD;
                if (xp == i) tma_ld3(xd, xm, bar + 8 * BX + (xc >> 8) * 8, xc & 255, xw, xh);
                __syncwarp();
                if (i % 3 == 2) TR(3, 21 + i / 3);
            }
        } else if (warp == 13) {
            mbar_wait(bar + 8 * (BRL + 1));
            if (lane == 0) {
                const unsigned far = lds32(sm + O_ROLE), t = atomicAdd(mp.cnt + 64 * (CT + far), 1u);
                sts32(sm + O_ROLE, far ? NCTA - 1 - t : t);
                mbar_arrive(bar + 8 * BRL);
            }
            __syncwarp();
            TR(5, 20);
        } else if (warp == 14) {
            TR(7, 5);
            unsigned vote = 0;
            until(tstart + VT, 0);
            for (int it = 0; __any_sync(0xffffffffu, lane < 31 && (vote & 15) + (vote >> 4) < (lane < 4 ? 5u : (lane < 20 ? 4u : 12u))) && it < (1 << 16); it++)
                asm volatile("ld.acquire.gpu.global.u8 %0,[%1];" : "=r"(vote) : "l"(reinterpret_cast<unsigned char*>(mp.cnt + 64 * (CV + (lane & 7))) + (lane >> 3)) : "memory");
            const unsigned cm = (__ballot_sync(0xffffffffu, lane < 20 && (vote >> 4) > (vote & 15)) << 1) | __ballot_sync(0xffffffffu, lane == 31 && vote);
            const unsigned gm = 0x7ff00000u, lo = __ballot_sync(0xffffffffu, vote < 64) & gm, hi = __ballot_sync(0xffffffffu, vote >= 144) & gm, mid = gm ^ lo ^ hi;
            const unsigned below = (1u << lane) - 1;
            const int pos = vote < 64 ? __popc(lo & below) : (vote < 144 ? __popc(lo) + __popc(mid & below) : 11 - __popc(hi) + __popc(hi & below));
            if (lane >= 20 && lane < 31) asm volatile("st.shared.u8 [%0],%1;" ::"r"(sm + O_PERM + lane - 20), "r"(pos) : "memory");
            __syncwarp();
            if (lane == 0) { sts32(sm + O_CM, cm); mbar_arrive(bar + 8 * BCM); }
            __syncwarp();
            TR(5, 22);
        }
        auto role = [&]() { mbar_wait(bar + 8 * BRL); return Role(bcast(lds32(sm + O_ROLE), 0)); };

        if (warp == 12) {
            const Role R = role();
            if (R.fp >= 0) {
                mbar_wait(bar + 8 * BCM);
                const unsigned cm = lds32(sm + O_CM);
                if (lane < 7) mbar_expect(bar + 8 * (BPF + lane), lane ? STG : 3072);
                mbar_wait(bar + 8 * (BIS + 2));
                const int v0 = stage_row(R, lane >> 3, lane & 7, cm, 0), v1 = stage_row(R, 4 + (lane >> 3), lane & 7, cm, 0);
                uint32_t dst = sm + O_S0, seen = 0;
#pragma unroll 1
                for (int s = 0; s < 7; s++) {
                    int row[6];
#pragma unroll
                    for (int i = 0; i < 6; i++) row[i] = bcast(s < 4 ? v0 : v1, 8 * s + i);
                    const CUtensorMap* m = s ? &mp.p16 : &mp.p2;
                    const uint32_t hs = s ? 4096 : 512;
                    for (int it = 0; !(seen >> s & 1) && it < (1 << 16); it++) {
                        unsigned v = 0;
                        if (lane == s || (s >= WIN && lane > s && lane < 7)) asm volatile("ld.acquire.gpu.global.u32 %0,[%1];" : "=r"(v) : "l"(mp.cnt + 64 * (CX + lane)) : "memory");
                        seen = __ballot_sync(0xffffffffu, v >= (lane ? 96u : 12u));
                    }
                    TR(5, s);
                    mbar_wait(bar + 8 * (s > 3 ? BPE + s - 3 : (s ? BWE + s - 1 : BD1)));
                    if (elect()) {
#pragma unroll
                        for (int i = 0; i < 6; i++) tma_ld5(dst + i * hs, m, bar + 8 * (BPF + s), 0, row[i], 0, 0, 0);
                    }
                    __syncwarp();
                    dst = dst >= sm + O_IN + 2 * STG ? sm + O_IN : dst + STG;
                    TR(3, 3 + s);
                }
            }
        } else if (warp == 13) {
            const Role R = role();
            mbar_wait(bar + 8 * BCM);
            if (R.fp >= 0) {
                const unsigned cm = lds32(sm + O_CM);
                if (lane < 3) mbar_expect(bar + 8 * (BWF + lane), STG);
                const int fw = R.fp / 11;
                {
                    const int fh = R.fp - 11 * fw, b = lane / 3, io = lane - 3 * b;
                    const int row = w_row(fw, fh >> 2, b ? b - 1 : 2, io, cm) + 2 * (fh & 3);
                    mbar_wait(bar + 8 * (BDW + 1));
                    poll(mp.cnt + 64 * (CW + fw), 12);
                    TR(3, 17);
                    const uint32_t t0 = clock();
#pragma unroll 1
                    for (int i = 0; i < 9; i++) {
                        if (i == 6) mbar_wait(bar + 8 * BD1);
                        until(t0 + i * LPW, NAP);
                        if (lane == i) tma_ld4(sm + O_IN + lane * 8192, &mp.wf, bar + 8 * (BWF + b), 0, row, 0, 0);
                        __syncwarp();
                    }
                    TR(3, 15);
                }
                {
                    const int row = stage_row(R, 0, lane & 7, cm, lane < 8);
                    mbar_wait(bar + 8 * BR2); mbar_wait(bar + 8 * (BR2 + 2)); mbar_wait(bar + 8 * (BR2 + 4));
                    TR(4, 7);
                    if (lane < 6 || (R.fp == 15 && lane < 14 && (lane & 9) == 9)) tma_st5(&mp.p2, sm + O_OUT + stage_off(0, lane & 7), 0, row, 0, 0, 0);
                    __syncwarp();
                    bulk_commit(); bulk_wait_read<0>();
                    __syncwarp();
                    if (lane < 4) mbar_arrive(bar + 8 * (lane < 3 ? BDP + 2 * lane : BI2));
                    if (lane == 0) red_add(mp.cnt + 64 * CY);
                    __syncwarp();
                }
            }
            if (lane < R.nu) mbar_expect(bar + 8 * (BZ + lane), SLAB);
            const int v = unit_row<1>(R, lane >> 1, 4 * (lane & 1), lds32(sm + O_CM));
            mbar_wait(bar + 8 * (BD1 + X.nu - 2)); mbar_wait(bar + 8 * (BD1 + X.nu - 1));
#pragma unroll 1
            for (int r = 0; r < R.nu; r++) {
                const int r0 = bcast(v, 2 * r), r1 = bcast(v, 2 * r + 1), gr = (r * NH + R.k + 42) / 48;
                const uint32_t dst = sm + zoff(r), fb = bar + 8 * (BZ + r);
                if (R.fp >= 0) {
                    if (r >= 3) { mbar_wait(bar + 8 * (r == 3 ? BPE + 4 : BD2)); mbar_wait(bar + 8 * (r == 3 ? BPE + 5 : BD2 + 1)); }
                    mbar_wait(bar + 8 * (BI2 + gr));
                }
                poll(mp.cnt + 64 * (CY + gr), NFP);
                TR(5, 8 + r);
                if (elect()) {
#pragma unroll
                    for (int i = 0; i < 8; i++)
                        tma_ld2(dst + unit_off(i), i ? &mp.s30 : &mp.s32, fb, 0, (i < 4 ? r0 : r1) ^ (((i & 1) * 96) ^ ((i & 2) * 272)));
                }
                __syncwarp();
                TR(3, 10 + r);
            }
            if (R.fp >= 0) mbar_wait(bar + 8 * (BPF + 6));
            unsigned last = 0;
            if (lane == 0) last = atomicAdd(mp.cnt + 64 * CD, 1u) == NCTA - 1;
            if (__shfl_sync(0xffffffffu, last, 0)) {
                mp.cnt[64 * lane] = 0;
                if (lane < 8) mp.cnt[64 * (CV + lane)] = lane == 7 ? ((lds32(sm + O_CM) >> 31) ^ 1) << 24 : 0;
            }
        } else {
            const int me = warp & 1;
            uint32_t next = tstart + T0;
            auto pace = [&](int cost) {
                const uint32_t now = until(next, NAP);
                next = ((int)(now - next) > CREDIT ? now - CREDIT : next) + cost;
            };
            const int bal = X.nu == 5 ? BAL : (256 * 875 - BAL * 431) / 445;
            mbar_wait(bar + 8 * BCM);
            const unsigned cm = __shfl_sync(0xffffffffu, lds32(sm + O_CM), 0);
            {
                const int iq = 2 * wip + me, w = lane / 3, hg = lane - 3 * w, wfw = lds8(sm + O_PERM + cta / 12);
                unsigned char* dst = mp.s + (size_t)w_row(wfw, hg, w, iq >> 3, cm) * 512 + ((iq & 3) << 14) + ((iq & 4) << 16);
                const uint32_t src = sm + (me ? O_W0 : O_B3) + w * 11264 + hg * 4096;
                fence_async_g();
                if (me) { mbar_wait(bar + 8 * BIS); next = lds32(sm + O_NEXT); }
#pragma unroll 1
                for (int i = 0; i < 3; i++) {
                    mbar_wait(bar + 8 * (BRW + 3 * me + i));
                    if (i == 0) TR(4, me);
                    pace((RW * 11 / 4 * bal) >> 8);
                    if (w == i) bulk_st(dst, src, hg < 2 ? 4096 : 3072);
                    __syncwarp();
                }
                if (lane == 0) { sts32(sm + O_NEXT, next); mbar_arrive(bar + 8 * (BIS + me)); if (EARLY == 2 - me) red_add(mp.cnt + 64 * (CW + wfw)); }
                bulk_commit(); bulk_wait<0>();
                __syncwarp();
                if (lane == 0) { if (me && EARLY == 0) red_add(mp.cnt + 64 * (CW + wfw)); mbar_arrive(bar + 8 * (BDW + me)); }
                TR(6, me);
            }
            const int vu = unit_row<0>(X, lane >> 1, 4 * (lane & 1), cm);
            const Role R = role();
            const int first = (X.nu ^ me) & 1;
            int v, vx;
            { const int n = first + (lane & 30), s = n / 3, l = 2 * (n - 3 * s) + (lane & 1); v = stage_row(R, s + 1, l, cm, 1); vx = stage_row(R, s + 1, l, cm, 0); }
            asm volatile("" : "+r"(v), "+r"(vx));
#pragma unroll 1
            for (int j = me; j < X.nu; j += 2) {
                const int r0 = bcast(vu, 2 * j), r1 = bcast(vu, 2 * j + 1), cost = ((j < 2 ? R1A : R1) * 121 / 64 * bal) >> 8;
                const uint32_t src = sm + soff(j);
                unsigned* cn = mp.cnt + 64 * (CX + (j * NH + X.k + 42) / 48);
                mbar_wait(bar + 8 * (BR1 + j));
                mbar_wait(bar + 8 * (BIS + 1 + j));
                next = lds32(sm + O_NEXT);
                TR(4, 2 + j);
                if (elect()) {
                    if (EARLY == 2) red_add(cn);
#pragma unroll
                    for (int i = 0; i < 4; i++) {
                        const int x = ((i & 1) * 96) ^ ((i & 2) * 272);
                        pace(cost);
                        tma_st2(i ? &mp.s30 : &mp.s32, src + unit_off(i), 0, r0 ^ x);
                        tma_st2(i || X.sd ? &mp.s30 : &mp.s32, src + unit_off(4 + i), 0, r1 ^ x);
                    }
                    sts32(sm + O_NEXT, next); mbar_arrive(bar + 8 * (BIS + 2 + j));
                    if (EARLY == 1) red_add(cn);
                    bulk_commit(); bulk_wait_read<0>();
                    if (EARLY == 0) red_add(cn);
                    mbar_arrive(bar + 8 * (BD1 + j));
                }
                __syncwarp();
                TR(6, j + 2);
            }
            if (R.fp >= 0) {
                mbar_wait(bar + 8 * (BIS + 1 + X.nu));
                next = lds32(sm + O_NEXT) + first * 2 * R2;
                uint32_t prev = 0;
                int s = 1, w = first;
#pragma unroll 1
                for (int i = 0; i < 18; i += 2) {
                    const int r0 = bcast(v, i), r1 = bcast(v, i + 1), rx = bcast(vx, i + 1);
                    const int bi = 2 * w + (s & 1);
                    const uint32_t src = sm + O_OUT + (s & 1) * STG + w * 8192;
                    mbar_wait_ph(bar + 8 * (BR2 + bi), (s >> 1) & 1);
                    const uint32_t now = until(next, NAP);
                    next = ((int)(now - next) > CREDIT2 ? now - CREDIT2 : next) + 4 * R2;
                    if (w == 0) TR(4, 7 + s);
                    if (elect()) {
                        tma_st5(&mp.p16, src, 0, r0, 0, 0, 0);
                        tma_st5(&mp.p16, src + 4096, 0, r1, 0, 0, 0);
                        if (R.fp == 15) tma_st5(&mp.p16, src + 4096, 0, rx, 0, 0, 0);
                        bulk_commit();
                        bulk_wait_read<1>();
                        if (prev) mbar_arrive(prev);
                        if (w == 2) { if (LATE2) bulk_wait_read<0>(); red_add(mp.cnt + 64 * (CY + s)); mbar_arrive(bar + 8 * (BI2 + s)); }
                    }
                    __syncwarp();
                    if (w == 2) TR(6, 7 + s);
                    prev = bar + 8 * (BDP + bi);
                    w += 2; if (w > 2) { w -= 3; s++; }
                }
                if (elect()) { bulk_wait_read<0>(); mbar_arrive(bar + 8 * (BD2 + me)); }
                __syncwarp();
                next = clock();
            }
#pragma unroll 1
            for (int r = me; r < R.nu; r += 2) {
                const int u = r * NH + R.k, ts = u / 3, cg = u - 3 * ts, tr = ts / 14, th = 7 * R.sd + tr, tw = ts - 14 * tr;
                mbar_wait(bar + 8 * (BR3 + r));
                if (r && r < 3) { mbar_wait(bar + 8 * (BIS + 6 + r)); next = lds32(sm + O_NEXT); }
                TR(4, 14 + r);
#pragma unroll 1
                for (int c = 0; c < 2; c++) {
                    if (r < 3) pace(2 * R3);
                    if (elect()) tma_st4(&mp.y, sm + zoff(r) + c * 8192, 32 * cg, 0, 16 * th, 4 * tw + 2 * c);
                    __syncwarp();
                }
                if (lane == 0) { sts32(sm + O_NEXT, next); mbar_arrive(bar + 8 * (BIS + 7 + r)); }
                __syncwarp();
            }
            bulk_commit(); bulk_wait_read<0>();
            TR(4, 19 + me);
        }
    } else {
        asm volatile("setmaxnreg.inc.sync.aligned.u32 160;");
        const int lane = laneid();
        const int wg = __shfl_sync(0xffffffffu, tid >> 7, 0), wq = __shfl_sync(0xffffffffu, tid >> 5, 0) & 3;
#pragma unroll 1
        for (int it = 0; it <= wg; it++) {
            const int j = it > 0, cg = j ? wg + it - 2 : wg;
            mbar_wait(bar + 8 * (j == 0 && wg ? BWL + wg - 1 : BW + j));
            TR(wg, 24 + 2 * it);
            wgen(sm + (j ? O_W1 : O_W0), sm + O_WT, sm + (j ? O_W0 : O_B3) + cg * 11264, 4 * cg + wq, (2 * wip + j) & 3, lane, bar + 8 * (BWC + j),
                 j == 0 && wg < 2 ? bar + 8 * (BWL + wg) : 0, bar + 8 * (j ? BWC : BCM), sm + O_CM);
            staged(bar + 8 * (BRW + 3 * j + cg), lane);
            TR(wg, 25 + 2 * it);
        }
        mbar_wait(bar + 8 * BC);
#pragma unroll 1
        for (int r = wg; r < X.nu; r += 3) {
            mbar_wait(bar + 8 * (BX + r));
            TR(wg, 1 + 2 * (r / 3));
            p1_unit(sm + xoff(r), sm + soff(r), sm + O_C, wg, wq, laneid());
            staged(bar + 8 * (BR1 + r), laneid());
            TR(wg, 2 + 2 * (r / 3));
        }
        mbar_wait(bar + 8 * BRL);
        const Role R(__shfl_sync(0xffffffffu, lds32(sm + O_ROLE), 0));
        uint32_t phw = 0;
        if (R.fp >= 0) {
            const int lane = laneid();
            uint32_t Wf[48];
            const int g = lane >> 2, q = lane & 3;
            {
                const int b = wg == 2 ? 0 : wg + 1;
                const uint32_t p = sm + O_IN + b * STG + q * 1024 + wq * 128 + ((g ^ (2 * q) ^ (4 * ((R.fp % 11) & 1))) << 4);
                mbar_wait(bar + 8 * (BWF + b));
                TR(wg, 5);
#pragma unroll 1
                for (int it = 0; it < 4096; it++) {
                    const uint32_t tag = ~lds32(sm + O_CM) >> 31, m = g == 7;
                    uint32_t bad = 0;
#pragma unroll
                    for (int i = 0; i < 12; i++) {
                        uint4 v = lds128((p ^ (i >= 6 ? 544 : 0)) + (i % 6) * 4096);
                        Wf[4 * i] = v.x; Wf[4 * i + 1] = v.y; Wf[4 * i + 2] = v.z; Wf[4 * i + 3] = v.w & ~m;
                        bad |= v.w ^ tag;
                    }
                    if (!bar_any(1 + wg, 128, bad & m)) break;
                    if (wq == 0) {
                        TRC(2);
                        fence_async_s();
                        if (lane == 0) mbar_expect(bar + 8 * (BRT + 1 + wg), STG);
                        __syncwarp();
                        const int l = laneid(), fp = Role(lds32(sm + O_ROLE)).fp, fw = fp / 11, fh = fp - 11 * fw;
                        if (l < 3) tma_ld4(sm + O_IN + b * STG + l * 8192, &mp.wf, bar + 8 * (BRT + 1 + wg), 0, w_row(fw, fh >> 2, wg, l, lds32(sm + O_CM)) + 2 * (fh & 3), 0, 0);
                        __syncwarp();
                    }
                    mbar_wait_ph(bar + 8 * (BRT + 1 + wg), phw); phw ^= 1;
                }
                staged(bar + 8 * (BWE + b), lane);
            }
            const int ro = (lane & 6) + ((lane >> 3) & 1);
            const uint32_t o0 = sm + O_OUT + wg * 8192 + (lane >> 4) * 1024 + ro * 128 + (((2 * wq + (lane & 1)) ^ ro) << 4);
            const uint32_t m = wq == 3 && g >= 6 ? 0x10000 : 0, tg = g == 6 ? TAGZ << 16 : TAGZ;
            uint32_t ph = 0;
            const int t = 32 * wq + lane;
            uint32_t c0 = t * 128 + ((7 ^ (t & 7)) << 4) + 12, c1 = (c0 & 8191) + 16384;
            auto stale = [&](uint32_t in) { return (((lds32(in + c0) ^ TAGX) | (lds32(in + c1) ^ TAGX)) & TAGM) != 0; };
            auto landed = [&](int s, uint32_t in) {
                mbar_wait(bar + 8 * (BPF + s));
#pragma unroll 1
                for (int it = 0; it < 4096; it++) {
                    if (!bar_any(1 + wg, 128, stale(in))) break;
                    fence_async_s();
                    bar_sync(7, 384);
                    if (wg + wq == 0) {
                        TRC(0);
                        if (lane == 0) mbar_expect(bar + 8 * BRT, s ? STG : 3072);
                        __syncwarp();
                        const int l = laneid();
                        if (l < 6) tma_ld5(in + l * (s ? 4096 : 512), s ? &mp.p16 : &mp.p2, bar + 8 * BRT, 0, stage_row(Role(lds32(sm + O_ROLE)), s, l, lds32(sm + O_CM), 0), 0, 0, 0);
                        __syncwarp();
                    }
                    mbar_wait_ph(bar + 8 * BRT, ph); ph ^= 1;
                }
            };
            mbar_wait(bar + 8 * BD1);
            c0 &= 2047; c1 = (c1 & 1023) + 2048;
            landed(0, sm + O_S0);
            p2_step<1>(Wf, sm + O_S0, o0, m, tg, bar, lane, wg, 0, []() {});
            staged(bar + 8 * (BR2 + 2 * wg), lane);
            TR(wg, 6);
            c0 |= t << 7; c1 = (c0 & 8191) + 16384;
            uint32_t in = sm + O_IN;
            bool todo = true;
#pragma unroll 1
            for (int s = 1; s < 7; s++) {
                if (todo) landed(s, in);
                const uint32_t nx = in == sm + O_IN + 2 * STG ? sm + O_IN : in + STG;
                p2_step<8>(Wf, in, o0 + (s & 1) * STG, m, tg, bar, lane, wg, s, [&]() { todo = !mbar_test(bar + 8 * (BPF + s + 1)) || stale(nx); });
                todo = bar_any(1 + wg, 128, todo);
                in = nx;
                staged(bar + 8 * (BR2 + 2 * wg + (s & 1)), lane);
                TR(wg, 6 + s);
            }
        }
#pragma unroll 1
        for (int r = wg; r < R.nu; r += 3) {
            mbar_wait(bar + 8 * (BZ + r));
            TR(wg, 13 + 2 * (r / 3));
#pragma unroll 1
            for (int it = 0; it < 4096; it++) {
                if (p3_unit(sm + zoff(r), sm + O_C, wg, wq, laneid())) break;
                if (wq == 0) {
                    TRC(1);
                    fence_async_s();
                    if (laneid() == 0) mbar_expect(bar + 8 * (BRT + 1 + wg), SLAB);
                    __syncwarp();
                    const int l = laneid();
                    if (l < 8) tma_ld2(sm + zoff(r) + unit_off(l), l ? &mp.s30 : &mp.s32, bar + 8 * (BRT + 1 + wg), 0, unit_row<1>(Role(lds32(sm + O_ROLE)), r, l, lds32(sm + O_CM)));
                    __syncwarp();
                }
                mbar_wait_ph(bar + 8 * (BRT + 1 + wg), phw); phw ^= 1;
            }
            staged(bar + 8 * (BR3 + r), laneid());
            TR(wg, 14 + 2 * (r / 3));
        }
    }
}

typedef CUresult (*EncFn)(CUtensorMap*, CUtensorMapDataType, cuuint32_t, void*, const cuuint64_t*, const cuuint64_t*, const cuuint32_t*,
                          const cuuint32_t*, CUtensorMapInterleave, CUtensorMapSwizzle, CUtensorMapL2promotion, CUtensorMapFloatOOBfill);

void enc(EncFn f, CUtensorMap* m, void* p, int rank, const cuuint64_t* dims, const cuuint64_t* strides, const cuuint32_t* box,
         CUtensorMapSwizzle sw, CUtensorMapL2promotion pr = CU_TENSOR_MAP_L2_PROMOTION_NONE) {
    cuuint32_t es[5] = {1, 1, 1, 1, 1};
    f(m, CU_TENSOR_MAP_DATA_TYPE_BFLOAT16, rank, p, dims, strides, box, es, CU_TENSOR_MAP_INTERLEAVE_NONE, sw, pr, CU_TENSOR_MAP_FLOAT_OOB_FILL_NONE);
}

}

extern "C" void kernel_launch(void* const* d_in, const int* in_sizes, int n_in, void* d_out, int out_size) {
    void* fn = nullptr; cudaDriverEntryPointQueryResult qr;
    cudaGetDriverEntryPoint("cuTensorMapEncodeTiled", &fn, cudaEnableDefault, &qr);
    EncFn f = (EncFn)fn;
    void* pS; cudaGetSymbolAddress(&pS, g_S);
    pS = (void*)(((uintptr_t)pS + (1u << 21) - 1) & ~(uintptr_t)((1u << 21) - 1));
    Maps mp;
    cudaGetSymbolAddress((void**)&mp.ctab, g_ctab); cudaGetSymbolAddress((void**)&mp.wtab, g_wtab); cudaGetSymbolAddress((void**)&mp.cnt, g_cnt);
    mp.s = (unsigned char*)pS; mp.x = (const unsigned char*)d_in[0]; mp.wraw = (const unsigned char*)d_in[1];
    { cuuint64_t d[4] = {256, NPAGE << 12, 4, 2}, s[3] = {512, 1 << 14, 1 << 18}; cuuint32_t b[4] = {256, 2, 4, 2}; enc(f, &mp.wf, pS, 4, d, s, b, CU_TENSOR_MAP_SWIZZLE_NONE); }
    {
        cuuint64_t d[3] = {96, 224, 224}, s[2] = {192, 43008};
        cuuint32_t b6[3] = {32, 8, 6}, b16[3] = {32, 8, 16}, b22[3] = {32, 8, 22};
        enc(f, &mp.x22, d_in[0], 3, d, s, b22, CU_TENSOR_MAP_SWIZZLE_64B, CU_TENSOR_MAP_L2_PROMOTION_L2_128B);
        enc(f, &mp.x6, d_in[0], 3, d, s, b6, CU_TENSOR_MAP_SWIZZLE_64B, CU_TENSOR_MAP_L2_PROMOTION_L2_128B);
        enc(f, &mp.x16, d_in[0], 3, d, s, b16, CU_TENSOR_MAP_SWIZZLE_64B, CU_TENSOR_MAP_L2_PROMOTION_L2_128B);
    }
    { cuuint64_t d[4] = {96, 4, 224, 56}, s[3] = {192, 43008, 768}; cuuint32_t b[4] = {32, 4, 16, 2}; enc(f, &mp.y, d_out, 4, d, s, b, CU_TENSOR_MAP_SWIZZLE_64B); }
    {
        cuuint64_t d[2] = {64, NPAGE << 14}, s[1] = {128};
        cuuint32_t b32[2] = {64, 32}, b30[2] = {64, 30};
        enc(f, &mp.s32, pS, 2, d, s, b32, CU_TENSOR_MAP_SWIZZLE_128B);
        enc(f, &mp.s30, pS, 2, d, s, b30, CU_TENSOR_MAP_SWIZZLE_128B);
    }
    {
        cuuint64_t d[5] = {64, NPAGE << 14, 4, 2, 2}, s[4] = {128, 1 << 14, 1 << 18, 1 << 20};
        cuuint32_t b16[5] = {64, 2, 4, 2, 2}, b2[5] = {64, 2, 2, 1, 1};
        enc(f, &mp.p16, pS, 5, d, s, b16, CU_TENSOR_MAP_SWIZZLE_128B);
        enc(f, &mp.p2, pS, 5, d, s, b2, CU_TENSOR_MAP_SWIZZLE_128B);
    }
    { cuuint64_t d[3] = {64, 144, 49}, s[2] = {128, 18432}; cuuint32_t b[3] = {64, 3, 49}; enc(f, &mp.w, d_in[1], 3, d, s, b, CU_TENSOR_MAP_SWIZZLE_128B); }
    cudaFuncSetAttribute(fftconv_kernel, cudaFuncAttributeMaxDynamicSharedMemorySize, SMEM);
    fftconv_kernel<<<NCTA, 512, SMEM>>>(mp);
}
```

```cpp
#include <cuda_runtime.h>
#include <cuda_bf16.h>
#include <cuda.h>
#include <stdint.h>

#define TUNABLES {260, 285, 250, 280, 500, 250, 30, 1, 2000, 600, 1, 1900, 1500, 0, 2, 0, 340, 248, 500, 0, 0, 100}
constexpr int c_tune[24] = TUNABLES;
template <int I> struct TuneV { static constexpr int v = c_tune[I]; };
#define TV(i) TuneV<i>::v
#define RW TV(0)
#define R1 TV(1)
#define R2 TV(2)
#define R3 TV(3)
#define CREDIT TV(4)
#define LPW TV(5)
#define NAP TV(6)
#define EARLY TV(7)
#define T0 0
#define XD TV(9)
#define XD0 TV(8)
#define LATE2 TV(10)
#define PFW 1
#define VT TV(11)
#define CREDIT2 TV(12)
#define W1AT TV(13)
#define X0N TV(14)
#define WIN TV(15)
#define R1A TV(16)
#define BAL TV(17)
#define YD TV(18)
#define CLATE 0
#define CAT TV(19)
#define XO TV(20)
#define XE TV(21)
#define SPLIT 3

namespace {

constexpr int NCTA = 132, NH = 66;
constexpr int NUH = 294;
constexpr int NFP = 121;
constexpr int BLK = 33792;
constexpr int SLAB = 242 * 128;
constexpr int WPIECE = 19456;
constexpr int STG = 24576;
constexpr int NPS = 16, NPAGE = 21;
constexpr int O_B4 = 0, O_B0 = 87040, O_B2 = O_B0 + 2 * BLK, O_B3 = O_B0 + 3 * BLK;
constexpr int O_W1 = 0, O_W0 = 2 * WPIECE, O_WT = 4 * WPIECE;
constexpr int O_IN = 33792, O_OUT = O_IN + 3 * STG, O_Z3 = O_IN, O_S0 = O_OUT + 4096, O_Z4 = 124928;
constexpr int O_C = 222208, O_BAR = 230912, SMEM = 232448;
constexpr int C_P1A = 0, C_P1B = 2560, C_P3 = 7168, C_BYTES = 8704, WT_BYTES = 6912;
constexpr int BC = 0, BW = 1, BX = 3, BZ = 8, BWF = 13, BPF = 16, BCM = 23, BDW = 24, BD1 = 26, BDP = 31, BD2 = 37, BIS = 39, BEP = 50, BI2 = 51, BRT = 58, BRL = 62;
constexpr int BPE = 64, BWC = 70;
constexpr int BR2 = 72, BRW = 78, BWL = 84, BR1 = 86, BR3 = 91, BWE = 96;
constexpr int O_NEXT = O_BAR + 1016, O_ROLE = O_BAR + 1000, O_PT = O_BAR + 976, O_CM = O_BAR + 1008, O_PERM = O_BAR + 944, O_EP = O_BAR + 1012;
constexpr uint32_t TAGM = 0x00010001u, TAGX = 0x00000001u, TAGZ = 0x00010000u;

constexpr uint16_t LUT_A[11] = {0x3f95, 0x3f92, 0x3f8c, 0x3f83, 0x3f6f, 0x3f53, 0x3f33, 0x3f0f, 0x3ed1, 0x3e7e, 0x3daa};
constexpr uint16_t LUT_B[11] = {0x3fe9, 0x3fe4, 0x3fdb, 0x3fcd, 0x3fbb, 0x3fa5, 0x3f8c, 0x3f60, 0x3f23, 0x3ec7, 0x3e05};
constexpr uint16_t LUT_W[12] = {0x3abb, 0x3ab9, 0x3ab3, 0x3aaa, 0x3a9d, 0x3a8d, 0x3a75, 0x3a4a, 0x3a1b, 0x39d3, 0x3955, 0};
constexpr uint16_t basis(int setb, int f, int a, int sn) {
    if (f < 0 || f > 10 || a < 0 || a > 21) return 0;
    int k = ((2 * f + 1) * (2 * a - 21) - 22 * sn + 88 * 7) % 88;
    if (k > 44) k = 88 - k;
    int neg = 0;
    if (k > 22) { k = 44 - k; neg = 1; }
    return (uint16_t)((setb ? LUT_B[k >> 1] : LUT_A[k >> 1]) | (neg << 15));
}
constexpr uint16_t neg16(uint16_t v) { return v ? (uint16_t)(v ^ 0x8000) : v; }
constexpr uint16_t wcoef(int fw, int fl, int sn, int tap) {
    if (fl > 21) return 0;
    int fh = fl >> 1, kh = tap / 7, kw = tap - 7 * kh;
    int u = (2 * fh + 1) * kh;
    if (fl & 1) u = -u;
    int k = (u + (2 * fw + 1) * kw - 11 * sn + 44 * 4) % 44;
    if (k > 22) k = 44 - k;
    int neg = 0;
    if (k > 11) { k = 22 - k; neg = 1; }
    return (uint16_t)(LUT_W[k] | (neg << 15));
}
struct alignas(128) CTab { uint16_t v[C_BYTES / 2]; };
struct alignas(128) WTab { uint16_t v[WT_BYTES / 2]; };
constexpr CTab make_ctab() {
    CTab t{};
    for (int lane = 0; lane < 32; lane++) {
        int g = lane >> 2, q = lane & 3;
        for (int r = 0; r < 18; r++) {
            int quad = r >> 2, j = r & 3;
            int set = quad < 3 ? quad : (quad == 3 ? 1 + (j >> 1) : 0);
            int sn = (j ^ (set == 0 ? g : g >> 1)) & 1;
            int t8 = quad < 3 ? 1 + (j >> 1) : 0;
            int b = 8 * t8 + 2 * q - 2;
            int fw = set == 0 ? g : (((g & 1) == set - 1) ? 8 + (g >> 1) : -1);
            int o = (C_P1A + (quad * 32 + lane) * 16 + j * 4) / 2;
            t.v[o] = basis(0, fw, b, sn); t.v[o + 1] = basis(0, fw, b + 1, sn);
        }
        for (int r = 0; r < 12; r++) {
            int o = (C_P3 + ((r >> 2) * 32 + lane) * 16 + (r & 3) * 4) / 2;
            if (r < 6) {
                int a = 6 + g + 8 * (r & 1), fh = 4 * (r >> 1) + q;
                t.v[o] = basis(0, fh, a, 0); t.v[o + 1] = basis(0, fh, a, 1);
            } else {
                int be = r < 8 ? r - 6 : (r - 8) >> 1, nu = r < 8 ? 2 : (r & 1);
                int b = 6 + 8 * be + 4 * (g & 1) + (g >> 1);
                t.v[o] = basis(1, 4 * nu + q, b, 0); t.v[o + 1] = basis(1, 4 * nu + q, b, 1);
            }
        }
    }
    for (int kc = 0; kc < 6; kc++)
        for (int nb = 0; nb < 6; nb++)
            for (int n = 0; n < 8; n++)
                for (int k = 0; k < 8; k++) {
                    int nu = kc >> 1, ds = kc & 1, im = nb & 1, fh = 4 * (nb >> 1) + (n >> 1), mi = n & 1;
                    int a = nu == 0 ? 6 + k : (nu == 1 ? 14 + k : (k < 6 ? k : -1));
                    uint16_t v = basis(0, fh, a, ds ^ im);
                    if (ds != im && (im ? mi : !mi)) v = neg16(v);
                    t.v[C_P1B / 2 + ((kc * 6 + nb) * 8 + n) * 8 + k] = v;
                }
    return t;
}
constexpr WTab make_wtab(int fw) {
    WTab t{};
    for (int nb = 0; nb < 6; nb++)
        for (int n = 0; n < 8; n++) {
            for (int tap = 0; tap < 48; tap++) t.v[(((tap >> 3) * 6 + nb) * 8 + n) * 8 + (tap & 7)] = wcoef(fw, 4 * nb + (n >> 1), n & 1, tap);
            t.v[((7 * 6 + nb) * 8 + n) * 8] = wcoef(fw, 4 * nb + (n >> 1), n & 1, 48);
        }
    return t;
}
__device__ const CTab g_ctab = make_ctab();
__device__ const WTab g_wtab[11] = {make_wtab(0), make_wtab(1), make_wtab(2), make_wtab(3), make_wtab(4), make_wtab(5),
                                    make_wtab(6), make_wtab(7), make_wtab(8), make_wtab(9), make_wtab(10)};

__device__ __align__(1024) unsigned char g_S[(size_t)(NPAGE + 1) << 21];
constexpr int CT = 0, CX = 2, CY = 10, CW = 18, CD = 29, CV = 32;
__device__ __align__(512) unsigned g_cnt[40 * 64];

struct Maps {
    const unsigned char* ctab; const unsigned char* wtab; const unsigned char* x; unsigned* cnt; unsigned char* s;
    const unsigned char* wraw;
    alignas(64) CUtensorMap w, ct, x22, x6, x16, wf, s32, s30, p16, p2, y;
};

#define TR(role, i)
#define TRL(role, i)
#define TRC(i)

__device__ __forceinline__ uint32_t s2u(const void* p) { return (uint32_t)__cvta_generic_to_shared(p); }
__device__ __forceinline__ void mbar_init(uint32_t b, int c) { asm volatile("mbarrier.init.shared::cta.b64 [%0],%1;" ::"r"(b), "r"(c) : "memory"); }
__device__ __forceinline__ void mbar_expect(uint32_t b, uint32_t tx) { asm volatile("mbarrier.arrive.expect_tx.shared::cta.b64 _,[%0],%1;" ::"r"(b), "r"(tx) : "memory"); }
__device__ __forceinline__ void mbar_arrive(uint32_t b) { asm volatile("mbarrier.arrive.shared::cta.b64 _,[%0];" ::"r"(b) : "memory"); }
__device__ __forceinline__ bool mbar_try(uint32_t b, uint32_t ph) {
    uint32_t ok;
    asm volatile("{.reg .pred p; mbarrier.try_wait.parity.shared::cta.b64 p,[%1],%2; selp.u32 %0,1,0,p;}" : "=r"(ok) : "r"(b), "r"(ph) : "memory");
    return ok;
}
__device__ __forceinline__ void mbar_wait_ph(uint32_t b, uint32_t ph) {
    if (mbar_try(b, ph)) return;
#pragma unroll 1
    for (int it = 0; it < (1 << 16); it++)
        if (mbar_try(b, ph)) return;
}
__device__ __forceinline__ void mbar_wait(uint32_t b) { mbar_wait_ph(b, 0); }
__device__ __forceinline__ void region_end(uint32_t b) {
    int it = 0;
    while (!mbar_try(b, 0) && ++it < (1 << 16)) {}
}
__device__ __forceinline__ bool mbar_test(uint32_t b) {
    uint32_t ok;
    asm volatile("{.reg .pred p; mbarrier.test_wait.parity.shared::cta.b64 p,[%1],0; selp.u32 %0,1,0,p;}" : "=r"(ok) : "r"(b) : "memory");
    return ok;
}
__device__ __forceinline__ bool elect() {
    uint32_t r;
    asm volatile("{.reg .pred p; elect.sync _|p,0xffffffff; selp.u32 %0,1,0,p;}" : "=r"(r));
    return r;
}
__device__ __forceinline__ uint32_t until(uint32_t t, int nap) {
    uint32_t now = clock();
    while ((int)(now - t) < 0) { if (nap) __nanosleep(nap); now = clock(); }
    return now;
}
__device__ __forceinline__ int bcast(int v, int l) { return __shfl_sync(0xffffffffu, v, l); }
__device__ __forceinline__ void poll(const unsigned* c, unsigned tgt) {
    unsigned v; int it = 0;
    do { asm volatile("ld.acquire.gpu.global.u32 %0,[%1];" : "=r"(v) : "l"(c) : "memory"); } while (v < tgt && ++it < (1 << 16));
}
__device__ __forceinline__ bool bar_any(int id, int n, bool v) {
    uint32_t r;
    asm volatile("{.reg .pred p,q; setp.ne.u32 p,%3,0; bar.red.or.pred q,%1,%2,p; selp.u32 %0,1,0,q;}" : "=r"(r) : "r"(id), "r"(n), "r"((uint32_t)v) : "memory");
    return __any_sync(0xffffffffu, r);
}
__device__ __forceinline__ int laneid() { int l; asm volatile("mov.u32 %0,%%laneid;" : "=r"(l)); return l; }
__device__ __forceinline__ uint32_t lds32(uint32_t a) { uint32_t v; asm volatile("ld.shared.u32 %0,[%1];" : "=r"(v) : "r"(a) : "memory"); return v; }
__device__ __forceinline__ uint32_t lds8(uint32_t a) { uint32_t v; asm volatile("ld.shared.u8 %0,[%1];" : "=r"(v) : "r"(a) : "memory"); return v; }
__device__ __forceinline__ uint32_t tagged(uint32_t v, uint32_t m, uint32_t t) { return (v & ~m) | (t & m); }
__device__ __forceinline__ void red_add(unsigned* c, unsigned v = 1) { asm volatile("red.relaxed.gpu.global.add.u32 [%0],%1;" ::"l"(c), "r"(v) : "memory"); }
__device__ __forceinline__ void pf_l2(const void* p) { asm volatile("prefetch.global.L2 [%0];" ::"l"(p)); }
__device__ __forceinline__ void fence_async_s() { asm volatile("fence.proxy.async.shared::cta;" ::: "memory"); }
__device__ __forceinline__ void fence_async_g() { asm volatile("fence.proxy.async.global;" ::: "memory"); }
__device__ __forceinline__ void bulk_ld(uint32_t dst, const void* src, uint32_t bytes, uint32_t bar) {
    asm volatile("cp.async.bulk.shared::cluster.global.mbarrier::complete_tx::bytes [%0],[%1],%2,[%3];" ::"r"(dst), "l"(src), "r"(bytes), "r"(bar) : "memory");
}
__device__ __forceinline__ void tma_ld2(uint32_t dst, const CUtensorMap* m, uint32_t bar, int c0, int c1) {
    asm volatile("cp.async.bulk.tensor.2d.shared::cluster.global.mbarrier::complete_tx::bytes [%0],[%1,{%3,%4}],[%2];" ::"r"(dst), "l"(m), "r"(bar), "r"(c0), "r"(c1) : "memory");
}
__device__ __forceinline__ void tma_ld3(uint32_t dst, const CUtensorMap* m, uint32_t bar, int c0, int c1, int c2) {
    asm volatile("cp.async.bulk.tensor.3d.shared::cluster.global.mbarrier::complete_tx::bytes [%0],[%1,{%3,%4,%5}],[%2];" ::"r"(dst), "l"(m), "r"(bar), "r"(c0), "r"(c1), "r"(c2) : "memory");
}
__device__ __forceinline__ void tma_ld4(uint32_t dst, const CUtensorMap* m, uint32_t bar, int c0, int c1, int c2, int c3) {
    asm volatile("cp.async.bulk.tensor.4d.shared::cluster.global.mbarrier::complete_tx::bytes [%0],[%1,{%3,%4,%5,%6}],[%2];" ::"r"(dst), "l"(m), "r"(bar), "r"(c0), "r"(c1), "r"(c2), "r"(c3) : "memory");
}
__device__ __forceinline__ void bulk_st(void* dst, uint32_t src, uint32_t bytes) {
    asm volatile("cp.async.bulk.global.shared::cta.bulk_group [%0],[%1],%2;" ::"l"(dst), "r"(src), "r"(bytes) : "memory");
}
__device__ __forceinline__ void tma_ld5(uint32_t dst, const CUtensorMap* m, uint32_t bar, int c0, int c1, int c2, int c3, int c4) {
    asm volatile("cp.async.bulk.tensor.5d.shared::cluster.global.mbarrier::complete_tx::bytes [%0],[%1,{%3,%4,%5,%6,%7}],[%2];" ::"r"(dst), "l"(m), "r"(bar), "r"(c0), "r"(c1), "r"(c2), "r"(c3), "r"(c4) : "memory");
}
__device__ __forceinline__ void tma_st2(const CUtensorMap* m, uint32_t src, int c0, int c1) {
    asm volatile("cp.async.bulk.tensor.2d.global.shared::cta.bulk_group [%0,{%2,%3}],[%1];" ::"l"(m), "r"(src), "r"(c0), "r"(c1) : "memory");
}
__device__ __forceinline__ void tma_st4(const CUtensorMap* m, uint32_t src, int c0, int c1, int c2, int c3) {
    asm volatile("cp.async.bulk.tensor.4d.global.shared::cta.bulk_group [%0,{%2,%3,%4,%5}],[%1];" ::"l"(m), "r"(src), "r"(c0), "r"(c1), "r"(c2), "r"(c3) : "memory");
}
__device__ __forceinline__ void tma_st5(const CUtensorMap* m, uint32_t src, int c0, int c1, int c2, int c3, int c4) {
    asm volatile("cp.async.bulk.tensor.5d.global.shared::cta.bulk_group [%0,{%2,%3,%4,%5,%6}],[%1];" ::"l"(m), "r"(src), "r"(c0), "r"(c1), "r"(c2), "r"(c3), "r"(c4) : "memory");
}
__device__ __forceinline__ void bulk_commit() { asm volatile("cp.async.bulk.commit_group;" ::: "memory"); }
template <int N> __device__ __forceinline__ void bulk_wait() { asm volatile("cp.async.bulk.wait_group %0;" ::"n"(N) : "memory"); }
template <int N> __device__ __forceinline__ void bulk_wait_read() { asm volatile("cp.async.bulk.wait_group.read %0;" ::"n"(N) : "memory"); }
__device__ __forceinline__ void bar_sync(int id, int n) { asm volatile("bar.sync %0,%1;" ::"r"(id), "r"(n) : "memory"); }

__device__ __forceinline__ uint4 lds128(uint32_t a) {
    uint4 v; asm volatile("ld.shared.v4.u32 {%0,%1,%2,%3},[%4];" : "=r"(v.x), "=r"(v.y), "=r"(v.z), "=r"(v.w) : "r"(a)); return v;
}
__device__ __forceinline__ void sts128(uint32_t a, uint32_t x, uint32_t y, uint32_t z, uint32_t w) {
    asm volatile("st.shared.v4.u32 [%0],{%1,%2,%3,%4};" ::"r"(a), "r"(x), "r"(y), "r"(z), "r"(w) : "memory");
}
__device__ __forceinline__ void sts64(uint32_t a, uint32_t x, uint32_t y) { asm volatile("st.shared.v2.u32 [%0],{%1,%2};" ::"r"(a), "r"(x), "r"(y) : "memory"); }
__device__ __forceinline__ void sts128p(uint32_t a, uint32_t x, uint32_t y, uint32_t z, uint32_t w, bool p) {
    asm volatile("{.reg .pred p; setp.ne.u32 p,%5,0; @p st.shared.v4.u32 [%0],{%1,%2,%3,%4};}" ::"r"(a), "r"(x), "r"(y), "r"(z), "r"(w), "r"((uint32_t)p) : "memory");
}
__device__ __forceinline__ void sts32(uint32_t a, uint32_t x) { asm volatile("st.shared.u32 [%0],%1;" ::"r"(a), "r"(x) : "memory"); }
__device__ __forceinline__ uint32_t pk(float lo, float hi) { uint32_t r; asm("cvt.rn.bf16x2.f32 %0,%1,%2;" : "=r"(r) : "f"(hi), "f"(lo)); return r; }

__device__ __forceinline__ uint32_t pkv(float lo, float hi) { uint32_t r; asm volatile("cvt.rn.bf16x2.f32 %0,%1,%2;" : "=r"(r) : "f"(hi), "f"(lo)); return r; }

__device__ __forceinline__ void mma16z(float* d, uint32_t a0, uint32_t a1, uint32_t a2, uint32_t a3, uint32_t b0, uint32_t b1) {
    asm("mma.sync.aligned.m16n8k16.row.col.f32.bf16.bf16.f32 {%0,%1,%2,%3},{%4,%5,%6,%7},{%8,%9},{%10,%10,%10,%10};"
        : "=f"(d[0]), "=f"(d[1]), "=f"(d[2]), "=f"(d[3]) : "r"(a0), "r"(a1), "r"(a2), "r"(a3), "r"(b0), "r"(b1), "f"(0.f));
}
__device__ __forceinline__ void mma16(float* d, uint32_t a0, uint32_t a1, uint32_t a2, uint32_t a3, uint32_t b0, uint32_t b1) {
    asm("mma.sync.aligned.m16n8k16.row.col.f32.bf16.bf16.f32 {%0,%1,%2,%3},{%4,%5,%6,%7},{%8,%9},{%0,%1,%2,%3};"
        : "+f"(d[0]), "+f"(d[1]), "+f"(d[2]), "+f"(d[3]) : "r"(a0), "r"(a1), "r"(a2), "r"(a3), "r"(b0), "r"(b1));
}
__device__ __forceinline__ void mma8(float* d, uint32_t a0, uint32_t a1, uint32_t b0) {
    asm("mma.sync.aligned.m16n8k8.row.col.f32.bf16.bf16.f32 {%0,%1,%2,%3},{%4,%5},{%6},{%0,%1,%2,%3};"
        : "+f"(d[0]), "+f"(d[1]), "+f"(d[2]), "+f"(d[3]) : "r"(a0), "r"(a1), "r"(b0));
}
__device__ __forceinline__ void wg_fence() { asm volatile("wgmma.fence.sync.aligned;" ::: "memory"); }
__device__ __forceinline__ void wg_commit() { asm volatile("wgmma.commit_group.sync.aligned;" ::: "memory"); }
template <int N> __device__ __forceinline__ void wg_wait() { asm volatile("wgmma.wait_group.sync.aligned %0;" ::"n"(N) : "memory"); }
template <int N> __device__ __forceinline__ void pin(float (&d)[N]) {
#pragma unroll
    for (int i = 0; i < N; i++) asm volatile("" : "+f"(d[i])::"memory");
}
#define ACC8(o) "+f"(d[o]), "+f"(d[o + 1]), "+f"(d[o + 2]), "+f"(d[o + 3]), "+f"(d[o + 4]), "+f"(d[o + 5]), "+f"(d[o + 6]), "+f"(d[o + 7])
#define OUT8(o) "=f"(d[o]), "=f"(d[o + 1]), "=f"(d[o + 2]), "=f"(d[o + 3]), "=f"(d[o + 4]), "=f"(d[o + 5]), "=f"(d[o + 6]), "=f"(d[o + 7])
template <int ACC> __device__ __forceinline__ void wgmma48(float (&d)[24], uint32_t a0, uint32_t a1, uint32_t a2, uint32_t a3, uint64_t desc) {
    if (ACC)
        asm volatile("wgmma.mma_async.sync.aligned.m64n48k16.f32.bf16.bf16 "
                     "{%0,%1,%2,%3,%4,%5,%6,%7,%8,%9,%10,%11,%12,%13,%14,%15,%16,%17,%18,%19,%20,%21,%22,%23},{%24,%25,%26,%27},%28,%29,1,1,0;"
                     : ACC8(0), ACC8(8), ACC8(16) : "r"(a0), "r"(a1), "r"(a2), "r"(a3), "l"(desc), "n"(ACC & 1));
    else
        asm volatile("wgmma.mma_async.sync.aligned.m64n48k16.f32.bf16.bf16 "
                     "{%0,%1,%2,%3,%4,%5,%6,%7,%8,%9,%10,%11,%12,%13,%14,%15,%16,%17,%18,%19,%20,%21,%22,%23},{%24,%25,%26,%27},%28,0,1,1,0;"
                     : OUT8(0), OUT8(8), OUT8(16) : "r"(a0), "r"(a1), "r"(a2), "r"(a3), "l"(desc));
}
template <int ACC> __device__ __forceinline__ void wgmma_p2(float (&d)[32], const uint32_t* a, uint64_t desc) {
    if (ACC)
        asm volatile("wgmma.mma_async.sync.aligned.m64n64k16.f32.bf16.bf16 "
                     "{%0,%1,%2,%3,%4,%5,%6,%7,%8,%9,%10,%11,%12,%13,%14,%15,%16,%17,%18,%19,%20,%21,%22,%23,%24,%25,%26,%27,%28,%29,%30,%31},{%32,%33,%34,%35},%36,1,1,1,0;"
                     : ACC8(0), ACC8(8), ACC8(16), ACC8(24) : "r"(a[0]), "r"(a[1]), "r"(a[2]), "r"(a[3]), "l"(desc));
    else
        asm volatile("wgmma.mma_async.sync.aligned.m64n64k16.f32.bf16.bf16 "
                     "{%0,%1,%2,%3,%4,%5,%6,%7,%8,%9,%10,%11,%12,%13,%14,%15,%16,%17,%18,%19,%20,%21,%22,%23,%24,%25,%26,%27,%28,%29,%30,%31},{%32,%33,%34,%35},%36,0,1,1,0;"
                     : OUT8(0), OUT8(8), OUT8(16), OUT8(24) : "r"(a[0]), "r"(a[1]), "r"(a[2]), "r"(a[3]), "l"(desc));
}
template <int ACC> __device__ __forceinline__ void wgmma_p2(float (&d)[4], const uint32_t* a, uint64_t desc) {
    if (ACC)
        asm volatile("wgmma.mma_async.sync.aligned.m64n8k16.f32.bf16.bf16 {%0,%1,%2,%3},{%4,%5,%6,%7},%8,1,1,1,0;"
                     : "+f"(d[0]), "+f"(d[1]), "+f"(d[2]), "+f"(d[3]) : "r"(a[0]), "r"(a[1]), "r"(a[2]), "r"(a[3]), "l"(desc));
    else
        asm volatile("wgmma.mma_async.sync.aligned.m64n8k16.f32.bf16.bf16 {%0,%1,%2,%3},{%4,%5,%6,%7},%8,0,1,1,0;"
                     : "=f"(d[0]), "=f"(d[1]), "=f"(d[2]), "=f"(d[3]) : "r"(a[0]), "r"(a[1]), "r"(a[2]), "r"(a[3]), "l"(desc));
}
__device__ __forceinline__ uint64_t desc_tab(uint32_t a) { return (uint64_t)((a & 0x3FFFF) >> 4) | ((uint64_t)(768 >> 4) << 16) | ((uint64_t)(128 >> 4) << 32); }

__device__ __forceinline__ void staged(uint32_t bar, int lane) {
    fence_async_s();
    __syncwarp();
    if (lane == 0) mbar_arrive(bar);
}

__device__ __forceinline__ void wgen(uint32_t win, uint32_t tab, uint32_t out, int c, int qq, int lane, uint32_t consumed, uint32_t chain, uint32_t gate, uint32_t cma) {
    uint32_t A[28];
    int mi = lane >> 3, rr = lane & 7;
    int L = 12 * (mi & 1) + c;
#pragma unroll
    for (int s = 0; s < 7; s++) {
        int u = s < 6 ? s / 3 : mi >> 1;
        int tap = s < 6 ? 16 * (s % 3) + 8 * (mi >> 1) + rr : 48;
        int line = 3 * tap + (L >> 3);
        uint32_t ad = win + u * WPIECE + line * 128 + (((L ^ line) & 7) << 4);
        asm volatile("ldmatrix.sync.aligned.m8n8.x4.trans.shared.b16 {%0,%1,%2,%3},[%4];"
                     : "=r"(A[4 * s]), "=r"(A[4 * s + 1]), "=r"(A[4 * s + 2]), "=r"(A[4 * s + 3]) : "r"(ad));
    }
    float d0[24], d1[24];
    uint64_t ds = desc_tab(tab);
    wg_fence();
    wgmma48<0>(d0, A[0], A[1], A[2], A[3], ds);
    wgmma48<0>(d1, A[12], A[13], A[14], A[15], ds);
    wgmma48<1>(d0, A[4], A[5], A[6], A[7], ds + 96);
    wgmma48<1>(d1, A[16], A[17], A[18], A[19], ds + 96);
    wgmma48<1>(d0, A[8], A[9], A[10], A[11], ds + 192);
    wgmma48<1>(d1, A[20], A[21], A[22], A[23], ds + 192);
    wgmma48<1>(d0, A[24], A[25], A[26], A[27], ds + 336);
    wgmma48<1>(d1, A[24], A[25], A[26], A[27], ds + 288);
    wg_commit();
    if (lane == 0) { if (chain) mbar_arrive(chain); mbar_arrive(consumed); }
    mbar_wait(gate);
    const uint32_t tag = ~lds32(cma);
    wg_wait<0>();
    pin(d0); pin(d1);
    int g = lane >> 2, q = lane & 3;
    const uint32_t p = out + q * 512 + (8 * (c & 3) + (g ^ (2 * (q ^ qq)))) * 16;
#pragma unroll
    for (int nb = 0; nb < 6; nb++)
        if (nb < 5 || q < 2)
            sts128(p + nb * 2048, pk(d0[4 * nb], d0[4 * nb + 2]), pk(d0[4 * nb + 1], d0[4 * nb + 3]), pk(d1[4 * nb], d1[4 * nb + 2]),
                   tagged(pk(d1[4 * nb + 1], d1[4 * nb + 3]), g == 7, tag));
}

__device__ __forceinline__ void p1_unit(uint32_t blk, uint32_t out, uint32_t cst, uint32_t full, int wg, int wq, int lane) {
    int g = lane >> 2, q = lane & 3;
    uint32_t T[20];
#pragma unroll
    for (int v = 0; v < 5; v++) { uint4 x = lds128(cst + C_P1A + (v * 32 + lane) * 16); T[4 * v] = x.x; T[4 * v + 1] = x.y; T[4 * v + 2] = x.z; T[4 * v + 3] = x.w; }
    uint32_t P[6][3][4];
    const uint32_t a0 = blk + g * 512 + (2 * q + (g & 1)) * 64 + ((wq ^ q) << 4), a1 = a0 ^ 64;
    const uint32_t sel0 = (g & 1) ? 0x1054 : 0x5410, sel1 = sel0 + 0x2222;
    uint32_t vv[2][3][2][4];
    auto ldv = [&](int nu) {
        const int ro = (nu == 0 ? 6 : (nu == 1 ? 14 : 0)) * 512;
#pragma unroll
        for (int t = 0; t < 3; t++)
#pragma unroll
            for (int e = 0; e < 2; e++) {
                uint4 x = lds128((e ? a1 : a0) + t * 11264 + ro);
                vv[nu & 1][t][e][0] = x.x; vv[nu & 1][t][e][1] = x.y; vv[nu & 1][t][e][2] = x.z; vv[nu & 1][t][e][3] = x.w;
            }
    };
    mbar_wait(full);
    ldv(0);
#pragma unroll
    for (int nu = 0; nu < 3; nu++) {
        if (nu < 2) ldv(nu + 1);
        auto& v = vv[nu & 1];
#pragma unroll
        for (int ch = 0; ch < 4; ch++) {
            const uint32_t sel = (ch & 1) ? sel1 : sel0;
            uint32_t b[2][3];
#pragma unroll
            for (int hf = 0; hf < 2; hf++)
#pragma unroll
                for (int t = 0; t < 3; t++) b[hf][t] = __byte_perm(v[t][0][(ch >> 1) + 2 * hf], v[t][1][(ch >> 1) + 2 * hf], sel);
            float d1[4];
            mma16z(d1, T[12], T[13], T[14], T[15], b[0][0], b[1][0]);
#pragma unroll
            for (int hf = 0; hf < 2; hf++) {
                float d0[4];
                mma16z(d0, T[0], T[1], T[2], T[3], b[hf][1], b[hf][2]);
                mma8(d0, T[16], T[17], b[hf][0]);
                mma16(d1, T[4 + 4 * hf], T[5 + 4 * hf], T[6 + 4 * hf], T[7 + 4 * hf], b[hf][1], b[hf][2]);
                P[(ch >> 1) + 2 * hf][nu][ch & 1] = pk(d0[0], d0[1]);
                P[(ch >> 1) + 2 * hf][nu][2 + (ch & 1)] = pk(d0[2], d0[3]);
            }
            P[4 + (ch >> 1)][nu][ch & 1] = pk(d1[0], d1[1]);
            P[4 + (ch >> 1)][nu][2 + (ch & 1)] = pk(d1[2], d1[3]);
        }
#pragma unroll
        for (int pb = 0; pb < 6; pb++) asm volatile("" : "+r"(P[pb][nu][0]), "+r"(P[pb][nu][1]), "+r"(P[pb][nu][2]), "+r"(P[pb][nu][3]));
                if (SPLIT >> nu & 1) region_end(cst + (O_BAR - O_C) + 8 * BC);
    }
    const uint64_t ds = desc_tab(cst + C_P1B);
    float dA[24], dB[24];
    auto issue = [&](int pb) {
        wg_fence();
        if (pb == 4) {
            wgmma48<0>(dA, P[pb][0][0], P[pb][0][1], P[pb][0][2], P[pb][0][3], ds);
            wgmma48<0>(dB, P[pb + 1][0][0], P[pb + 1][0][1], P[pb + 1][0][2], P[pb + 1][0][3], ds);
        } else {
            wgmma48<2>(dA, P[pb][0][0], P[pb][0][1], P[pb][0][2], P[pb][0][3], ds);
            wgmma48<2>(dB, P[pb + 1][0][0], P[pb + 1][0][1], P[pb + 1][0][2], P[pb + 1][0][3], ds);
        }
        wgmma48<1>(dA, P[pb][1][0], P[pb][1][1], P[pb][1][2], P[pb][1][3], ds + 96);
        wgmma48<1>(dB, P[pb + 1][1][0], P[pb + 1][1][1], P[pb + 1][1][2], P[pb + 1][1][3], ds + 96);
        wgmma48<1>(dA, P[pb][2][0], P[pb][2][1], P[pb][2][2], P[pb][2][3], ds + 192);
        wgmma48<1>(dB, P[pb + 1][2][0], P[pb + 1][2][1], P[pb + 1][2][2], P[pb + 1][2][3], ds + 192);
        wg_commit();
    };
    issue(4);
    bar_sync(1 + wg, 128);
    asm volatile("" : "+r"(g), "+r"(q));
    wg_wait<0>(); pin(dA); pin(dB);
    uint32_t o[12][2];
#pragma unroll
    for (int k = 0; k < 12; k++) { const int i = 4 * (k >> 1) + (k & 1); o[k][0] = pkv(dA[i], dA[i + 2]); o[k][1] = pkv(dB[i], dB[i + 2]); }
    issue(0);
    {
        const int sw = (g >> 1) & 1, r0 = 2 * (lds8(cst + (O_PERM - O_C) + (g < 6 ? 8 + (g >> 1) : 1)) * 11 + q) + sw;
        const uint32_t a0 = out + r0 * 128 + ((((4 * sw + wq) ^ r0) & 7) << 4) + 8 * (g & 1);
        const uint32_t m = wq == 3 && (g & 1) ? TAGM : 0, m0 = sw ? m : 0, m1 = m ^ m0;
#pragma unroll
        for (int k = 11; k >= 0; k--) {
            sts64((a0 ^ ((k & 2) * 72 + (k & 1) * 64)) + 1024 * (k >> 2), o[k][0], tagged(o[k][1], (k & 1) ? m1 : m0, TAGX));
            if (k == 8) __syncwarp();
        }
    }
    wg_wait<0>(); pin(dA); pin(dB);
#pragma unroll
    for (int k = 0; k < 12; k++) { const int i = 4 * (k >> 1) + (k & 1); o[k][0] = pkv(dA[i], dA[i + 2]); o[k][1] = pkv(dB[i], dB[i + 2]); }
    issue(2);
    region_end(cst + (O_BAR - O_C) + 8 * BC);
    const int r0 = 2 * (lds8(cst + (O_PERM - O_C) + g) * 11 + q) + (g & 1);
    const uint32_t ao = out + r0 * 128 + ((((4 * (g & 1) + wq) ^ r0) & 7) << 4);
    const uint32_t m = wq == 3 ? TAGM : 0, m0 = (g & 1) ? m : 0, m1 = m ^ m0;
    wg_wait<0>(); pin(dA); pin(dB);
#pragma unroll
    for (int k = 0; k < 12; k++) {
        const int i = 4 * (k >> 1) + (k & 1);
        sts128p((ao ^ ((k & 2) * 72 + (k & 1) * 64)) + 1024 * (k >> 2), o[k][0], o[k][1], pk(dA[i], dA[i + 2]),
                tagged(pk(dB[i], dB[i + 2]), (k & 1) ? m1 : m0, TAGX), k < 8 || q < 3);
    }
}

template <int NB, class F>
__device__ __forceinline__ void p2_step(const uint32_t (&Wf)[48], uint32_t in, uint32_t a0, uint32_t m, uint32_t t, uint32_t bar, int lane, int wg, int s, F meanwhile) {
    float dp[4 * NB], dm[4 * NB];
    const uint32_t lo = ((in & 0x3FFFF) >> 4) | (1u << 16);
    auto desc = [&](int o) { return (uint64_t)(lo + o) | ((uint64_t)(1024 >> 4) << 32) | (1ull << 62); };
    if (NB > 1 && (wg || s > 1)) bar_sync(4 + wg, 256);
    wg_fence();
    wgmma_p2<0>(dp, &Wf[0], desc(0));
    wgmma_p2<0>(dm, &Wf[24], desc(4));
#pragma unroll
    for (int ks = 1; ks < 6; ks++) {
        wgmma_p2<1>(dp, &Wf[4 * ks], desc((ks >> 1) * NB * 64 + (ks & 1) * 2));
        wgmma_p2<1>(dm, &Wf[24 + 4 * ks], desc((ks >> 1) * NB * 64 + (ks & 1) * 2 + 4));
    }
    wg_commit();
    if (NB > 1 && (wg < 2 || s < 6)) asm volatile("bar.arrive %0,256;" ::"r"(wg == 2 ? 4 : 5 + wg) : "memory");
    meanwhile();
    mbar_wait_ph(bar + 8 * (s < 2 ? BD1 + 1 : BDP + 2 * wg + (s & 1)), s >= 2 ? ((s >> 1) & 1) ^ 1 : 0);
    wg_wait<0>();
    pin(dp); pin(dm);
    if (NB > 1 && s < 6 && lane == 0) mbar_arrive(bar + 8 * (BPE + s));
    uint32_t v[2 * NB];
#pragma unroll
    for (int nb = 0; nb < NB; nb++) {
        float pr = dp[4 * nb] - dp[4 * nb + 3], pi = dp[4 * nb + 1] + dp[4 * nb + 2];
        float mr = dm[4 * nb] - dm[4 * nb + 3], mi = dm[4 * nb + 1] + dm[4 * nb + 2];
        v[2 * nb] = tagged(pk(pr + mr, pi - mi), m, t);
        v[2 * nb + 1] = tagged(pk(pi + mi, mr - pr), m, t);
        if (nb & 1)
            asm volatile("stmatrix.sync.aligned.m8n8.x4.trans.shared.b16 [%0],{%1,%2,%3,%4};" ::"r"(a0 + (nb - 1) * 1024), "r"(v[2 * nb - 2]), "r"(v[2 * nb - 1]),
                         "r"(v[2 * nb]), "r"(v[2 * nb + 1]) : "memory");
    }
    if (NB == 1) asm volatile("stmatrix.sync.aligned.m8n8.x2.trans.shared.b16 [%0],{%1,%2};" ::"r"(a0), "r"(v[0]), "r"(v[1]) : "memory");
}

__device__ __forceinline__ bool p3_unit(uint32_t blk, uint32_t cst, uint32_t full, uint32_t ph, int wg, int wq, int lane) {
    int g = lane >> 2, q = lane & 3;
    uint32_t T[12];
#pragma unroll
    for (int v = 0; v < 3; v++) { uint4 x = lds128(cst + C_P3 + (v * 32 + lane) * 16); T[4 * v] = x.x; T[4 * v + 1] = x.y; T[4 * v + 2] = x.z; T[4 * v + 3] = x.w; }
    uint32_t ad[3][2];
#pragma unroll
    for (int nu = 0; nu < 3; nu++) {
        const int pos = lds8(cst + (O_PERM - O_C) + min(4 * nu + (g >> 1), 10));
#pragma unroll
        for (int ka = 0; ka < 2; ka++) {
            int r = 2 * (pos * 11 + (ka ? min(8 + q, 10) : q)) + (g & 1);
            ad[nu][ka] = blk + r * 128 + ((((2 * wq) ^ r) & 7) << 4);
        }
    }
    mbar_wait_ph(full, ph);
    uint32_t o[2][4][4], bad = 0, P[8][3][2];
#pragma unroll
    for (int nu = 0; nu < 3; nu++) {
        uint32_t z[3][2][4];
#pragma unroll
        for (int ka = 0; ka < 3; ka++)
#pragma unroll
            for (int h = 0; h < 2; h++) {
                uint4 x = lds128((ad[nu][ka >> 1] ^ (h << 4)) + (ka & 1) * 1024);
                z[ka][h][0] = x.x; z[ka][h][1] = x.y; z[ka][h][2] = x.z; z[ka][h][3] = x.w;
                if (h) bad |= x.w ^ TAGZ;
            }
#pragma unroll
        for (int ch = 0; ch < 8; ch++) {
            const uint32_t sel = (ch & 1) ? 0x7632 : 0x5410;
            float d[4];
            mma16z(d, T[0], T[1], T[2], T[3], __byte_perm(z[0][0][ch >> 1], z[0][1][ch >> 1], sel), __byte_perm(z[1][0][ch >> 1], z[1][1][ch >> 1], sel));
            mma8(d, T[4], T[5], __byte_perm(z[2][0][ch >> 1], z[2][1][ch >> 1], sel));
            P[ch][nu][0] = pk(d[0], d[1]); P[ch][nu][1] = pk(d[2], d[3]);
        }
    }
    if (bar_any(1 + wg, 128, wq == 3 && (bad & TAGM))) return false;
#pragma unroll
    for (int j = 0; j < 4; j++) {
        float d2[2][2][4];
#pragma unroll
        for (int e = 0; e < 2; e++)
#pragma unroll
            for (int be = 0; be < 2; be++) {
                const int ch = 2 * j + e;
                mma16z(d2[e][be], P[ch][0][0], P[ch][0][1], P[ch][1][0], P[ch][1][1], T[8 + 2 * be], T[9 + 2 * be]);
                mma8(d2[e][be], P[ch][2][0], P[ch][2][1], T[6 + be]);
            }
#pragma unroll
        for (int be = 0; be < 2; be++)
#pragma unroll
            for (int k = 0; k < 4; k++) o[be][k][j] = pk(d2[0][be][k], d2[1][be][k]);
    }
    const int p = 4 * g + q;
    const uint32_t a = blk + p * 64 + ((wq ^ ((p >> 1) & 3)) << 4);
#pragma unroll
    for (int be = 0; be < 2; be++)
#pragma unroll
        for (int k = 0; k < 4; k++)
            sts128(a + (2 * be + (k & 1)) * 4096 + (k >> 1) * 2048, o[be][k][0], o[be][k][1], o[be][k][2], o[be][k][3]);
    return true;
}

template <int Z> __device__ __forceinline__ int s_row(int gr, int st, int cg, int ci, unsigned cm) {
    const int sf = (ci >> 2) & 1, y = 3 * (3 * gr + cg) + ((st ^ sf) << (Z ^ (cm >> 31))), pg = y >> 2;
    const int r = (pg << 14) | ((ci & 1) << 6) | ((ci & 2) << 8) | ((y & 1) << 10) | ((y & 2) << 11);
    return r | ((((Z ? st : sf) ^ ci ^ (ci >> 1) ^ y ^ (y >> 1) ^ (cm >> pg)) & 1) << 5);
}
__device__ __forceinline__ int w_row(int fw, int hg, int cg, int io, unsigned cm) {
    const int home = fw == 5 ? hg >> 1 : fw > 5;
    const int col = fw == 5 ? 15 + (hg & 1) : 3 * (fw > 5 ? fw - 6 : fw) + hg;
    const int z = 9 * col + 3 * cg + io, pg = NPS + (z >> 5);
    const int r = (pg << 12) | ((z & 1) << 4) | ((z & 6) << 6) | ((z & 24) << 7);
    return r | (((home ^ __popc(z & 15) ^ (cm >> pg)) & 1) << 3);
}
__device__ __forceinline__ int s_tile(int t) { return ((t & 3) << 7) | ((t & 4) << 9) | ((t & 8) << 10); }
__device__ __forceinline__ int xoff(int r) { return r < 3 ? O_B0 + r * BLK : (r == 3 ? O_B4 : O_B3); }
__device__ __forceinline__ int soff(int r) { return r == 2 ? O_B2 + 2048 : xoff(r); }
__device__ __forceinline__ int zoff(int r) { return r == 0 ? O_B2 + 2048 : (r == 1 ? O_B3 : (r == 2 ? O_B4 : (r == 3 ? O_Z3 : O_Z4))); }

struct Role1 {
    int sd, k, nu;
    __device__ __forceinline__ Role1(int cta) {
        sd = cta >= NH; k = cta - sd * NH;
        if (k < 60) k = (k >> 1) + ((k & 1) ? 0 : 30);
        nu = k < NUH - 4 * NH ? 5 : 4;
    }
};
struct Role {
    int sd, k, fp, nu;
    __device__ __forceinline__ Role(int rho) {
        sd = rho >= NH;
        const int kk = sd ? NCTA - 1 - rho : rho;
        k = NH - 1 - kk;
        nu = k < NUH - 4 * NH ? 5 : 4;
        fp = k >= 5 + sd ? 60 * sd + k - 5 : -1;
    }
};
__device__ __forceinline__ int stage_row(const Role& R, int s, int lane, unsigned cm, int z) {
    const int ci = R.fp > 0 ? (R.fp - 1) / 15 : 0, rw = 2 * (ci ? R.fp - 15 * ci - 1 : R.fp);
    return (z ? s_row<1>(s, lane & 1, lane >> 1, ci, cm) : s_row<0>(s, lane & 1, lane >> 1, ci, cm)) + rw + (s ? 0 : s_tile(14));
}
__device__ __forceinline__ int stage_off(int s, int lane) { return (lane >> 1) * 8192 + (lane & 1) * (s ? 4096 : 512); }
template <int Z, class RT> __device__ __forceinline__ int unit_row(const RT& R, int r, int lane, unsigned cm) {
    const int u = r * NH + R.k, ts = u / 3;
    return s_row<Z>((ts + 14) >> 4, R.sd, u - 3 * ts, lane, cm) + s_tile(ts + 14);
}
__device__ __forceinline__ int unit_off(int lane) { return lane ? 3840 * lane + 256 : 0; }

__global__ void __launch_bounds__(512, 1) fftconv_kernel(const __grid_constant__ Maps mp) {
    extern __shared__ __align__(1024) unsigned char smraw[];
    const uint32_t sm = s2u(smraw);
    const uint32_t bar = sm + O_BAR;
    const int tid = threadIdx.x, lane = tid & 31;
    const uint32_t tstart = clock();
    if (tid >= 480) {
        if (elect()) {
            const int c = blockIdx.x, ip = c % 12, pr = 3 * (8 * (ip >> 1) + 2 * (ip & 1));
#pragma unroll
            for (int i = 0; i < 8; i++) mbar_init(bar + 8 * i, 1);
            mbar_expect(bar + 8 * BW, 2 * 18816 + WT_BYTES);
            TR(3, 18);
            tma_ld3(sm + O_W0, &mp.w, bar + 8 * BW, 0, pr, 0);
            tma_ld3(sm + O_W0 + WPIECE, &mp.w, bar + 8 * BW, 0, pr + 12, 0);
            bulk_ld(sm + O_WT, mp.wtab + (c / 12) * WT_BYTES, WT_BYTES, bar + 8 * BW);
            asm volatile("prefetch.tensormap [%0];" ::"l"(&mp.x22) : "memory");
            TR(3, 19);
        }
        __syncwarp();
        asm volatile("bar.arrive 9,64;\n bar.arrive 0,288;" ::: "memory");
    }
    if (tid < 128) {
        const int c = blockIdx.x, vp = min(c & 31, NPAGE - 2);
        const int r0 = 94 + (c & 1) + ((c >> 1) << 7);
        const int r1 = ((vp + 1) << 14) + 94 + ((c >> 5) & 1) + ((c >> 6) << 7) + (vp < NPS - 1 ? 0 : ((0xA151 >> (5 * (vp - NPS + 1))) & 31) << 9);
        unsigned* a = reinterpret_cast<unsigned*>(mp.s) + ((tid & 64 ? r1 : r0) + (tid & 32)) * 32 + lane;
        const bool on = tid < 64 || (c & 31) < NPAGE - 1;
        if (on) *a = 0;
        bar_sync(10, 128);
        TR(5, 18);
        unsigned t = 0;
        if (on) asm volatile("{.reg .u32 v; .reg .pred p;\n atom.relaxed.gpu.global.exch.b32 v,[%1],1;\n setp.eq.u32 p,v,0;\n @p mov.u32 %0,%%clock;}" : "+r"(t) : "l"(a) : "memory");
        if (lane == 0) sts32(sm + O_PT + (tid >> 3), t);
        bar_sync(10, 128);
        const uint4 tt = lds128(sm + O_PT);
        const int far = (((int)(tt.x - tt.y) > 0) ^ __popc(r0 & 0x1640)) & 1;
        TR(5, 19);
        if (lane == 0 && (tid == 32 || (tid == 64 && on))) {
            const int i = tid == 32 ? 20 + c / 12 : vp, v = tid == 32 ? far : (far ^ ((int)(tt.z - tt.w) > 0) ^ __popc(r1 & 0x1640)) & 1;
            red_add(mp.cnt + 64 * (CV + (i & 7)), 1u << ((i & 24) + 4 * v));
        }
        if (tid == 0) sts32(sm + O_ROLE, far);
        __syncwarp();
        bar_sync(11, 160);
        if (tid == 0) mbar_arrive(bar + 8 * (BRL + 1));
        __syncwarp();
    }
    const int warp = __shfl_sync(0xffffffffu, tid >> 5, 0);
    int cta;
    asm volatile("mov.u32 %0,%%ctaid.x;" : "=r"(cta));
    const int wip = cta % 12;
    const Role1 X(cta);

    if (warp >= 12) {
        asm volatile("setmaxnreg.dec.sync.aligned.u32 32;");
        if (warp & 1) bar_sync(warp, 64);
        if (warp == 12) {
            TR(7, 4);
            const int p = lane & 15, top = lane >> 4, r = p / 3, t = p - 3 * r;
            const int u = r * NH + X.k, ts = u / 3, tr = ts / 14, th = 7 * X.sd + tr, tw = ts - 14 * tr;
            const bool w1 = p == 15, ct = lane == 30;
            const int xc = w1 || ct ? 0 : 32 * (u - 3 * ts);
            const int xw = ct ? 0 : (w1 ? 3 * (8 * (wip >> 1) + 2 * (wip & 1) + 4 * top + 1) : (t || tw ? 16 * tw - 8 + 8 * t : 216));
            const int xh = w1 || ct ? 0 : (th ? 16 * th - 6 : (top ? 218 : 0));
            const uint32_t xd = sm + (ct ? O_C : (w1 ? O_W1 + top * WPIECE : xoff(r) + t * 11264 + (th || top ? 0 : 3072)));
            const uint32_t xb = bar + 8 * (ct ? BC : (w1 ? BW + 1 : BX + r));
            const CUtensorMap* xm = ct ? &mp.ct : (w1 ? &mp.w : (th ? &mp.x22 : (top ? &mp.x6 : &mp.x16)));
            const int xp = ct ? 0 : (w1 ? 1 : (top && th ? -1 : p + 2));
            bar_sync(9, 64);
            if (lane < 3 + X.nu && lane != BW) mbar_expect(bar + 8 * lane, lane >= BX ? BLK : (lane ? 2 * 18816 : C_BYTES));
            __syncwarp();
            TR(3, 20);
            uint32_t due = tstart + XD0;
            auto loads = [&](int i0, int i1) {
#pragma unroll 1
                for (int i = i0; i < i1; i++) {
                    if (xp == i) tma_ld3(xd, xm, xb, xc, xw, xh);
                    __syncwarp();
                    if (i % 3 == 1) TR(3, 21 + i / 3);
                    until(due, 0);
                    due += i < X0N ? XE : XD;
                }
            };
            loads(0, 11);
            bar_sync(12, 64);
            mbar_wait(bar + 8 * (BWC + 1));
            loads(11, 14);
            if (X.nu == 5) { mbar_wait(bar + 8 * BDW); loads(14, 17); }
        } else if (warp == 13) {
            mbar_wait(bar + 8 * (BRL + 1));
            if (lane == 0) {
                const unsigned far = lds32(sm + O_ROLE), t = atomicAdd(mp.cnt + 64 * (CT + far), 1u);
                sts32(sm + O_ROLE, far ? NCTA - 1 - t : t);
                mbar_arrive(bar + 8 * BRL);
            }
            __syncwarp();
            TR(5, 20);
        } else if (warp == 14) {
            TR(7, 5);
            unsigned par, vote = 0;
            asm volatile("ld.relaxed.gpu.global.u32 %0,[%1];" : "=r"(par) : "l"(mp.cnt + 64 * (CV + (cta & 7)) + 1) : "memory");
            unsigned cm; int pos;
#pragma unroll 1
            for (int it = 0; it < (1 << 16); it++) {
                cm = (__ballot_sync(0xffffffffu, lane < 20 && (vote >> 4) > (vote & 15)) << 1);
                const unsigned gm = 0x7ff00000u, lo = __ballot_sync(0xffffffffu, vote < 64) & gm, hi = __ballot_sync(0xffffffffu, vote >= 144) & gm, mid = gm ^ lo ^ hi;
                const unsigned below = (1u << lane) - 1;
                pos = vote < 64 ? __popc(lo & below) : (vote < 144 ? __popc(lo) + __popc(mid & below) : 11 - __popc(hi) + __popc(hi & below));
                asm volatile("" : "+r"(cm), "+r"(pos));
                if (it < 5) TR(7, 22 + it);
                if (!__any_sync(0xffffffffu, lane < 31 && (vote & 15) + (vote >> 4) < (lane < 4 ? 5u : (lane < 20 ? 4u : 12u)))) break;
                if (it == 0) {
                    bar_sync(14, 64);
                    if (lane == 0) { sts32(sm + O_EP, par); mbar_arrive(bar + 8 * BEP); }
                    until(tstart + VT, 0);
                }
                asm volatile("ld.acquire.gpu.global.u8 %0,[%1];" : "=r"(vote) : "l"(reinterpret_cast<unsigned char*>(mp.cnt + 64 * (CV + (lane & 7))) + (lane >> 3)) : "memory");
            }
            if (lane >= 20 && lane < 31) asm volatile("st.shared.u8 [%0],%1;" ::"r"(sm + O_PERM + lane - 20), "r"(pos) : "memory");
            __syncwarp();
            if (lane == 0) { sts32(sm + O_CM, cm | (par << 31)); mbar_arrive(bar + 8 * BCM); }
            __syncwarp();
            TR(5, 22);
        }
        auto role = [&]() { mbar_wait(bar + 8 * BRL); return Role(bcast(lds32(sm + O_ROLE), 0)); };

        if (warp == 12) {
            const Role R = role();
            if (R.fp >= 0) {
                mbar_wait(bar + 8 * BCM);
                const unsigned cm = lds32(sm + O_CM);
                if (lane < 7) mbar_expect(bar + 8 * (BPF + lane), lane ? STG : 3072);
                mbar_wait(bar + 8 * (BIS + 2));
                const int v0 = stage_row(R, lane >> 3, lane & 7, cm, 0), v1 = stage_row(R, 4 + (lane >> 3), lane & 7, cm, 0);
                uint32_t dst = sm + O_S0, seen = 0;
#pragma unroll 1
                for (int s = 0; s < 7; s++) {
                    int row[6];
#pragma unroll
                    for (int i = 0; i < 6; i++) row[i] = bcast(s < 4 ? v0 : v1, 8 * s + i);
                    const CUtensorMap* m = s ? &mp.p16 : &mp.p2;
                    const uint32_t hs = s ? 4096 : 512;
                    for (int it = 0; !(seen >> s & 1) && it < (1 << 16); it++) {
                        unsigned v = 0;
                        if (lane == s || (s >= WIN && lane > s && lane < 7)) asm volatile("ld.acquire.gpu.global.u32 %0,[%1];" : "=r"(v) : "l"(mp.cnt + 64 * (CX + lane)) : "memory");
                        seen = __ballot_sync(0xffffffffu, v >= (lane ? 96u : 12u));
                    }
                    TR(5, s);
                    mbar_wait(bar + 8 * (s > 3 ? BPE + s - 3 : (s ? BWE + s - 1 : BD1)));
                    if (elect()) {
#pragma unroll
                        for (int i = 0; i < 6; i++) tma_ld5(dst + i * hs, m, bar + 8 * (BPF + s), 0, row[i], 0, 0, 0);
                    }
                    __syncwarp();
                    dst = dst >= sm + O_IN + 2 * STG ? sm + O_IN : dst + STG;
                    TR(3, 3 + s);
                }
            }
        } else if (warp == 13) {
            const Role R = role();
            mbar_wait(bar + 8 * BCM);
            if (R.fp >= 0) {
                const unsigned cm = lds32(sm + O_CM);
                if (lane < 3) mbar_expect(bar + 8 * (BWF + lane), STG);
                const int fw = R.fp / 11;
                {
                    const int fh = R.fp - 11 * fw, b = lane / 3, io = lane - 3 * b;
                    const int row = w_row(fw, fh >> 2, b, io, cm) + 2 * (fh & 3);
                    mbar_wait(bar + 8 * (BDW + 1));
                    poll(mp.cnt + 64 * (CW + fw), 12);
                    TR(3, 17);
                    const uint32_t t0 = clock();
#pragma unroll 1
                    for (int i = 0; i < 9; i++) {
                        if (i == 6) mbar_wait(bar + 8 * BD1);
                        until(t0 + i * LPW, NAP);
                        if (lane == i) tma_ld4(sm + O_IN + lane * 8192, &mp.wf, bar + 8 * (BWF + b), 0, row, 0, 0);
                        __syncwarp();
                    }
                    TR(3, 15);
                }
                {
                    const int row = stage_row(R, 0, lane & 7, cm, lane < 8);
                    mbar_wait(bar + 8 * BR2); mbar_wait(bar + 8 * (BR2 + 2)); mbar_wait(bar + 8 * (BR2 + 4));
                    TR(4, 7);
                    if (lane < 6 || (R.fp == 15 && lane < 14 && (lane & 9) == 9)) tma_st5(&mp.p2, sm + O_OUT + stage_off(0, lane & 7), 0, row, 0, 0, 0);
                    __syncwarp();
                    bulk_commit(); bulk_wait_read<0>();
                    __syncwarp();
                    if (lane < 4) mbar_arrive(bar + 8 * (lane < 3 ? BDP + 2 * lane : BI2));
                    if (lane == 0) red_add(mp.cnt + 64 * CY);
                    __syncwarp();
                }
            }
            if (lane < R.nu) mbar_expect(bar + 8 * (BZ + lane), SLAB);
            const int v = unit_row<1>(R, lane >> 1, 4 * (lane & 1), lds32(sm + O_CM));
            mbar_wait(bar + 8 * (BD1 + X.nu - 2)); mbar_wait(bar + 8 * (BD1 + X.nu - 1));
#pragma unroll 1
            for (int r = 0; r < R.nu; r++) {
                const int r0 = bcast(v, 2 * r), r1 = bcast(v, 2 * r + 1), gr = (r * NH + R.k + 42) / 48;
                const uint32_t dst = sm + zoff(r), fb = bar + 8 * (BZ + r);
                if (R.fp >= 0) {
                    if (r >= 3) { mbar_wait(bar + 8 * (r == 3 ? BPE + 4 : BD2)); mbar_wait(bar + 8 * (r == 3 ? BPE + 5 : BD2 + 1)); }
                    mbar_wait(bar + 8 * (BI2 + gr));
                }
                poll(mp.cnt + 64 * (CY + gr), NFP);
                TR(5, 8 + r);
                if (elect()) {
#pragma unroll
                    for (int i = 0; i < 8; i++)
                        tma_ld2(dst + unit_off(i), i ? &mp.s30 : &mp.s32, fb, 0, (i < 4 ? r0 : r1) ^ (((i & 1) * 96) ^ ((i & 2) * 272)));
                }
                __syncwarp();
                TR(3, 10 + r);
            }
            if (R.fp >= 0) mbar_wait(bar + 8 * (BPF + 6));
            unsigned last = 0;
            if (lane == 0) last = atomicAdd(mp.cnt + 64 * CD, 1u) == NCTA - 1;
            if (__shfl_sync(0xffffffffu, last, 0)) {
                mp.cnt[64 * lane] = 0;
                if (lane < 16) mp.cnt[64 * (CV + (lane >> 1)) + (lane & 1)] = (lane & 1) ? lds32(sm + O_EP) ^ 1 : 0;
            }
        } else {
            const int me = warp & 1;
            uint32_t next = tstart + T0;
            auto pace = [&](int cost) {
                const uint32_t now = until(next, NAP);
                next = ((int)(now - next) > CREDIT ? now - CREDIT : next) + cost;
            };
            const int bal = X.nu == 5 ? BAL : (256 * 875 - BAL * 431) / 445;
            mbar_wait(bar + 8 * BCM);
            const unsigned cm = __shfl_sync(0xffffffffu, lds32(sm + O_CM), 0);
            {
                const int iq = 2 * wip + me, w = lane / 3, hg = lane - 3 * w, wfw = lds8(sm + O_PERM + cta / 12);
                unsigned char* dst = mp.s + (size_t)w_row(wfw, hg, w, iq >> 3, cm) * 512 + ((iq & 3) << 14) + ((iq & 4) << 16);
                const uint32_t src = sm + (me ? O_W0 : O_B3) + w * 11264 + hg * 4096;
                if (me) { mbar_wait(bar + 8 * BIS); next = lds32(sm + O_NEXT); }
#pragma unroll 1
                for (int i = 0; i < 3; i++) {
                    mbar_wait(bar + 8 * (BRW + 3 * me + i));
                    if (i == 0) TR(4, me);
                    pace((RW * 11 / 4 * bal) >> 8);
                    if (w == i) bulk_st(dst, src, hg < 2 ? 4096 : 3072);
                    __syncwarp();
                }
                if (lane == 0) { sts32(sm + O_NEXT, next); mbar_arrive(bar + 8 * (BIS + me)); if (EARLY == 2 - me) red_add(mp.cnt + 64 * (CW + wfw)); }
                bulk_commit(); bulk_wait<0>();
                __syncwarp();
                if (lane == 0) { if (me && EARLY == 0) red_add(mp.cnt + 64 * (CW + wfw)); mbar_arrive(bar + 8 * (BDW + me)); }
                TR(6, me);
            }
            const int vu = unit_row<0>(X, lane >> 1, 4 * (lane & 1), cm);
            const Role R = role();
            const int first = (X.nu ^ me) & 1;
            int v, vx;
            { const int n = first + (lane & 30), s = n / 3, l = 2 * (n - 3 * s) + (lane & 1); v = stage_row(R, s + 1, l, cm, 1); vx = stage_row(R, s + 1, l, cm, 0); }
            asm volatile("" : "+r"(v), "+r"(vx));
#pragma unroll 1
            for (int j = me; j < X.nu; j += 2) {
                const int r0 = bcast(vu, 2 * j), r1 = bcast(vu, 2 * j + 1), cost = ((j < 2 ? R1A : R1) * 121 / 64 * bal) >> 8;
                const uint32_t src = sm + soff(j);
                unsigned* cn = mp.cnt + 64 * (CX + (j * NH + X.k + 42) / 48);
                mbar_wait(bar + 8 * (BR1 + j));
                mbar_wait(bar + 8 * (BIS + 1 + j));
                next = lds32(sm + O_NEXT);
                TR(4, 2 + j);
                if (elect()) {
                    if (EARLY == 2) red_add(cn);
#pragma unroll
                    for (int i = 0; i < 4; i++) {
                        const int x = ((i & 1) * 96) ^ ((i & 2) * 272);
                        pace(cost);
                        tma_st2(i ? &mp.s30 : &mp.s32, src + unit_off(i), 0, r0 ^ x);
                        tma_st2(i || X.sd ? &mp.s30 : &mp.s32, src + unit_off(4 + i), 0, r1 ^ x);
                    }
                    sts32(sm + O_NEXT, next); mbar_arrive(bar + 8 * (BIS + 2 + j));
                    if (EARLY == 1) red_add(cn);
                    bulk_commit(); bulk_wait_read<0>();
                    if (EARLY == 0) red_add(cn);
                    mbar_arrive(bar + 8 * (BD1 + j));
                }
                __syncwarp();
                TR(6, j + 2);
            }
            if (R.fp >= 0) {
                mbar_wait(bar + 8 * (BIS + 1 + X.nu));
                next = lds32(sm + O_NEXT) + first * 2 * R2;
                uint32_t prev = 0;
                int s = 1, w = first;
#pragma unroll 1
                for (int i = 0; i < 18; i += 2) {
                    const int r0 = bcast(v, i), r1 = bcast(v, i + 1), rx = bcast(vx, i + 1);
                    const int bi = 2 * w + (s & 1);
                    const uint32_t src = sm + O_OUT + (s & 1) * STG + w * 8192;
                    mbar_wait_ph(bar + 8 * (BR2 + bi), (s >> 1) & 1);
                    const uint32_t now = until(next, NAP);
                    next = ((int)(now - next) > CREDIT2 ? now - CREDIT2 : next) + 4 * R2;
                    if (w == 0) TR(4, 7 + s);
                    if (elect()) {
                        tma_st5(&mp.p16, src, 0, r0, 0, 0, 0);
                        tma_st5(&mp.p16, src + 4096, 0, r1, 0, 0, 0);
                        if (R.fp == 15) tma_st5(&mp.p16, src + 4096, 0, rx, 0, 0, 0);
                        bulk_commit();
                        bulk_wait_read<1>();
                        if (prev) mbar_arrive(prev);
                        if (w == 2) { if (LATE2) bulk_wait_read<0>(); red_add(mp.cnt + 64 * (CY + s)); mbar_arrive(bar + 8 * (BI2 + s)); }
                    }
                    __syncwarp();
                    if (w == 2) TR(6, 7 + s);
                    prev = bar + 8 * (BDP + bi);
                    w += 2; if (w > 2) { w -= 3; s++; }
                }
                if (elect()) { bulk_wait_read<0>(); mbar_arrive(bar + 8 * (BD2 + me)); }
                __syncwarp();
                next = clock() + YD;
            }
#pragma unroll 1
            for (int r = me; r < R.nu; r += 2) {
                const int u = r * NH + R.k, ts = u / 3, cg = u - 3 * ts, tr = ts / 14, th = 7 * R.sd + tr, tw = ts - 14 * tr;
                mbar_wait(bar + 8 * (BR3 + r));
                if (r && r < 3) { mbar_wait(bar + 8 * (BIS + 6 + r)); next = lds32(sm + O_NEXT); }
                TR(4, 14 + r);
#pragma unroll 1
                for (int c = 0; c < 2; c++) {
                    if (r < 3) pace(2 * R3);
                    if (elect()) tma_st4(&mp.y, sm + zoff(r) + c * 8192, 32 * cg, 0, 16 * th, 4 * tw + 2 * c);
                    __syncwarp();
                }
                if (lane == 0 && r < 2) { sts32(sm + O_NEXT, next); mbar_arrive(bar + 8 * (BIS + 7 + r)); }
                __syncwarp();
            }
            bulk_commit(); bulk_wait_read<0>();
            TR(4, 19 + me);
        }
    } else {
        if (warp >= 4) {
            if (elect()) {
                const int gi = warp - 3;
#pragma unroll
                for (int i = 0; i < 8; i++) mbar_init(bar + 64 * gi + 8 * i, gi < 8 ? 1 : 12);
                if (gi < 5) {
#pragma unroll
                    for (int i = 0; i < 8; i++) mbar_init(bar + 64 * (gi + 8) + 8 * i, 4);
                }
            }
            __syncwarp();
            bar_sync(0, 288);
            if (warp < 9) asm volatile("bar.arrive %0,%1;" ::"r"(warp + 7), "r"(warp == 4 ? 160 : 64) : "memory");
            else if (warp == 10 && lane < 8) asm volatile("prefetch.tensormap [%0];" ::"l"(&mp.x6 + lane) : "memory");
            __syncwarp();
            if (warp == 4) TR(7, 3);
        }
        asm volatile("setmaxnreg.inc.sync.aligned.u32 160;");
        const int lane = laneid();
        const int wg = __shfl_sync(0xffffffffu, tid >> 7, 0), wq = __shfl_sync(0xffffffffu, tid >> 5, 0) & 3;
        const int pw = wg ? wg - 1 : 2;
#pragma unroll 1
        for (int it = 0; it <= pw; it++) {
            const int j = it > 0, cg = j ? pw + it - 2 : pw;
            mbar_wait(bar + 8 * (j == 0 && pw ? BWL + pw - 1 : BW + j));
            TR(wg, 24 + 2 * it);
            wgen(sm + (j ? O_W1 : O_W0), sm + O_WT, sm + (j ? O_W0 : O_B3) + cg * 11264, 4 * cg + wq, (2 * wip + j) & 3, lane, bar + 8 * (BWC + j),
                 j == 0 && pw < 2 ? bar + 8 * (BWL + pw) : 0, bar + 8 * (j ? BWC : BEP), sm + O_EP);
            staged(bar + 8 * (BRW + 3 * j + cg), lane);
            TR(wg, 25 + 2 * it);
        }
        mbar_wait(bar + 8 * BC); mbar_wait(bar + 8 * BCM);
#pragma unroll 1
        for (int r = pw; r < X.nu; r += 3) {
            p1_unit(sm + xoff(r), sm + soff(r), sm + O_C, bar + 8 * (BX + r), wg, wq, laneid());
            staged(bar + 8 * (BR1 + r), laneid());
            TR(wg, 2 + 2 * (r / 3));
        }
        mbar_wait(bar + 8 * BRL);
        const Role R(__shfl_sync(0xffffffffu, lds32(sm + O_ROLE), 0));
        uint32_t phw = 0;
        if (R.fp >= 0) {
            const int lane = laneid();
            uint32_t Wf[48];
            const int g = lane >> 2, q = lane & 3;
            {
                const int b = wg;
                const uint32_t p = sm + O_IN + b * STG + q * 1024 + wq * 128 + ((g ^ (2 * q) ^ (4 * ((R.fp % 11) & 1))) << 4);
                mbar_wait(bar + 8 * (BWF + b));
                TR(wg, 5);
#pragma unroll 1
                for (int it = 0; it < 4096; it++) {
                    const uint32_t tag = ~lds32(sm + O_CM) >> 31, m = g == 7;
                    uint32_t bad = 0;
#pragma unroll
                    for (int i = 0; i < 12; i++) {
                        uint4 v = lds128((p ^ (i >= 6 ? 544 : 0)) + (i % 6) * 4096);
                        Wf[4 * i] = v.x; Wf[4 * i + 1] = v.y; Wf[4 * i + 2] = v.z; Wf[4 * i + 3] = v.w & ~m;
                        bad |= v.w ^ tag;
                    }
                    if (!bar_any(1 + wg, 128, bad & m)) break;
                    if (wq == 0) {
                        TRC(2);
                        fence_async_s();
                        if (lane == 0) mbar_expect(bar + 8 * (BRT + 1 + wg), STG);
                        __syncwarp();
                        const int l = laneid(), fp = Role(lds32(sm + O_ROLE)).fp, fw = fp / 11, fh = fp - 11 * fw;
                        if (l < 3) tma_ld4(sm + O_IN + b * STG + l * 8192, &mp.wf, bar + 8 * (BRT + 1 + wg), 0, w_row(fw, fh >> 2, wg, l, lds32(sm + O_CM)) + 2 * (fh & 3), 0, 0);
                        __syncwarp();
                    }
                    mbar_wait_ph(bar + 8 * (BRT + 1 + wg), phw); phw ^= 1;
                }
                staged(bar + 8 * (BWE + b), lane);
            }
            const int ro = (lane & 6) + ((lane >> 3) & 1);
            const uint32_t o0 = sm + O_OUT + wg * 8192 + (lane >> 4) * 1024 + ro * 128 + (((2 * wq + (lane & 1)) ^ ro) << 4);
            const uint32_t m = wq == 3 && g >= 6 ? 0x10000 : 0, tg = g == 6 ? TAGZ << 16 : TAGZ;
            uint32_t ph = 0;
            const int t = 32 * wq + lane;
            uint32_t c0 = t * 128 + ((7 ^ (t & 7)) << 4) + 12, c1 = (c0 & 8191) + 16384;
            auto stale = [&](uint32_t in) { return (((lds32(in + c0) ^ TAGX) | (lds32(in + c1) ^ TAGX)) & TAGM) != 0; };
            auto landed = [&](int s, uint32_t in) {
                mbar_wait(bar + 8 * (BPF + s));
#pragma unroll 1
                for (int it = 0; it < 4096; it++) {
                    if (!bar_any(1 + wg, 128, stale(in))) break;
                    fence_async_s();
                    bar_sync(7, 384);
                    if (wg + wq == 0) {
                        TRC(0);
                        if (lane == 0) mbar_expect(bar + 8 * BRT, s ? STG : 3072);
                        __syncwarp();
                        const int l = laneid();
                        if (l < 6) tma_ld5(in + l * (s ? 4096 : 512), s ? &mp.p16 : &mp.p2, bar + 8 * BRT, 0, stage_row(Role(lds32(sm + O_ROLE)), s, l, lds32(sm + O_CM), 0), 0, 0, 0);
                        __syncwarp();
                    }
                    mbar_wait_ph(bar + 8 * BRT, ph); ph ^= 1;
                }
            };
            mbar_wait(bar + 8 * BD1);
            c0 &= 2047; c1 = (c1 & 1023) + 2048;
            landed(0, sm + O_S0);
            p2_step<1>(Wf, sm + O_S0, o0, m, tg, bar, lane, wg, 0, []() {});
            staged(bar + 8 * (BR2 + 2 * wg), lane);
            TR(wg, 6);
            c0 |= t << 7; c1 = (c0 & 8191) + 16384;
            uint32_t in = sm + O_IN;
            bool todo = true;
#pragma unroll 1
            for (int s = 1; s < 7; s++) {
                if (todo) landed(s, in);
                const uint32_t nx = in == sm + O_IN + 2 * STG ? sm + O_IN : in + STG;
                p2_step<8>(Wf, in, o0 + (s & 1) * STG, m, tg, bar, lane, wg, s, [&]() { todo = !mbar_test(bar + 8 * (BPF + s + 1)) || stale(nx); });
                todo = bar_any(1 + wg, 128, todo);
                in = nx;
                staged(bar + 8 * (BR2 + 2 * wg + (s & 1)), lane);
                TR(wg, 6 + s);
            }
        }
#pragma unroll 1
        for (int r = wg; r < R.nu; r += 3) {
#pragma unroll 1
            for (int it = 0; it < 4096; it++) {
                if (p3_unit(sm + zoff(r), sm + O_C, bar + 8 * (it ? BRT + 1 + wg : BZ + r), it ? phw ^ 1 : 0, wg, wq, laneid())) break;
                if (wq == 0) {
                    TRC(1);
                    fence_async_s();
                    if (laneid() == 0) mbar_expect(bar + 8 * (BRT + 1 + wg), SLAB);
                    __syncwarp();
                    const int l = laneid();
                    if (l < 8) tma_ld2(sm + zoff(r) + unit_off(l), l ? &mp.s30 : &mp.s32, bar + 8 * (BRT + 1 + wg), 0, unit_row<1>(Role(lds32(sm + O_ROLE)), r, l, lds32(sm + O_CM)));
                    __syncwarp();
                }
                phw ^= 1;
            }
            staged(bar + 8 * (BR3 + r), laneid());
            TR(wg, 14 + 2 * (r / 3));
        }
    }
}

typedef CUresult (*EncFn)(CUtensorMap*, CUtensorMapDataType, cuuint32_t, void*, const cuuint64_t*, const cuuint64_t*, const cuuint32_t*,
                          const cuuint32_t*, CUtensorMapInterleave, CUtensorMapSwizzle, CUtensorMapL2promotion, CUtensorMapFloatOOBfill);

void enc(EncFn f, CUtensorMap* m, void* p, int rank, const cuuint64_t* dims, const cuuint64_t* strides, const cuuint32_t* box,
         CUtensorMapSwizzle sw, CUtensorMapL2promotion pr = CU_TENSOR_MAP_L2_PROMOTION_NONE) {
    cuuint32_t es[5] = {1, 1, 1, 1, 1};
    f(m, CU_TENSOR_MAP_DATA_TYPE_BFLOAT16, rank, p, dims, strides, box, es, CU_TENSOR_MAP_INTERLEAVE_NONE, sw, pr, CU_TENSOR_MAP_FLOAT_OOB_FILL_NONE);
}

}

extern "C" void kernel_launch(void* const* d_in, const int* in_sizes, int n_in, void* d_out, int out_size) {
    void* fn = nullptr; cudaDriverEntryPointQueryResult qr;
    cudaGetDriverEntryPoint("cuTensorMapEncodeTiled", &fn, cudaEnableDefault, &qr);
    EncFn f = (EncFn)fn;
    void* pS; cudaGetSymbolAddress(&pS, g_S);
    pS = (void*)(((uintptr_t)pS + (1u << 21) - 1) & ~(uintptr_t)((1u << 21) - 1));
    Maps mp;
    cudaGetSymbolAddress((void**)&mp.ctab, g_ctab); cudaGetSymbolAddress((void**)&mp.wtab, g_wtab); cudaGetSymbolAddress((void**)&mp.cnt, g_cnt);
    mp.s = (unsigned char*)pS; mp.x = (const unsigned char*)d_in[0]; mp.wraw = (const unsigned char*)d_in[1];
    { cuuint64_t d[4] = {256, NPAGE << 12, 4, 2}, s[3] = {512, 1 << 14, 1 << 18}; cuuint32_t b[4] = {256, 2, 4, 2}; enc(f, &mp.wf, pS, 4, d, s, b, CU_TENSOR_MAP_SWIZZLE_NONE); }
    {
        cuuint64_t d[3] = {96, 224, 224}, s[2] = {192, 43008};
        cuuint32_t b6[3] = {32, 8, 6}, b16[3] = {32, 8, 16}, b22[3] = {32, 8, 22};
        enc(f, &mp.x22, d_in[0], 3, d, s, b22, CU_TENSOR_MAP_SWIZZLE_64B, CU_TENSOR_MAP_L2_PROMOTION_L2_128B);
        enc(f, &mp.x6, d_in[0], 3, d, s, b6, CU_TENSOR_MAP_SWIZZLE_64B, CU_TENSOR_MAP_L2_PROMOTION_L2_128B);
        enc(f, &mp.x16, d_in[0], 3, d, s, b16, CU_TENSOR_MAP_SWIZZLE_64B, CU_TENSOR_MAP_L2_PROMOTION_L2_128B);
    }
    { cuuint64_t d[4] = {96, 4, 224, 56}, s[3] = {192, 43008, 768}; cuuint32_t b[4] = {32, 4, 16, 2}; enc(f, &mp.y, d_out, 4, d, s, b, CU_TENSOR_MAP_SWIZZLE_64B); }
    {
        cuuint64_t d[2] = {64, NPAGE << 14}, s[1] = {128};
        cuuint32_t b32[2] = {64, 32}, b30[2] = {64, 30};
        enc(f, &mp.s32, pS, 2, d, s, b32, CU_TENSOR_MAP_SWIZZLE_128B);
        enc(f, &mp.s30, pS, 2, d, s, b30, CU_TENSOR_MAP_SWIZZLE_128B);
    }
    {
        cuuint64_t d[5] = {64, NPAGE << 14, 4, 2, 2}, s[4] = {128, 1 << 14, 1 << 18, 1 << 20};
        cuuint32_t b16[5] = {64, 2, 4, 2, 2}, b2[5] = {64, 2, 2, 1, 1};
        enc(f, &mp.p16, pS, 5, d, s, b16, CU_TENSOR_MAP_SWIZZLE_128B);
        enc(f, &mp.p2, pS, 5, d, s, b2, CU_TENSOR_MAP_SWIZZLE_128B);
    }
    { cuuint64_t d[3] = {64, C_BYTES / 128, 1}, s[2] = {128, C_BYTES}; cuuint32_t b[3] = {64, C_BYTES / 128, 1}; enc(f, &mp.ct, (void*)mp.ctab, 3, d, s, b, CU_TENSOR_MAP_SWIZZLE_NONE); }
    { cuuint64_t d[3] = {64, 144, 49}, s[2] = {128, 18432}; cuuint32_t b[3] = {64, 3, 49}; enc(f, &mp.w, d_in[1], 3, d, s, b, CU_TENSOR_MAP_SWIZZLE_128B); }
    cudaFuncSetAttribute(fftconv_kernel, cudaFuncAttributeMaxDynamicSharedMemorySize, SMEM);
    fftconv_kernel<<<NCTA, 512, SMEM>>>(mp);
}
```

```cpp
#include <cuda_runtime.h>
#include <cuda_bf16.h>
#include <cuda.h>
#include <stdint.h>

namespace {

constexpr int RW = 260;
constexpr int R1A = 338;
constexpr int R1 = 283;
constexpr int R2 = 245;
constexpr int R3 = 280;
constexpr int BAL = 248;
constexpr int CREDIT = 350;
constexpr int CREDIT2 = 1500;
constexpr int YD = 500;
constexpr int LATE2 = 400;
constexpr int XD0 = 1900;
constexpr int XE = 300;
constexpr int XD1 = 3400;
constexpr int XD = 600;
constexpr int LPW = 250;
constexpr int VT = 1900;
constexpr int NAP = 30;
constexpr int WIN = 4;

constexpr int NCTA = 132, NH = 66;
constexpr int NUH = 294;
constexpr int NFP = 121;
constexpr int BLK = 33792;
constexpr int SLAB = 242 * 128;
constexpr int WPIECE = 19456;
constexpr int STG = 24576;
constexpr int NPS = 16, NPAGE = 21;
constexpr int O_B4 = 0, O_B0 = 87040, O_B2 = O_B0 + 2 * BLK, O_B3 = O_B0 + 3 * BLK;
constexpr int O_W1 = 0, O_W0 = 2 * WPIECE, O_WT = 4 * WPIECE;
constexpr int O_IN = 33792, O_OUT = O_IN + 3 * STG, O_Z3 = O_IN, O_S0 = O_OUT + 4096, O_Z4 = 124928;
constexpr int O_C = 222208, O_BAR = 230912, SMEM = 232448;
constexpr int C_P1A = 0, C_P1B = 2560, C_P3 = 7168, C_BYTES = 8704, WT_BYTES = 6912;
constexpr int BC = 0, BW = 1, BX = 3, BZ = 8, BWF = 13, BPF = 16, BCM = 23, BDW = 24, BD1 = 26, BDP = 31, BD2 = 37, BIS = 39, BEP = 50, BI2 = 51, BRT = 58, BRL = 62;
constexpr int BPE = 64, BWC = 70;
constexpr int BR2 = 72, BRW = 78, BWL = 84, BR1 = 86, BR3 = 91, BWE = 96;
constexpr int O_NEXT = O_BAR + 1016, O_ROLE = O_BAR + 1000, O_PT = O_BAR + 976, O_CM = O_BAR + 1008, O_PERM = O_BAR + 944, O_EP = O_BAR + 1012;
constexpr uint32_t TAGM = 0x00010001u, TAGX = 0x00000001u, TAGZ = 0x00010000u;

constexpr uint16_t LUT_A[11] = {0x3f95, 0x3f92, 0x3f8c, 0x3f83, 0x3f6f, 0x3f53, 0x3f33, 0x3f0f, 0x3ed1, 0x3e7e, 0x3daa};
constexpr uint16_t LUT_B[11] = {0x3fe9, 0x3fe4, 0x3fdb, 0x3fcd, 0x3fbb, 0x3fa5, 0x3f8c, 0x3f60, 0x3f23, 0x3ec7, 0x3e05};
constexpr uint16_t LUT_W[12] = {0x3abb, 0x3ab9, 0x3ab3, 0x3aaa, 0x3a9d, 0x3a8d, 0x3a75, 0x3a4a, 0x3a1b, 0x39d3, 0x3955, 0};
constexpr uint16_t basis(int setb, int f, int a, int sn) {
    if (f < 0 || f > 10 || a < 0 || a > 21) return 0;
    int k = ((2 * f + 1) * (2 * a - 21) - 22 * sn + 88 * 7) % 88;
    if (k > 44) k = 88 - k;
    int neg = 0;
    if (k > 22) { k = 44 - k; neg = 1; }
    return (uint16_t)((setb ? LUT_B[k >> 1] : LUT_A[k >> 1]) | (neg << 15));
}
constexpr uint16_t neg16(uint16_t v) { return v ? (uint16_t)(v ^ 0x8000) : v; }
constexpr uint16_t wcoef(int fw, int fl, int sn, int tap) {
    if (fl > 21) return 0;
    int fh = fl >> 1, kh = tap / 7, kw = tap - 7 * kh;
    int u = (2 * fh + 1) * kh;
    if (fl & 1) u = -u;
    int k = (u + (2 * fw + 1) * kw - 11 * sn + 44 * 4) % 44;
    if (k > 22) k = 44 - k;
    int neg = 0;
    if (k > 11) { k = 22 - k; neg = 1; }
    return (uint16_t)(LUT_W[k] | (neg << 15));
}
struct alignas(128) CTab { uint16_t v[C_BYTES / 2]; };
struct alignas(128) WTab { uint16_t v[WT_BYTES / 2]; };
constexpr CTab make_ctab() {
    CTab t{};
    for (int lane = 0; lane < 32; lane++) {
        int g = lane >> 2, q = lane & 3;
        for (int r = 0; r < 18; r++) {
            int quad = r >> 2, j = r & 3;
            int set = quad < 3 ? quad : (quad == 3 ? 1 + (j >> 1) : 0);
            int sn = (j ^ (set == 0 ? g : g >> 1)) & 1;
            int t8 = quad < 3 ? 1 + (j >> 1) : 0;
            int b = 8 * t8 + 2 * q - 2;
            int fw = set == 0 ? g : (((g & 1) == set - 1) ? 8 + (g >> 1) : -1);
            int o = (C_P1A + (quad * 32 + lane) * 16 + j * 4) / 2;
            t.v[o] = basis(0, fw, b, sn); t.v[o + 1] = basis(0, fw, b + 1, sn);
        }
        for (int r = 0; r < 12; r++) {
            int o = (C_P3 + ((r >> 2) * 32 + lane) * 16 + (r & 3) * 4) / 2;
            if (r < 6) {
                int a = 6 + g + 8 * (r & 1), fh = 4 * (r >> 1) + q;
                t.v[o] = basis(0, fh, a, 0); t.v[o + 1] = basis(0, fh, a, 1);
            } else {
                int be = r < 8 ? r - 6 : (r - 8) >> 1, nu = r < 8 ? 2 : (r & 1);
                int b = 6 + 8 * be + 4 * (g & 1) + (g >> 1);
                t.v[o] = basis(1, 4 * nu + q, b, 0); t.v[o + 1] = basis(1, 4 * nu + q, b, 1);
            }
        }
    }
    for (int kc = 0; kc < 6; kc++)
        for (int nb = 0; nb < 6; nb++)
            for (int n = 0; n < 8; n++)
                for (int k = 0; k < 8; k++) {
                    int nu = kc >> 1, ds = kc & 1, im = nb & 1, fh = 4 * (nb >> 1) + (n >> 1), mi = n & 1;
                    int a = nu == 0 ? 6 + k : (nu == 1 ? 14 + k : (k < 6 ? k : -1));
                    uint16_t v = basis(0, fh, a, ds ^ im);
                    if (ds != im && (im ? mi : !mi)) v = neg16(v);
                    t.v[C_P1B / 2 + ((kc * 6 + nb) * 8 + n) * 8 + k] = v;
                }
    return t;
}
constexpr WTab make_wtab(int fw) {
    WTab t{};
    for (int nb = 0; nb < 6; nb++)
        for (int n = 0; n < 8; n++) {
            for (int tap = 0; tap < 48; tap++) t.v[(((tap >> 3) * 6 + nb) * 8 + n) * 8 + (tap & 7)] = wcoef(fw, 4 * nb + (n >> 1), n & 1, tap);
            t.v[((7 * 6 + nb) * 8 + n) * 8] = wcoef(fw, 4 * nb + (n >> 1), n & 1, 48);
        }
    return t;
}
__device__ const CTab g_ctab = make_ctab();
__device__ const WTab g_wtab[11] = {make_wtab(0), make_wtab(1), make_wtab(2), make_wtab(3), make_wtab(4), make_wtab(5),
                                    make_wtab(6), make_wtab(7), make_wtab(8), make_wtab(9), make_wtab(10)};

__device__ __align__(1024) unsigned char g_S[(size_t)(NPAGE + 1) << 21];
constexpr int CT = 0, CX = 2, CY = 10, CW = 18, CD = 29, CV = 32;
__device__ __align__(512) unsigned g_cnt[40 * 64];

struct Maps {
    const unsigned char* ctab; const unsigned char* wtab; unsigned* cnt; unsigned char* s;
    alignas(64) CUtensorMap w, x22, x6, x16, wf, s32, s30, p16, p2, y;
};

__device__ __forceinline__ uint32_t s2u(const void* p) { return (uint32_t)__cvta_generic_to_shared(p); }
__device__ __forceinline__ void mbar_init(uint32_t b, int c) { asm volatile("mbarrier.init.shared::cta.b64 [%0],%1;" ::"r"(b), "r"(c) : "memory"); }
__device__ __forceinline__ void mbar_expect(uint32_t b, uint32_t tx) { asm volatile("mbarrier.arrive.expect_tx.shared::cta.b64 _,[%0],%1;" ::"r"(b), "r"(tx) : "memory"); }
__device__ __forceinline__ void mbar_arrive(uint32_t b) { asm volatile("mbarrier.arrive.shared::cta.b64 _,[%0];" ::"r"(b) : "memory"); }
__device__ __forceinline__ bool mbar_try(uint32_t b, uint32_t ph) {
    uint32_t ok;
    asm volatile("{.reg .pred p; mbarrier.try_wait.parity.shared::cta.b64 p,[%1],%2; selp.u32 %0,1,0,p;}" : "=r"(ok) : "r"(b), "r"(ph) : "memory");
    return ok;
}
__device__ __forceinline__ void mbar_wait_ph(uint32_t b, uint32_t ph) {
    if (mbar_try(b, ph)) return;
#pragma unroll 1
    for (int it = 0; it < (1 << 16); it++)
        if (mbar_try(b, ph)) return;
}
__device__ __forceinline__ void mbar_wait(uint32_t b) { mbar_wait_ph(b, 0); }
__device__ __forceinline__ void region_end(uint32_t b) {
    int it = 0;
    while (!mbar_try(b, 0) && ++it < (1 << 16)) {}
}
__device__ __forceinline__ bool mbar_test(uint32_t b) {
    uint32_t ok;
    asm volatile("{.reg .pred p; mbarrier.test_wait.parity.shared::cta.b64 p,[%1],0; selp.u32 %0,1,0,p;}" : "=r"(ok) : "r"(b) : "memory");
    return ok;
}
__device__ __forceinline__ bool elect() {
    uint32_t r;
    asm volatile("{.reg .pred p; elect.sync _|p,0xffffffff; selp.u32 %0,1,0,p;}" : "=r"(r));
    return r;
}
__device__ __forceinline__ uint32_t until(uint32_t t, int nap) {
    uint32_t now = clock();
    while ((int)(now - t) < 0) { if (nap) __nanosleep(nap); now = clock(); }
    return now;
}
__device__ __forceinline__ int bcast(int v, int l) { return __shfl_sync(0xffffffffu, v, l); }
__device__ __forceinline__ void poll(const unsigned* c, unsigned tgt) {
    unsigned v; int it = 0;
    do { asm volatile("ld.acquire.gpu.global.u32 %0,[%1];" : "=r"(v) : "l"(c) : "memory"); } while (v < tgt && ++it < (1 << 16));
}
__device__ __forceinline__ bool bar_any(int id, int n, bool v) {
    uint32_t r;
    asm volatile("{.reg .pred p,q; setp.ne.u32 p,%3,0; bar.red.or.pred q,%1,%2,p; selp.u32 %0,1,0,q;}" : "=r"(r) : "r"(id), "r"(n), "r"((uint32_t)v) : "memory");
    return __any_sync(0xffffffffu, r);
}
__device__ __forceinline__ int laneid() { int l; asm volatile("mov.u32 %0,%%laneid;" : "=r"(l)); return l; }
__device__ __forceinline__ uint32_t lds32(uint32_t a) { uint32_t v; asm volatile("ld.shared.u32 %0,[%1];" : "=r"(v) : "r"(a) : "memory"); return v; }
__device__ __forceinline__ uint32_t lds8(uint32_t a) { uint32_t v; asm volatile("ld.shared.u8 %0,[%1];" : "=r"(v) : "r"(a) : "memory"); return v; }
__device__ __forceinline__ uint32_t tagged(uint32_t v, uint32_t m, uint32_t t) { return (v & ~m) | (t & m); }
__device__ __forceinline__ void red_add(unsigned* c, unsigned v = 1) { asm volatile("red.relaxed.gpu.global.add.u32 [%0],%1;" ::"l"(c), "r"(v) : "memory"); }
__device__ __forceinline__ void fence_async_s() { asm volatile("fence.proxy.async.shared::cta;" ::: "memory"); }
__device__ __forceinline__ void bulk_ld(uint32_t dst, const void* src, uint32_t bytes, uint32_t bar) {
    asm volatile("cp.async.bulk.shared::cluster.global.mbarrier::complete_tx::bytes [%0],[%1],%2,[%3];" ::"r"(dst), "l"(src), "r"(bytes), "r"(bar) : "memory");
}
__device__ __forceinline__ void tma_ld2(uint32_t dst, const CUtensorMap* m, uint32_t bar, int c0, int c1) {
    asm volatile("cp.async.bulk.tensor.2d.shared::cluster.global.mbarrier::complete_tx::bytes [%0],[%1,{%3,%4}],[%2];" ::"r"(dst), "l"(m), "r"(bar), "r"(c0), "r"(c1) : "memory");
}
__device__ __forceinline__ void tma_ld3(uint32_t dst, const CUtensorMap* m, uint32_t bar, int c0, int c1, int c2) {
    asm volatile("cp.async.bulk.tensor.3d.shared::cluster.global.mbarrier::complete_tx::bytes [%0],[%1,{%3,%4,%5}],[%2];" ::"r"(dst), "l"(m), "r"(bar), "r"(c0), "r"(c1), "r"(c2) : "memory");
}
__device__ __forceinline__ void tma_ld4(uint32_t dst, const CUtensorMap* m, uint32_t bar, int c0, int c1, int c2, int c3) {
    asm volatile("cp.async.bulk.tensor.4d.shared::cluster.global.mbarrier::complete_tx::bytes [%0],[%1,{%3,%4,%5,%6}],[%2];" ::"r"(dst), "l"(m), "r"(bar), "r"(c0), "r"(c1), "r"(c2), "r"(c3) : "memory");
}
__device__ __forceinline__ void bulk_st(void* dst, uint32_t src, uint32_t bytes) {
    asm volatile("cp.async.bulk.global.shared::cta.bulk_group [%0],[%1],%2;" ::"l"(dst), "r"(src), "r"(bytes) : "memory");
}
__device__ __forceinline__ void tma_ld5(uint32_t dst, const CUtensorMap* m, uint32_t bar, int c0, int c1, int c2, int c3, int c4) {
    asm volatile("cp.async.bulk.tensor.5d.shared::cluster.global.mbarrier::complete_tx::bytes [%0],[%1,{%3,%4,%5,%6,%7}],[%2];" ::"r"(dst), "l"(m), "r"(bar), "r"(c0), "r"(c1), "r"(c2), "r"(c3), "r"(c4) : "memory");
}
__device__ __forceinline__ void tma_st2(const CUtensorMap* m, uint32_t src, int c0, int c1) {
    asm volatile("cp.async.bulk.tensor.2d.global.shared::cta.bulk_group [%0,{%2,%3}],[%1];" ::"l"(m), "r"(src), "r"(c0), "r"(c1) : "memory");
}
__device__ __forceinline__ void tma_st4(const CUtensorMap* m, uint32_t src, int c0, int c1, int c2, int c3) {
    asm volatile("cp.async.bulk.tensor.4d.global.shared::cta.bulk_group [%0,{%2,%3,%4,%5}],[%1];" ::"l"(m), "r"(src), "r"(c0), "r"(c1), "r"(c2), "r"(c3) : "memory");
}
__device__ __forceinline__ void tma_st5(const CUtensorMap* m, uint32_t src, int c0, int c1, int c2, int c3, int c4) {
    asm volatile("cp.async.bulk.tensor.5d.global.shared::cta.bulk_group [%0,{%2,%3,%4,%5,%6}],[%1];" ::"l"(m), "r"(src), "r"(c0), "r"(c1), "r"(c2), "r"(c3), "r"(c4) : "memory");
}
__device__ __forceinline__ void bulk_commit() { asm volatile("cp.async.bulk.commit_group;" ::: "memory"); }
template <int N> __device__ __forceinline__ void bulk_wait_read() { asm volatile("cp.async.bulk.wait_group.read %0;" ::"n"(N) : "memory"); }
__device__ __forceinline__ void bar_sync(int id, int n) { asm volatile("bar.sync %0,%1;" ::"r"(id), "r"(n) : "memory"); }

__device__ __forceinline__ uint4 lds128(uint32_t a) {
    uint4 v; asm volatile("ld.shared.v4.u32 {%0,%1,%2,%3},[%4];" : "=r"(v.x), "=r"(v.y), "=r"(v.z), "=r"(v.w) : "r"(a)); return v;
}
__device__ __forceinline__ void sts128(uint32_t a, uint32_t x, uint32_t y, uint32_t z, uint32_t w) {
    asm volatile("st.shared.v4.u32 [%0],{%1,%2,%3,%4};" ::"r"(a), "r"(x), "r"(y), "r"(z), "r"(w) : "memory");
}
__device__ __forceinline__ void sts64(uint32_t a, uint32_t x, uint32_t y) { asm volatile("st.shared.v2.u32 [%0],{%1,%2};" ::"r"(a), "r"(x), "r"(y) : "memory"); }
__device__ __forceinline__ void sts128p(uint32_t a, uint32_t x, uint32_t y, uint32_t z, uint32_t w, bool p) {
    asm volatile("{.reg .pred p; setp.ne.u32 p,%5,0; @p st.shared.v4.u32 [%0],{%1,%2,%3,%4};}" ::"r"(a), "r"(x), "r"(y), "r"(z), "r"(w), "r"((uint32_t)p) : "memory");
}
__device__ __forceinline__ void sts32(uint32_t a, uint32_t x) { asm volatile("st.shared.u32 [%0],%1;" ::"r"(a), "r"(x) : "memory"); }
__device__ __forceinline__ uint32_t pk(float lo, float hi) { uint32_t r; asm("cvt.rn.bf16x2.f32 %0,%1,%2;" : "=r"(r) : "f"(hi), "f"(lo)); return r; }

__device__ __forceinline__ uint32_t pkv(float lo, float hi) { uint32_t r; asm volatile("cvt.rn.bf16x2.f32 %0,%1,%2;" : "=r"(r) : "f"(hi), "f"(lo)); return r; }

__device__ __forceinline__ void mma16z(float* d, uint32_t a0, uint32_t a1, uint32_t a2, uint32_t a3, uint32_t b0, uint32_t b1) {
    asm("mma.sync.aligned.m16n8k16.row.col.f32.bf16.bf16.f32 {%0,%1,%2,%3},{%4,%5,%6,%7},{%8,%9},{%10,%10,%10,%10};"
        : "=f"(d[0]), "=f"(d[1]), "=f"(d[2]), "=f"(d[3]) : "r"(a0), "r"(a1), "r"(a2), "r"(a3), "r"(b0), "r"(b1), "f"(0.f));
}
__device__ __forceinline__ void mma16(float* d, uint32_t a0, uint32_t a1, uint32_t a2, uint32_t a3, uint32_t b0, uint32_t b1) {
    asm("mma.sync.aligned.m16n8k16.row.col.f32.bf16.bf16.f32 {%0,%1,%2,%3},{%4,%5,%6,%7},{%8,%9},{%0,%1,%2,%3};"
        : "+f"(d[0]), "+f"(d[1]), "+f"(d[2]), "+f"(d[3]) : "r"(a0), "r"(a1), "r"(a2), "r"(a3), "r"(b0), "r"(b1));
}
__device__ __forceinline__ void mma8(float* d, uint32_t a0, uint32_t a1, uint32_t b0) {
    asm("mma.sync.aligned.m16n8k8.row.col.f32.bf16.bf16.f32 {%0,%1,%2,%3},{%4,%5},{%6},{%0,%1,%2,%3};"
        : "+f"(d[0]), "+f"(d[1]), "+f"(d[2]), "+f"(d[3]) : "r"(a0), "r"(a1), "r"(b0));
}
__device__ __forceinline__ void wg_fence() { asm volatile("wgmma.fence.sync.aligned;" ::: "memory"); }
__device__ __forceinline__ void wg_commit() { asm volatile("wgmma.commit_group.sync.aligned;" ::: "memory"); }
template <int N> __device__ __forceinline__ void wg_wait() { asm volatile("wgmma.wait_group.sync.aligned %0;" ::"n"(N) : "memory"); }
template <int N> __device__ __forceinline__ void pin(float (&d)[N]) {
#pragma unroll
    for (int i = 0; i < N; i++) asm volatile("" : "+f"(d[i])::"memory");
}
#define ACC8(o) "+f"(d[o]), "+f"(d[o + 1]), "+f"(d[o + 2]), "+f"(d[o + 3]), "+f"(d[o + 4]), "+f"(d[o + 5]), "+f"(d[o + 6]), "+f"(d[o + 7])
#define OUT8(o) "=f"(d[o]), "=f"(d[o + 1]), "=f"(d[o + 2]), "=f"(d[o + 3]), "=f"(d[o + 4]), "=f"(d[o + 5]), "=f"(d[o + 6]), "=f"(d[o + 7])
template <int ACC> __device__ __forceinline__ void wgmma48(float (&d)[24], uint32_t a0, uint32_t a1, uint32_t a2, uint32_t a3, uint64_t desc) {
    if (ACC)
        asm volatile("wgmma.mma_async.sync.aligned.m64n48k16.f32.bf16.bf16 "
                     "{%0,%1,%2,%3,%4,%5,%6,%7,%8,%9,%10,%11,%12,%13,%14,%15,%16,%17,%18,%19,%20,%21,%22,%23},{%24,%25,%26,%27},%28,%29,1,1,0;"
                     : ACC8(0), ACC8(8), ACC8(16) : "r"(a0), "r"(a1), "r"(a2), "r"(a3), "l"(desc), "n"(ACC & 1));
    else
        asm volatile("wgmma.mma_async.sync.aligned.m64n48k16.f32.bf16.bf16 "
                     "{%0,%1,%2,%3,%4,%5,%6,%7,%8,%9,%10,%11,%12,%13,%14,%15,%16,%17,%18,%19,%20,%21,%22,%23},{%24,%25,%26,%27},%28,0,1,1,0;"
                     : OUT8(0), OUT8(8), OUT8(16) : "r"(a0), "r"(a1), "r"(a2), "r"(a3), "l"(desc));
}
template <int ACC> __device__ __forceinline__ void wgmma_p2(float (&d)[32], const uint32_t* a, uint64_t desc) {
    if (ACC)
        asm volatile("wgmma.mma_async.sync.aligned.m64n64k16.f32.bf16.bf16 "
                     "{%0,%1,%2,%3,%4,%5,%6,%7,%8,%9,%10,%11,%12,%13,%14,%15,%16,%17,%18,%19,%20,%21,%22,%23,%24,%25,%26,%27,%28,%29,%30,%31},{%32,%33,%34,%35},%36,1,1,1,0;"
                     : ACC8(0), ACC8(8), ACC8(16), ACC8(24) : "r"(a[0]), "r"(a[1]), "r"(a[2]), "r"(a[3]), "l"(desc));
    else
        asm volatile("wgmma.mma_async.sync.aligned.m64n64k16.f32.bf16.bf16 "
                     "{%0,%1,%2,%3,%4,%5,%6,%7,%8,%9,%10,%11,%12,%13,%14,%15,%16,%17,%18,%19,%20,%21,%22,%23,%24,%25,%26,%27,%28,%29,%30,%31},{%32,%33,%34,%35},%36,0,1,1,0;"
                     : OUT8(0), OUT8(8), OUT8(16), OUT8(24) : "r"(a[0]), "r"(a[1]), "r"(a[2]), "r"(a[3]), "l"(desc));
}
template <int ACC> __device__ __forceinline__ void wgmma_p2(float (&d)[4], const uint32_t* a, uint64_t desc) {
    if (ACC)
        asm volatile("wgmma.mma_async.sync.aligned.m64n8k16.f32.bf16.bf16 {%0,%1,%2,%3},{%4,%5,%6,%7},%8,1,1,1,0;"
                     : "+f"(d[0]), "+f"(d[1]), "+f"(d[2]), "+f"(d[3]) : "r"(a[0]), "r"(a[1]), "r"(a[2]), "r"(a[3]), "l"(desc));
    else
        asm volatile("wgmma.mma_async.sync.aligned.m64n8k16.f32.bf16.bf16 {%0,%1,%2,%3},{%4,%5,%6,%7},%8,0,1,1,0;"
                     : "=f"(d[0]), "=f"(d[1]), "=f"(d[2]), "=f"(d[3]) : "r"(a[0]), "r"(a[1]), "r"(a[2]), "r"(a[3]), "l"(desc));
}
__device__ __forceinline__ uint64_t desc_tab(uint32_t a) { return (uint64_t)((a & 0x3FFFF) >> 4) | ((uint64_t)(768 >> 4) << 16) | ((uint64_t)(128 >> 4) << 32); }

__device__ __forceinline__ void staged(uint32_t bar, int lane) {
    fence_async_s();
    __syncwarp();
    if (lane == 0) mbar_arrive(bar);
}

__device__ __forceinline__ void wgen(uint32_t win, uint32_t tab, uint32_t out, int c, int qq, int lane, uint32_t consumed, uint32_t chain, uint32_t gate, uint32_t cma) {
    uint32_t A[28];
    int mi = lane >> 3, rr = lane & 7;
    int L = 12 * (mi & 1) + c;
#pragma unroll
    for (int s = 0; s < 7; s++) {
        int u = s < 6 ? s / 3 : mi >> 1;
        int tap = s < 6 ? 16 * (s % 3) + 8 * (mi >> 1) + rr : 48;
        int line = 3 * tap + (L >> 3);
        uint32_t ad = win + u * WPIECE + line * 128 + (((L ^ line) & 7) << 4);
        asm volatile("ldmatrix.sync.aligned.m8n8.x4.trans.shared.b16 {%0,%1,%2,%3},[%4];"
                     : "=r"(A[4 * s]), "=r"(A[4 * s + 1]), "=r"(A[4 * s + 2]), "=r"(A[4 * s + 3]) : "r"(ad));
    }
    float d0[24], d1[24];
    uint64_t ds = desc_tab(tab);
    wg_fence();
    wgmma48<0>(d0, A[0], A[1], A[2], A[3], ds);
    wgmma48<0>(d1, A[12], A[13], A[14], A[15], ds);
    wgmma48<1>(d0, A[4], A[5], A[6], A[7], ds + 96);
    wgmma48<1>(d1, A[16], A[17], A[18], A[19], ds + 96);
    wgmma48<1>(d0, A[8], A[9], A[10], A[11], ds + 192);
    wgmma48<1>(d1, A[20], A[21], A[22], A[23], ds + 192);
    wgmma48<1>(d0, A[24], A[25], A[26], A[27], ds + 336);
    wgmma48<1>(d1, A[24], A[25], A[26], A[27], ds + 288);
    wg_commit();
    if (lane == 0) { if (chain) mbar_arrive(chain); mbar_arrive(consumed); }
    mbar_wait(gate);
    const uint32_t tag = ~lds32(cma);
    wg_wait<0>();
    pin(d0); pin(d1);
    int g = lane >> 2, q = lane & 3;
    const uint32_t p = out + q * 512 + (8 * (c & 3) + (g ^ (2 * (q ^ qq)))) * 16;
#pragma unroll
    for (int nb = 0; nb < 6; nb++)
        if (nb < 5 || q < 2)
            sts128(p + nb * 2048, pk(d0[4 * nb], d0[4 * nb + 2]), pk(d0[4 * nb + 1], d0[4 * nb + 3]), pk(d1[4 * nb], d1[4 * nb + 2]),
                   tagged(pk(d1[4 * nb + 1], d1[4 * nb + 3]), g == 7, tag));
}

__device__ __forceinline__ void p1_unit(uint32_t blk, uint32_t out, uint32_t cst, uint32_t full, int wg, int wq, int lane) {
    int g = lane >> 2, q = lane & 3;
    uint32_t T[20];
#pragma unroll
    for (int v = 0; v < 5; v++) { uint4 x = lds128(cst + C_P1A + (v * 32 + lane) * 16); T[4 * v] = x.x; T[4 * v + 1] = x.y; T[4 * v + 2] = x.z; T[4 * v + 3] = x.w; }
    uint32_t P[6][3][4];
    const uint32_t a0 = blk + g * 512 + (2 * q + (g & 1)) * 64 + ((wq ^ q) << 4), a1 = a0 ^ 64;
    const uint32_t sel0 = (g & 1) ? 0x1054 : 0x5410, sel1 = sel0 + 0x2222;
    uint32_t vv[2][3][2][4];
    auto ldv = [&](int nu) {
        const int ro = (nu == 0 ? 6 : (nu == 1 ? 14 : 0)) * 512;
#pragma unroll
        for (int t = 0; t < 3; t++)
#pragma unroll
            for (int e = 0; e < 2; e++) {
                uint4 x = lds128((e ? a1 : a0) + t * 11264 + ro);
                vv[nu & 1][t][e][0] = x.x; vv[nu & 1][t][e][1] = x.y; vv[nu & 1][t][e][2] = x.z; vv[nu & 1][t][e][3] = x.w;
            }
    };
    mbar_wait(full);
    ldv(0);
#pragma unroll
    for (int nu = 0; nu < 3; nu++) {
        if (nu < 2) ldv(nu + 1);
        auto& v = vv[nu & 1];
#pragma unroll
        for (int ch = 0; ch < 4; ch++) {
            const uint32_t sel = (ch & 1) ? sel1 : sel0;
            uint32_t b[2][3];
#pragma unroll
            for (int hf = 0; hf < 2; hf++)
#pragma unroll
                for (int t = 0; t < 3; t++) b[hf][t] = __byte_perm(v[t][0][(ch >> 1) + 2 * hf], v[t][1][(ch >> 1) + 2 * hf], sel);
            float d1[4];
            mma16z(d1, T[12], T[13], T[14], T[15], b[0][0], b[1][0]);
#pragma unroll
            for (int hf = 0; hf < 2; hf++) {
                float d0[4];
                mma16z(d0, T[0], T[1], T[2], T[3], b[hf][1], b[hf][2]);
                mma8(d0, T[16], T[17], b[hf][0]);
                mma16(d1, T[4 + 4 * hf], T[5 + 4 * hf], T[6 + 4 * hf], T[7 + 4 * hf], b[hf][1], b[hf][2]);
                P[(ch >> 1) + 2 * hf][nu][ch & 1] = pk(d0[0], d0[1]);
                P[(ch >> 1) + 2 * hf][nu][2 + (ch & 1)] = pk(d0[2], d0[3]);
            }
            P[4 + (ch >> 1)][nu][ch & 1] = pk(d1[0], d1[1]);
            P[4 + (ch >> 1)][nu][2 + (ch & 1)] = pk(d1[2], d1[3]);
        }
#pragma unroll
        for (int pb = 0; pb < 6; pb++) asm volatile("" : "+r"(P[pb][nu][0]), "+r"(P[pb][nu][1]), "+r"(P[pb][nu][2]), "+r"(P[pb][nu][3]));
                if (nu < 2) region_end(cst + (O_BAR - O_C) + 8 * BC);
    }
    const uint64_t ds = desc_tab(cst + C_P1B);
    float dA[24], dB[24];
    auto issue = [&](int pb) {
        wg_fence();
        if (pb == 4) {
            wgmma48<0>(dA, P[pb][0][0], P[pb][0][1], P[pb][0][2], P[pb][0][3], ds);
            wgmma48<0>(dB, P[pb + 1][0][0], P[pb + 1][0][1], P[pb + 1][0][2], P[pb + 1][0][3], ds);
        } else {
            wgmma48<2>(dA, P[pb][0][0], P[pb][0][1], P[pb][0][2], P[pb][0][3], ds);
            wgmma48<2>(dB, P[pb + 1][0][0], P[pb + 1][0][1], P[pb + 1][0][2], P[pb + 1][0][3], ds);
        }
        wgmma48<1>(dA, P[pb][1][0], P[pb][1][1], P[pb][1][2], P[pb][1][3], ds + 96);
        wgmma48<1>(dB, P[pb + 1][1][0], P[pb + 1][1][1], P[pb + 1][1][2], P[pb + 1][1][3], ds + 96);
        wgmma48<1>(dA, P[pb][2][0], P[pb][2][1], P[pb][2][2], P[pb][2][3], ds + 192);
        wgmma48<1>(dB, P[pb + 1][2][0], P[pb + 1][2][1], P[pb + 1][2][2], P[pb + 1][2][3], ds + 192);
        wg_commit();
    };
    issue(4);
    bar_sync(1 + wg, 128);
    asm volatile("" : "+r"(g), "+r"(q));
    wg_wait<0>(); pin(dA); pin(dB);
    uint32_t o[12][2];
#pragma unroll
    for (int k = 0; k < 12; k++) { const int i = 4 * (k >> 1) + (k & 1); o[k][0] = pkv(dA[i], dA[i + 2]); o[k][1] = pkv(dB[i], dB[i + 2]); }
    issue(0);
    {
        const int sw = (g >> 1) & 1, r0 = 2 * (lds8(cst + (O_PERM - O_C) + (g < 6 ? 8 + (g >> 1) : 1)) * 11 + q) + sw;
        const uint32_t a0 = out + r0 * 128 + ((((4 * sw + wq) ^ r0) & 7) << 4) + 8 * (g & 1);
        const uint32_t m = wq == 3 && (g & 1) ? TAGM : 0, m0 = sw ? m : 0, m1 = m ^ m0;
#pragma unroll
        for (int k = 11; k >= 0; k--) {
            sts64((a0 ^ ((k & 2) * 72 + (k & 1) * 64)) + 1024 * (k >> 2), o[k][0], tagged(o[k][1], (k & 1) ? m1 : m0, TAGX));
            if (k == 8) __syncwarp();
        }
    }
    wg_wait<0>(); pin(dA); pin(dB);
#pragma unroll
    for (int k = 0; k < 12; k++) { const int i = 4 * (k >> 1) + (k & 1); o[k][0] = pkv(dA[i], dA[i + 2]); o[k][1] = pkv(dB[i], dB[i + 2]); }
    issue(2);
    region_end(cst + (O_BAR - O_C) + 8 * BC);
    const int r0 = 2 * (lds8(cst + (O_PERM - O_C) + g) * 11 + q) + (g & 1);
    const uint32_t ao = out + r0 * 128 + ((((4 * (g & 1) + wq) ^ r0) & 7) << 4);
    const uint32_t m = wq == 3 ? TAGM : 0, m0 = (g & 1) ? m : 0, m1 = m ^ m0;
    wg_wait<0>(); pin(dA); pin(dB);
#pragma unroll
    for (int k = 0; k < 12; k++) {
        const int i = 4 * (k >> 1) + (k & 1);
        sts128p((ao ^ ((k & 2) * 72 + (k & 1) * 64)) + 1024 * (k >> 2), o[k][0], o[k][1], pk(dA[i], dA[i + 2]),
                tagged(pk(dB[i], dB[i + 2]), (k & 1) ? m1 : m0, TAGX), k < 8 || q < 3);
    }
}

template <int NB, class F>
__device__ __forceinline__ void p2_step(const uint32_t (&Wf)[48], uint32_t in, uint32_t a0, uint32_t m, uint32_t t, uint32_t bar, int lane, int wg, int s, F meanwhile) {
    float dp[4 * NB], dm[4 * NB];
    const uint32_t lo = ((in & 0x3FFFF) >> 4) | (1u << 16);
    auto desc = [&](int o) { return (uint64_t)(lo + o) | ((uint64_t)(1024 >> 4) << 32) | (1ull << 62); };
    if (NB > 1 && (wg || s > 1)) bar_sync(4 + wg, 256);
    wg_fence();
    wgmma_p2<0>(dp, &Wf[0], desc(0));
    wgmma_p2<0>(dm, &Wf[24], desc(4));
#pragma unroll
    for (int ks = 1; ks < 6; ks++) {
        wgmma_p2<1>(dp, &Wf[4 * ks], desc((ks >> 1) * NB * 64 + (ks & 1) * 2));
        wgmma_p2<1>(dm, &Wf[24 + 4 * ks], desc((ks >> 1) * NB * 64 + (ks & 1) * 2 + 4));
    }
    wg_commit();
    if (NB > 1 && (wg < 2 || s < 6)) asm volatile("bar.arrive %0,256;" ::"r"(wg == 2 ? 4 : 5 + wg) : "memory");
    meanwhile();
    mbar_wait_ph(bar + 8 * (s < 2 ? BD1 + 1 : BDP + 2 * wg + (s & 1)), s >= 2 ? ((s >> 1) & 1) ^ 1 : 0);
    wg_wait<0>();
    pin(dp); pin(dm);
    if (NB > 1 && s < 6 && lane == 0) mbar_arrive(bar + 8 * (BPE + s));
    uint32_t v[2 * NB];
#pragma unroll
    for (int nb = 0; nb < NB; nb++) {
        float pr = dp[4 * nb] - dp[4 * nb + 3], pi = dp[4 * nb + 1] + dp[4 * nb + 2];
        float mr = dm[4 * nb] - dm[4 * nb + 3], mi = dm[4 * nb + 1] + dm[4 * nb + 2];
        v[2 * nb] = tagged(pk(pr + mr, pi - mi), m, t);
        v[2 * nb + 1] = tagged(pk(pi + mi, mr - pr), m, t);
        if (nb & 1)
            asm volatile("stmatrix.sync.aligned.m8n8.x4.trans.shared.b16 [%0],{%1,%2,%3,%4};" ::"r"(a0 + (nb - 1) * 1024), "r"(v[2 * nb - 2]), "r"(v[2 * nb - 1]),
                         "r"(v[2 * nb]), "r"(v[2 * nb + 1]) : "memory");
    }
    if (NB == 1) asm volatile("stmatrix.sync.aligned.m8n8.x2.trans.shared.b16 [%0],{%1,%2};" ::"r"(a0), "r"(v[0]), "r"(v[1]) : "memory");
}

__device__ __forceinline__ bool p3_unit(uint32_t blk, uint32_t cst, uint32_t full, uint32_t ph, int wg, int wq, int lane) {
    int g = lane >> 2, q = lane & 3;
    uint32_t T[12];
#pragma unroll
    for (int v = 0; v < 3; v++) { uint4 x = lds128(cst + C_P3 + (v * 32 + lane) * 16); T[4 * v] = x.x; T[4 * v + 1] = x.y; T[4 * v + 2] = x.z; T[4 * v + 3] = x.w; }
    uint32_t ad[3][2];
#pragma unroll
    for (int nu = 0; nu < 3; nu++) {
        const int pos = lds8(cst + (O_PERM - O_C) + min(4 * nu + (g >> 1), 10));
#pragma unroll
        for (int ka = 0; ka < 2; ka++) {
            int r = 2 * (pos * 11 + (ka ? min(8 + q, 10) : q)) + (g & 1);
            ad[nu][ka] = blk + r * 128 + ((((2 * wq) ^ r) & 7) << 4);
        }
    }
    mbar_wait_ph(full, ph);
    uint32_t o[2][4][4], bad = 0, P[8][3][2];
#pragma unroll
    for (int nu = 0; nu < 3; nu++) {
        uint32_t z[3][2][4];
#pragma unroll
        for (int ka = 0; ka < 3; ka++)
#pragma unroll
            for (int h = 0; h < 2; h++) {
                uint4 x = lds128((ad[nu][ka >> 1] ^ (h << 4)) + (ka & 1) * 1024);
                z[ka][h][0] = x.x; z[ka][h][1] = x.y; z[ka][h][2] = x.z; z[ka][h][3] = x.w;
                if (h) bad |= x.w ^ TAGZ;
            }
#pragma unroll
        for (int ch = 0; ch < 8; ch++) {
            const uint32_t sel = (ch & 1) ? 0x7632 : 0x5410;
            float d[4];
            mma16z(d, T[0], T[1], T[2], T[3], __byte_perm(z[0][0][ch >> 1], z[0][1][ch >> 1], sel), __byte_perm(z[1][0][ch >> 1], z[1][1][ch >> 1], sel));
            mma8(d, T[4], T[5], __byte_perm(z[2][0][ch >> 1], z[2][1][ch >> 1], sel));
            P[ch][nu][0] = pk(d[0], d[1]); P[ch][nu][1] = pk(d[2], d[3]);
        }
    }
    if (bar_any(1 + wg, 128, wq == 3 && (bad & TAGM))) return false;
#pragma unroll
    for (int j = 0; j < 4; j++) {
        float d2[2][2][4];
#pragma unroll
        for (int e = 0; e < 2; e++)
#pragma unroll
            for (int be = 0; be < 2; be++) {
                const int ch = 2 * j + e;
                mma16z(d2[e][be], P[ch][0][0], P[ch][0][1], P[ch][1][0], P[ch][1][1], T[8 + 2 * be], T[9 + 2 * be]);
                mma8(d2[e][be], P[ch][2][0], P[ch][2][1], T[6 + be]);
            }
#pragma unroll
        for (int be = 0; be < 2; be++)
#pragma unroll
            for (int k = 0; k < 4; k++) o[be][k][j] = pk(d2[0][be][k], d2[1][be][k]);
    }
    const int p = 4 * g + q;
    const uint32_t a = blk + p * 64 + ((wq ^ ((p >> 1) & 3)) << 4);
#pragma unroll
    for (int be = 0; be < 2; be++)
#pragma unroll
        for (int k = 0; k < 4; k++)
            sts128(a + (2 * be + (k & 1)) * 4096 + (k >> 1) * 2048, o[be][k][0], o[be][k][1], o[be][k][2], o[be][k][3]);
    return true;
}

template <int Z> __device__ __forceinline__ int s_row(int gr, int st, int cg, int ci, unsigned cm) {
    const int sf = (ci >> 2) & 1, y = 3 * (3 * gr + cg) + ((st ^ sf) << (Z ^ (cm >> 31))), pg = y >> 2;
    const int r = (pg << 14) | ((ci & 1) << 6) | ((ci & 2) << 8) | ((y & 1) << 10) | ((y & 2) << 11);
    return r | ((((Z ? st : sf) ^ ci ^ (ci >> 1) ^ y ^ (y >> 1) ^ (cm >> pg)) & 1) << 5);
}
__device__ __forceinline__ int w_row(int fw, int hg, int cg, int io, unsigned cm) {
    const int home = fw == 5 ? hg >> 1 : fw > 5;
    const int col = fw == 5 ? 15 + (hg & 1) : 3 * (fw > 5 ? fw - 6 : fw) + hg;
    const int z = 9 * col + 3 * cg + io, pg = NPS + (z >> 5);
    const int r = (pg << 12) | ((z & 1) << 4) | ((z & 6) << 6) | ((z & 24) << 7);
    return r | (((home ^ __popc(z & 15) ^ (cm >> pg)) & 1) << 3);
}
__device__ __forceinline__ int s_tile(int t) { return ((t & 3) << 7) | ((t & 4) << 9) | ((t & 8) << 10); }
__device__ __forceinline__ int xoff(int r) { return r < 3 ? O_B0 + r * BLK : (r == 3 ? O_B4 : O_B3); }
__device__ __forceinline__ int soff(int r) { return r == 2 ? O_B2 + 2048 : xoff(r); }
__device__ __forceinline__ int zoff(int r) { return r == 0 ? O_B2 + 2048 : (r == 1 ? O_B3 : (r == 2 ? O_B4 : (r == 3 ? O_Z3 : O_Z4))); }

struct Role1 {
    int sd, k, nu;
    __device__ __forceinline__ Role1(int cta) {
        sd = cta >= NH; k = cta - sd * NH;
        if (k < 60) k = (k >> 1) + ((k & 1) ? 0 : 30);
        nu = k < NUH - 4 * NH ? 5 : 4;
    }
};
struct Role {
    int sd, k, fp, nu;
    __device__ __forceinline__ Role(int rho) {
        sd = rho >= NH;
        const int kk = sd ? NCTA - 1 - rho : rho;
        k = NH - 1 - kk;
        nu = k < NUH - 4 * NH ? 5 : 4;
        fp = k >= 5 + sd ? 60 * sd + k - 5 : -1;
    }
};
__device__ __forceinline__ int stage_row(const Role& R, int s, int lane, unsigned cm, int z) {
    const int ci = R.fp > 0 ? (R.fp - 1) / 15 : 0, rw = 2 * (ci ? R.fp - 15 * ci - 1 : R.fp);
    return (z ? s_row<1>(s, lane & 1, lane >> 1, ci, cm) : s_row<0>(s, lane & 1, lane >> 1, ci, cm)) + rw + (s ? 0 : s_tile(14));
}
__device__ __forceinline__ int stage_off(int s, int lane) { return (lane >> 1) * 8192 + (lane & 1) * (s ? 4096 : 512); }
template <int Z, class RT> __device__ __forceinline__ int unit_row(const RT& R, int r, int lane, unsigned cm) {
    const int u = r * NH + R.k, ts = u / 3;
    return s_row<Z>((ts + 14) >> 4, R.sd, u - 3 * ts, lane, cm) + s_tile(ts + 14);
}
__device__ __forceinline__ int unit_off(int lane) { return lane ? 3840 * lane + 256 : 0; }

__global__ void __launch_bounds__(512, 1) fftconv_kernel(const __grid_constant__ Maps mp) {
    extern __shared__ __align__(1024) unsigned char smraw[];
    const uint32_t sm = s2u(smraw);
    const uint32_t bar = sm + O_BAR;
    const int tid = threadIdx.x, lane = tid & 31;
    const uint32_t tstart = clock();
    if (tid >= 480) {
        if (elect()) {
            const int c = blockIdx.x, ip = c % 12, pr = 3 * (8 * (ip >> 1) + 2 * (ip & 1));
#pragma unroll
            for (int i = 0; i < 8; i++) mbar_init(bar + 8 * i, 1);
            mbar_expect(bar + 8 * BW, 2 * 18816 + WT_BYTES);
            tma_ld3(sm + O_W0, &mp.w, bar + 8 * BW, 0, pr, 0);
            tma_ld3(sm + O_W0 + WPIECE, &mp.w, bar + 8 * BW, 0, pr + 12, 0);
            bulk_ld(sm + O_WT, mp.wtab + (c / 12) * WT_BYTES, WT_BYTES, bar + 8 * BW);
            asm volatile("prefetch.tensormap [%0];" ::"l"(&mp.x22) : "memory");
        }
        __syncwarp();
        asm volatile("bar.arrive 9,64;\n bar.arrive 0,288;" ::: "memory");
    }
    if (tid < 128) {
        const int c = blockIdx.x, vp = min(c & 31, NPAGE - 2);
        const int r0 = 94 + (c & 1) + ((c >> 1) << 7);
        const int r1 = ((vp + 1) << 14) + 94 + ((c >> 5) & 1) + ((c >> 6) << 7) + (vp < NPS - 1 ? 0 : ((0xA151 >> (5 * (vp - NPS + 1))) & 31) << 9);
        unsigned* a = reinterpret_cast<unsigned*>(mp.s) + ((tid & 64 ? r1 : r0) + (tid & 32)) * 32 + lane;
        const bool on = tid < 64 || (c & 31) < NPAGE - 1;
        if (on) *a = 0;
        bar_sync(10, 128);
        unsigned t = 0;
        if (on) asm volatile("{.reg .u32 v; .reg .pred p;\n atom.relaxed.gpu.global.exch.b32 v,[%1],1;\n setp.eq.u32 p,v,0;\n @p mov.u32 %0,%%clock;}" : "+r"(t) : "l"(a) : "memory");
        if (lane == 0) sts32(sm + O_PT + (tid >> 3), t);
        bar_sync(10, 128);
        const uint4 tt = lds128(sm + O_PT);
        const int far = (((int)(tt.x - tt.y) > 0) ^ __popc(r0 & 0x1640)) & 1;
        if (lane == 0 && (tid == 32 || (tid == 64 && on))) {
            const int i = tid == 32 ? 20 + c / 12 : vp, v = tid == 32 ? far : (far ^ ((int)(tt.z - tt.w) > 0) ^ __popc(r1 & 0x1640)) & 1;
            red_add(mp.cnt + 64 * (CV + (i & 7)), 1u << ((i & 24) + 4 * v));
        }
        if (tid == 0) sts32(sm + O_ROLE, far);
        __syncwarp();
        bar_sync(11, 160);
        if (tid == 0) mbar_arrive(bar + 8 * (BRL + 1));
        __syncwarp();
    }
    const int warp = __shfl_sync(0xffffffffu, tid >> 5, 0);
    int cta;
    asm volatile("mov.u32 %0,%%ctaid.x;" : "=r"(cta));
    const int wip = cta % 12;
    const Role1 X(cta);

    if (warp >= 12) {
        asm volatile("setmaxnreg.dec.sync.aligned.u32 32;");
        if (warp & 1) bar_sync(warp, 64);
        if (warp == 12) {
            {
                const int pr = 3 * (8 * (wip >> 1) + 2 * (wip & 1) + 1);
                const int ts = X.k / 3, xc = 32 * (X.k - 3 * ts), tr = ts >= 14, th = 7 * X.sd + tr, w0 = 16 * (ts - 14 * tr);
                const CUtensorMap* xm = th ? &mp.x22 : &mp.x16;
                const uint32_t xd = sm + O_B0 + (th ? 0 : 3072);
                const int xh = th ? 16 * th - 6 : 0;
                bar_sync(9, 64);
                if (elect()) {
                    mbar_expect(bar + 8 * BC, C_BYTES); mbar_expect(bar + 8 * (BW + 1), 2 * 18816); mbar_expect(bar + 8 * BX, BLK);
                    bulk_ld(sm + O_C, mp.ctab, C_BYTES, bar + 8 * BC);
                    until(tstart + XD0, 0);
                    tma_ld3(sm + O_W1, &mp.w, bar + 8 * (BW + 1), 0, pr, 0);
                    tma_ld3(sm + O_W1 + WPIECE, &mp.w, bar + 8 * (BW + 1), 0, pr + 12, 0);
                    tma_ld3(xd + 11264, xm, bar + 8 * BX, xc, w0, xh);
                    until(tstart + XD0 + XE, 0);
                    tma_ld3(xd + 22528, xm, bar + 8 * BX, xc, w0 + 8, xh);
                    until(tstart + XD0 + 2 * XE, 0);
                    tma_ld3(xd, xm, bar + 8 * BX, xc, w0 ? w0 - 8 : 216, xh);
                    if (!th) {
#pragma unroll
                        for (int t = 0; t < 3; t++) tma_ld3(sm + O_B0 + t * 11264, &mp.x6, bar + 8 * BX, xc, t || w0 ? w0 - 8 + 8 * t : 216, 218);
                    }
                }
                __syncwarp();
            }
            const int r = lane / 3 + 1, t = lane - 3 * r + 3;
            const int u = r * NH + X.k, ts = u / 3, tr = ts / 14, tw = ts - 14 * tr;
            const int xc = 32 * (u - 3 * ts), xw = t || tw ? 16 * tw - 8 + 8 * t : 216, xh = 16 * (7 * X.sd + tr) - 6;
            const uint32_t xd = sm + xoff(r) + t * 11264, xb = bar + 8 * (BX + r);
            if (lane && lane < X.nu) mbar_expect(bar + 8 * (BX + lane), BLK);
            bar_sync(12, 64);
            uint32_t due = tstart + XD1;
#pragma unroll 1
            for (int i = 0; i < 3 * X.nu - 3; i++) {
                if (i == 6 || i == 9) mbar_wait(bar + 8 * (i == 6 ? BWC + 1 : BDW));
                until(due, NAP);
                due += XD;
                if (lane == i) tma_ld3(xd, &mp.x22, xb, xc, xw, xh);
                __syncwarp();
            }
        } else if (warp == 13) {
            mbar_wait(bar + 8 * (BRL + 1));
            if (lane == 0) {
                const unsigned far = lds32(sm + O_ROLE), t = atomicAdd(mp.cnt + 64 * (CT + far), 1u);
                sts32(sm + O_ROLE, far ? NCTA - 1 - t : t);
                mbar_arrive(bar + 8 * BRL);
            }
            __syncwarp();
        } else if (warp == 14) {
            unsigned par, vote = 0;
            asm volatile("ld.relaxed.gpu.global.u32 %0,[%1];" : "=r"(par) : "l"(mp.cnt + 64 * (CV + (cta & 7)) + 1) : "memory");
            unsigned cm; int pos;
#pragma unroll 1
            for (int it = 0; it < (1 << 16); it++) {
                cm = (__ballot_sync(0xffffffffu, lane < 20 && (vote >> 4) > (vote & 15)) << 1);
                const unsigned gm = 0x7ff00000u, lo = __ballot_sync(0xffffffffu, vote < 64) & gm, hi = __ballot_sync(0xffffffffu, vote >= 144) & gm, mid = gm ^ lo ^ hi;
                const unsigned below = (1u << lane) - 1;
                pos = vote < 64 ? __popc(lo & below) : (vote < 144 ? __popc(lo) + __popc(mid & below) : 11 - __popc(hi) + __popc(hi & below));
                asm volatile("" : "+r"(cm), "+r"(pos));
                if (!__any_sync(0xffffffffu, lane < 31 && (vote & 15) + (vote >> 4) < (lane < 4 ? 5u : (lane < 20 ? 4u : 12u)))) break;
                if (it == 0) {
                    bar_sync(14, 64);
                    if (lane == 0) { sts32(sm + O_EP, par); mbar_arrive(bar + 8 * BEP); }
                    until(tstart + VT, 0);
                }
                asm volatile("ld.acquire.gpu.global.u8 %0,[%1];" : "=r"(vote) : "l"(reinterpret_cast<unsigned char*>(mp.cnt + 64 * (CV + (lane & 7))) + (lane >> 3)) : "memory");
            }
            if (lane >= 20 && lane < 31) asm volatile("st.shared.u8 [%0],%1;" ::"r"(sm + O_PERM + lane - 20), "r"(pos) : "memory");
            __syncwarp();
            if (lane == 0) { sts32(sm + O_CM, cm | (par << 31)); mbar_arrive(bar + 8 * BCM); }
            __syncwarp();
        }
        auto role = [&]() { mbar_wait(bar + 8 * BRL); return Role(bcast(lds32(sm + O_ROLE), 0)); };

        if (warp == 12) {
            const Role R = role();
            if (R.fp >= 0) {
                mbar_wait(bar + 8 * BCM);
                const unsigned cm = lds32(sm + O_CM);
                if (lane < 7) mbar_expect(bar + 8 * (BPF + lane), lane ? STG : 3072);
                mbar_wait(bar + 8 * (BIS + 2));
                const int v0 = stage_row(R, lane >> 3, lane & 7, cm, 0), v1 = stage_row(R, 4 + (lane >> 3), lane & 7, cm, 0);
                uint32_t dst = sm + O_S0, seen = 0;
#pragma unroll 1
                for (int s = 0; s < 7; s++) {
                    int row[6];
#pragma unroll
                    for (int i = 0; i < 6; i++) row[i] = bcast(s < 4 ? v0 : v1, 8 * s + i);
                    const CUtensorMap* m = s ? &mp.p16 : &mp.p2;
                    const uint32_t hs = s ? 4096 : 512;
                    for (int it = 0; !(seen >> s & 1) && it < (1 << 16); it++) {
                        unsigned v = 0;
                        if (lane == s || (s >= WIN && lane > s && lane < 7)) asm volatile("ld.acquire.gpu.global.u32 %0,[%1];" : "=r"(v) : "l"(mp.cnt + 64 * (CX + lane)) : "memory");
                        seen = __ballot_sync(0xffffffffu, v >= (lane ? 96u : 12u));
                    }
                    mbar_wait(bar + 8 * (s > 3 ? BPE + s - 3 : (s ? BWE + s - 1 : BD1)));
                    if (elect()) {
#pragma unroll
                        for (int i = 0; i < 6; i++) tma_ld5(dst + i * hs, m, bar + 8 * (BPF + s), 0, row[i], 0, 0, 0);
                    }
                    __syncwarp();
                    dst = dst >= sm + O_IN + 2 * STG ? sm + O_IN : dst + STG;
                }
            }
        } else if (warp == 13) {
            const Role R = role();
            mbar_wait(bar + 8 * BCM);
            if (R.fp >= 0) {
                const unsigned cm = lds32(sm + O_CM);
                if (lane < 3) mbar_expect(bar + 8 * (BWF + lane), STG);
                const int fw = R.fp / 11;
                {
                    const int fh = R.fp - 11 * fw, b = lane / 3, io = lane - 3 * b;
                    const int row = w_row(fw, fh >> 2, b, io, cm) + 2 * (fh & 3);
                    mbar_wait(bar + 8 * (BDW + 1));
                    poll(mp.cnt + 64 * (CW + fw), 12);
                    const uint32_t t0 = clock();
#pragma unroll 1
                    for (int i = 0; i < 9; i++) {
                        if (i == 6) mbar_wait(bar + 8 * BD1);
                        until(t0 + i * LPW, NAP);
                        if (lane == i) tma_ld4(sm + O_IN + lane * 8192, &mp.wf, bar + 8 * (BWF + b), 0, row, 0, 0);
                        __syncwarp();
                    }
                }
                {
                    const int row = stage_row(R, 0, lane & 7, cm, lane < 8);
                    mbar_wait(bar + 8 * BR2); mbar_wait(bar + 8 * (BR2 + 2)); mbar_wait(bar + 8 * (BR2 + 4));
                    if (lane < 6 || (R.fp == 15 && lane < 14 && (lane & 9) == 9)) tma_st5(&mp.p2, sm + O_OUT + stage_off(0, lane & 7), 0, row, 0, 0, 0);
                    __syncwarp();
                    bulk_commit(); bulk_wait_read<0>();
                    __syncwarp();
                    if (lane < 4) mbar_arrive(bar + 8 * (lane < 3 ? BDP + 2 * lane : BI2));
                    if (lane == 0) red_add(mp.cnt + 64 * CY);
                    __syncwarp();
                }
            }
            if (lane < R.nu) mbar_expect(bar + 8 * (BZ + lane), SLAB);
            const int v = unit_row<1>(R, lane >> 1, 4 * (lane & 1), lds32(sm + O_CM));
            mbar_wait(bar + 8 * (BD1 + X.nu - 2)); mbar_wait(bar + 8 * (BD1 + X.nu - 1));
#pragma unroll 1
            for (int r = 0; r < R.nu; r++) {
                const int r0 = bcast(v, 2 * r), r1 = bcast(v, 2 * r + 1), gr = (r * NH + R.k + 42) / 48;
                const uint32_t dst = sm + zoff(r), fb = bar + 8 * (BZ + r);
                if (R.fp >= 0) {
                    if (r >= 3) { mbar_wait(bar + 8 * (r == 3 ? BPE + 4 : BD2)); mbar_wait(bar + 8 * (r == 3 ? BPE + 5 : BD2 + 1)); }
                    mbar_wait(bar + 8 * (BI2 + gr));
                }
                poll(mp.cnt + 64 * (CY + gr), NFP);
                if (elect()) {
#pragma unroll
                    for (int i = 0; i < 8; i++)
                        tma_ld2(dst + unit_off(i), i ? &mp.s30 : &mp.s32, fb, 0, (i < 4 ? r0 : r1) ^ (((i & 1) * 96) ^ ((i & 2) * 272)));
                }
                __syncwarp();
            }
            if (R.fp >= 0) mbar_wait(bar + 8 * (BPF + 6));
            unsigned last = 0;
            if (lane == 0) last = atomicAdd(mp.cnt + 64 * CD, 1u) == NCTA - 1;
            if (__shfl_sync(0xffffffffu, last, 0)) {
                mp.cnt[64 * lane] = 0;
                if (lane < 16) mp.cnt[64 * (CV + (lane >> 1)) + (lane & 1)] = (lane & 1) ? lds32(sm + O_EP) ^ 1 : 0;
            }
        } else {
            const int me = warp & 1;
            uint32_t next = tstart;
            auto pace = [&](int cost) {
                const uint32_t now = until(next, NAP);
                next = ((int)(now - next) > CREDIT ? now - CREDIT : next) + cost;
            };
            const int bal = X.nu == 5 ? BAL : (256 * 875 - BAL * 431) / 445;
            mbar_wait(bar + 8 * BCM);
            const unsigned cm = __shfl_sync(0xffffffffu, lds32(sm + O_CM), 0);
            {
                const int iq = 2 * wip + me, w = lane / 3, hg = lane - 3 * w, wfw = lds8(sm + O_PERM + cta / 12);
                unsigned char* dst = mp.s + (size_t)w_row(wfw, hg, w, iq >> 3, cm) * 512 + ((iq & 3) << 14) + ((iq & 4) << 16);
                const uint32_t src = sm + (me ? O_W0 : O_B3) + w * 11264 + hg * 4096;
                if (me) { mbar_wait(bar + 8 * BIS); next = lds32(sm + O_NEXT); }
#pragma unroll 1
                for (int i = 0; i < 3; i++) {
                    mbar_wait(bar + 8 * (BRW + 3 * me + i));
                    pace((RW * 11 / 4 * bal) >> 8);
                    if (w == i) bulk_st(dst, src, hg < 2 ? 4096 : 3072);
                    __syncwarp();
                }
                if (lane == 0) { sts32(sm + O_NEXT, next); mbar_arrive(bar + 8 * (BIS + me)); if (me) red_add(mp.cnt + 64 * (CW + wfw)); }
                bulk_commit(); bulk_wait_read<0>();
                __syncwarp();
                if (lane == 0) mbar_arrive(bar + 8 * (BDW + me));
            }
            const int vu = unit_row<0>(X, lane >> 1, 4 * (lane & 1), cm);
            const Role R = role();
            const int first = (X.nu ^ me) & 1;
            int v, vx;
            { const int n = first + (lane & 30), s = n / 3, l = 2 * (n - 3 * s) + (lane & 1); v = stage_row(R, s + 1, l, cm, 1); vx = stage_row(R, s + 1, l, cm, 0); }
            asm volatile("" : "+r"(v), "+r"(vx));
#pragma unroll 1
            for (int j = me; j < X.nu; j += 2) {
                const int r0 = bcast(vu, 2 * j), r1 = bcast(vu, 2 * j + 1), cost = ((j < 2 ? R1A : R1) * 121 / 64 * bal) >> 8;
                const uint32_t src = sm + soff(j);
                unsigned* cn = mp.cnt + 64 * (CX + (j * NH + X.k + 42) / 48);
                mbar_wait(bar + 8 * (BR1 + j));
                mbar_wait(bar + 8 * (BIS + 1 + j));
                next = lds32(sm + O_NEXT);
                if (elect()) {
#pragma unroll
                    for (int i = 0; i < 4; i++) {
                        const int x = ((i & 1) * 96) ^ ((i & 2) * 272);
                        pace(cost);
                        tma_st2(i ? &mp.s30 : &mp.s32, src + unit_off(i), 0, r0 ^ x);
                        tma_st2(i || X.sd ? &mp.s30 : &mp.s32, src + unit_off(4 + i), 0, r1 ^ x);
                    }
                    sts32(sm + O_NEXT, next); mbar_arrive(bar + 8 * (BIS + 2 + j));
                    red_add(cn);
                    bulk_commit(); bulk_wait_read<0>();
                    mbar_arrive(bar + 8 * (BD1 + j));
                }
                __syncwarp();
            }
            if (R.fp >= 0) {
                mbar_wait(bar + 8 * (BIS + 1 + X.nu));
                next = lds32(sm + O_NEXT) + first * 2 * R2;
                uint32_t prev = 0;
                int s = 1, w = first;
#pragma unroll 1
                for (int i = 0; i < 18; i += 2) {
                    const int r0 = bcast(v, i), r1 = bcast(v, i + 1), rx = bcast(vx, i + 1);
                    const int bi = 2 * w + (s & 1);
                    const uint32_t src = sm + O_OUT + (s & 1) * STG + w * 8192;
                    mbar_wait_ph(bar + 8 * (BR2 + bi), (s >> 1) & 1);
                    const uint32_t now = until(next, NAP);
                    next = ((int)(now - next) > CREDIT2 ? now - CREDIT2 : next) + 4 * R2;
                    if (elect()) {
                        tma_st5(&mp.p16, src, 0, r0, 0, 0, 0);
                        tma_st5(&mp.p16, src + 4096, 0, r1, 0, 0, 0);
                        if (R.fp == 15) tma_st5(&mp.p16, src + 4096, 0, rx, 0, 0, 0);
                        bulk_commit();
                        bulk_wait_read<1>();
                        if (prev) mbar_arrive(prev);
                        if (w == 2) { until(now + LATE2, 0); red_add(mp.cnt + 64 * (CY + s)); mbar_arrive(bar + 8 * (BI2 + s)); }
                    }
                    __syncwarp();
                    prev = bar + 8 * (BDP + bi);
                    w += 2; if (w > 2) { w -= 3; s++; }
                }
                if (elect()) { bulk_wait_read<0>(); mbar_arrive(bar + 8 * (BD2 + me)); }
                __syncwarp();
                next = clock() + YD;
            }
#pragma unroll 1
            for (int r = me; r < 3; r += 2) {
                const int u = r * NH + R.k, ts = u / 3, cg = u - 3 * ts, tr = ts / 14, th = 7 * R.sd + tr, tw = ts - 14 * tr;
                mbar_wait(bar + 8 * (BR3 + r));
                if (r) { mbar_wait(bar + 8 * (BIS + 6 + r)); next = lds32(sm + O_NEXT); }
#pragma unroll 1
                for (int c = 0; c < 2; c++) {
                    pace(2 * R3);
                    if (elect()) tma_st4(&mp.y, sm + zoff(r) + c * 8192, 32 * cg, 0, 16 * th, 4 * tw + 2 * c);
                    __syncwarp();
                }
                if (lane == 0 && r < 2) { sts32(sm + O_NEXT, next); mbar_arrive(bar + 8 * (BIS + 7 + r)); }
                __syncwarp();
            }
            bulk_commit(); bulk_wait_read<0>();
        }
    } else {
        if (warp >= 4) {
            if (elect()) {
                const int gi = warp - 3;
#pragma unroll
                for (int i = 0; i < 8; i++) mbar_init(bar + 64 * gi + 8 * i, gi < 8 ? 1 : 12);
                if (gi < 5) {
#pragma unroll
                    for (int i = 0; i < 8; i++) mbar_init(bar + 64 * (gi + 8) + 8 * i, 4);
                }
            }
            __syncwarp();
            bar_sync(0, 288);
            if (warp < 9) asm volatile("bar.arrive %0,%1;" ::"r"(warp + 7), "r"(warp == 4 ? 160 : 64) : "memory");
            else if (warp == 10 && lane < 8) asm volatile("prefetch.tensormap [%0];" ::"l"(&mp.x6 + lane) : "memory");
            __syncwarp();
        }
        asm volatile("setmaxnreg.inc.sync.aligned.u32 160;");
        const int lane = laneid();
        const int wg = __shfl_sync(0xffffffffu, tid >> 7, 0), wq = __shfl_sync(0xffffffffu, tid >> 5, 0) & 3;
        const int pw = wg ? wg - 1 : 2;
#pragma unroll 1
        for (int it = 0; it <= pw; it++) {
            const int j = it > 0, cg = j ? pw + it - 2 : pw;
            mbar_wait(bar + 8 * (j == 0 && pw ? BWL + pw - 1 : BW + j));
            wgen(sm + (j ? O_W1 : O_W0), sm + O_WT, sm + (j ? O_W0 : O_B3) + cg * 11264, 4 * cg + wq, (2 * wip + j) & 3, lane, bar + 8 * (BWC + j),
                 j == 0 && pw < 2 ? bar + 8 * (BWL + pw) : 0, bar + 8 * (j ? BWC : BEP), sm + O_EP);
            staged(bar + 8 * (BRW + 3 * j + cg), lane);
        }
        mbar_wait(bar + 8 * BC); mbar_wait(bar + 8 * BCM);
#pragma unroll 1
        for (int r = pw; r < X.nu; r += 3) {
            p1_unit(sm + xoff(r), sm + soff(r), sm + O_C, bar + 8 * (BX + r), wg, wq, laneid());
            staged(bar + 8 * (BR1 + r), laneid());
        }
        mbar_wait(bar + 8 * BRL);
        const Role R(__shfl_sync(0xffffffffu, lds32(sm + O_ROLE), 0));
        uint32_t phw = 0;
        if (R.fp >= 0) {
            const int lane = laneid();
            uint32_t Wf[48];
            const int g = lane >> 2, q = lane & 3;
            {
                const int b = wg;
                const uint32_t p = sm + O_IN + b * STG + q * 1024 + wq * 128 + ((g ^ (2 * q) ^ (4 * ((R.fp % 11) & 1))) << 4);
                mbar_wait(bar + 8 * (BWF + b));
#pragma unroll 1
                for (int it = 0; it < 4096; it++) {
                    const uint32_t tag = ~lds32(sm + O_CM) >> 31, m = g == 7;
                    uint32_t bad = 0;
#pragma unroll
                    for (int i = 0; i < 12; i++) {
                        uint4 v = lds128((p ^ (i >= 6 ? 544 : 0)) + (i % 6) * 4096);
                        Wf[4 * i] = v.x; Wf[4 * i + 1] = v.y; Wf[4 * i + 2] = v.z; Wf[4 * i + 3] = v.w & ~m;
                        bad |= v.w ^ tag;
                    }
                    if (!bar_any(1 + wg, 128, bad & m)) break;
                    if (wq == 0) {
                        fence_async_s();
                        if (lane == 0) mbar_expect(bar + 8 * (BRT + 1 + wg), STG);
                        __syncwarp();
                        const int l = laneid(), fp = Role(lds32(sm + O_ROLE)).fp, fw = fp / 11, fh = fp - 11 * fw;
                        if (l < 3) tma_ld4(sm + O_IN + b * STG + l * 8192, &mp.wf, bar + 8 * (BRT + 1 + wg), 0, w_row(fw, fh >> 2, wg, l, lds32(sm + O_CM)) + 2 * (fh & 3), 0, 0);
                        __syncwarp();
                    }
                    mbar_wait_ph(bar + 8 * (BRT + 1 + wg), phw); phw ^= 1;
                }
                staged(bar + 8 * (BWE + b), lane);
            }
            const int ro = (lane & 6) + ((lane >> 3) & 1);
            const uint32_t o0 = sm + O_OUT + wg * 8192 + (lane >> 4) * 1024 + ro * 128 + (((2 * wq + (lane & 1)) ^ ro) << 4);
            const uint32_t m = wq == 3 && g >= 6 ? 0x10000 : 0, tg = g == 6 ? TAGZ << 16 : TAGZ;
            uint32_t ph = 0;
            const int t = 32 * wq + lane;
            uint32_t c0 = t * 128 + ((7 ^ (t & 7)) << 4) + 12, c1 = (c0 & 8191) + 16384;
            auto stale = [&](uint32_t in) { return (((lds32(in + c0) ^ TAGX) | (lds32(in + c1) ^ TAGX)) & TAGM) != 0; };
            auto landed = [&](int s, uint32_t in) {
                mbar_wait(bar + 8 * (BPF + s));
#pragma unroll 1
                for (int it = 0; it < 4096; it++) {
                    if (!bar_any(1 + wg, 128, stale(in))) break;
                    fence_async_s();
                    bar_sync(7, 384);
                    if (wg + wq == 0) {
                        if (lane == 0) mbar_expect(bar + 8 * BRT, s ? STG : 3072);
                        __syncwarp();
                        const int l = laneid();
                        if (l < 6) tma_ld5(in + l * (s ? 4096 : 512), s ? &mp.p16 : &mp.p2, bar + 8 * BRT, 0, stage_row(Role(lds32(sm + O_ROLE)), s, l, lds32(sm + O_CM), 0), 0, 0, 0);
                        __syncwarp();
                    }
                    mbar_wait_ph(bar + 8 * BRT, ph); ph ^= 1;
                }
            };
            mbar_wait(bar + 8 * BD1);
            c0 &= 2047; c1 = (c1 & 1023) + 2048;
            landed(0, sm + O_S0);
            p2_step<1>(Wf, sm + O_S0, o0, m, tg, bar, lane, wg, 0, []() {});
            staged(bar + 8 * (BR2 + 2 * wg), lane);
            c0 |= t << 7; c1 = (c0 & 8191) + 16384;
            uint32_t in = sm + O_IN;
            bool todo = true;
#pragma unroll 1
            for (int s = 1; s < 7; s++) {
                if (todo) landed(s, in);
                const uint32_t nx = in == sm + O_IN + 2 * STG ? sm + O_IN : in + STG;
                p2_step<8>(Wf, in, o0 + (s & 1) * STG, m, tg, bar, lane, wg, s, [&]() { todo = !mbar_test(bar + 8 * (BPF + s + 1)) || stale(nx); });
                todo = bar_any(1 + wg, 128, todo);
                in = nx;
                staged(bar + 8 * (BR2 + 2 * wg + (s & 1)), lane);
            }
        }
#pragma unroll 1
        for (int r = wg; r < R.nu; r += 3) {
            const int yu = r * NH + R.k, yt = yu / 3, yr = yt / 14, yc = 32 * (yu - 3 * yt), yh = 16 * (7 * R.sd + yr), yw = 4 * (yt - 14 * yr);
#pragma unroll 1
            for (int it = 0; it < 4096; it++) {
                if (p3_unit(sm + zoff(r), sm + O_C, bar + 8 * (it ? BRT + 1 + wg : BZ + r), it ? phw ^ 1 : 0, wg, wq, laneid())) break;
                if (wq == 0) {
                    fence_async_s();
                    if (laneid() == 0) mbar_expect(bar + 8 * (BRT + 1 + wg), SLAB);
                    __syncwarp();
                    const int l = laneid();
                    if (l < 8) tma_ld2(sm + zoff(r) + unit_off(l), l ? &mp.s30 : &mp.s32, bar + 8 * (BRT + 1 + wg), 0, unit_row<1>(Role(lds32(sm + O_ROLE)), r, l, lds32(sm + O_CM)));
                    __syncwarp();
                }
                phw ^= 1;
            }
            if (r < 3) staged(bar + 8 * (BR3 + r), laneid());
            else {
                fence_async_s();
                bar_sync(1 + wg, 128);
                if (wq < 2 && elect()) {
                    tma_st4(&mp.y, sm + zoff(r) + wq * 8192, yc, 0, yh, yw + 2 * wq);
                    bulk_commit(); bulk_wait_read<0>();
                }
                __syncwarp();
            }
        }
    }
}

__global__ void direct_kernel(const __nv_bfloat16* __restrict__ x, const __nv_bfloat16* __restrict__ w, __nv_bfloat16* __restrict__ y) {
    __shared__ float xs[49 * 96];
    const int h = blockIdx.x / 224, p = blockIdx.x % 224, o = threadIdx.x;
    for (int t = 0; t < 49; t++) xs[t * 96 + o] = __bfloat162float(x[(((h + 224 - t / 7) % 224) * 224 + (p + 224 - t % 7) % 224) * 96 + o]);
    __syncthreads();
    float a = 0.f;
    for (int k = 0; k < 49 * 96; k++) a += xs[k] * __bfloat162float(w[k * 96 + o]);
    y[blockIdx.x * 96 + o] = __float2bfloat16(a);
}

typedef CUresult (*EncFn)(CUtensorMap*, CUtensorMapDataType, cuuint32_t, void*, const cuuint64_t*, const cuuint64_t*, const cuuint32_t*,
                          const cuuint32_t*, CUtensorMapInterleave, CUtensorMapSwizzle, CUtensorMapL2promotion, CUtensorMapFloatOOBfill);

void enc(EncFn f, CUtensorMap* m, void* p, int rank, const cuuint64_t* dims, const cuuint64_t* strides, const cuuint32_t* box,
         CUtensorMapSwizzle sw, CUtensorMapL2promotion pr = CU_TENSOR_MAP_L2_PROMOTION_NONE) {
    cuuint32_t es[5] = {1, 1, 1, 1, 1};
    f(m, CU_TENSOR_MAP_DATA_TYPE_BFLOAT16, rank, p, dims, strides, box, es, CU_TENSOR_MAP_INTERLEAVE_NONE, sw, pr, CU_TENSOR_MAP_FLOAT_OOB_FILL_NONE);
}

}

extern "C" void kernel_launch(void* const* d_in, const int* in_sizes, int n_in, void* d_out, int out_size) {
    void* fn = nullptr; cudaDriverEntryPointQueryResult qr;
    cudaGetDriverEntryPoint("cuTensorMapEncodeTiled", &fn, cudaEnableDefault, &qr);
    EncFn f = (EncFn)fn;
    int dev = 0, sms = 0;
    cudaGetDevice(&dev);
    cudaDeviceGetAttribute(&sms, cudaDevAttrMultiProcessorCount, dev);
    if (sms < NCTA || !f || cudaFuncSetAttribute(fftconv_kernel, cudaFuncAttributeMaxDynamicSharedMemorySize, SMEM) != cudaSuccess) {
        direct_kernel<<<224 * 224, 96>>>((const __nv_bfloat16*)d_in[0], (const __nv_bfloat16*)d_in[1], (__nv_bfloat16*)d_out);
        return;
    }
    void* pS; cudaGetSymbolAddress(&pS, g_S);
    pS = (void*)(((uintptr_t)pS + (1u << 21) - 1) & ~(uintptr_t)((1u << 21) - 1));
    Maps mp;
    cudaGetSymbolAddress((void**)&mp.ctab, g_ctab); cudaGetSymbolAddress((void**)&mp.wtab, g_wtab); cudaGetSymbolAddress((void**)&mp.cnt, g_cnt);
    mp.s = (unsigned char*)pS;
    { cuuint64_t d[4] = {256, NPAGE << 12, 4, 2}, s[3] = {512, 1 << 14, 1 << 18}; cuuint32_t b[4] = {256, 2, 4, 2}; enc(f, &mp.wf, pS, 4, d, s, b, CU_TENSOR_MAP_SWIZZLE_NONE); }
    {
        cuuint64_t d[3] = {96, 224, 224}, s[2] = {192, 43008};
        cuuint32_t b6[3] = {32, 8, 6}, b16[3] = {32, 8, 16}, b22[3] = {32, 8, 22};
        enc(f, &mp.x22, d_in[0], 3, d, s, b22, CU_TENSOR_MAP_SWIZZLE_64B, CU_TENSOR_MAP_L2_PROMOTION_L2_128B);
        enc(f, &mp.x6, d_in[0], 3, d, s, b6, CU_TENSOR_MAP_SWIZZLE_64B, CU_TENSOR_MAP_L2_PROMOTION_L2_128B);
        enc(f, &mp.x16, d_in[0], 3, d, s, b16, CU_TENSOR_MAP_SWIZZLE_64B, CU_TENSOR_MAP_L2_PROMOTION_L2_128B);
    }
    { cuuint64_t d[4] = {96, 4, 224, 56}, s[3] = {192, 43008, 768}; cuuint32_t b[4] = {32, 4, 16, 2}; enc(f, &mp.y, d_out, 4, d, s, b, CU_TENSOR_MAP_SWIZZLE_64B); }
    {
        cuuint64_t d[2] = {64, NPAGE << 14}, s[1] = {128};
        cuuint32_t b32[2] = {64, 32}, b30[2] = {64, 30};
        enc(f, &mp.s32, pS, 2, d, s, b32, CU_TENSOR_MAP_SWIZZLE_128B);
        enc(f, &mp.s30, pS, 2, d, s, b30, CU_TENSOR_MAP_SWIZZLE_128B);
    }
    {
        cuuint64_t d[5] = {64, NPAGE << 14, 4, 2, 2}, s[4] = {128, 1 << 14, 1 << 18, 1 << 20};
        cuuint32_t b16[5] = {64, 2, 4, 2, 2}, b2[5] = {64, 2, 2, 1, 1};
        enc(f, &mp.p16, pS, 5, d, s, b16, CU_TENSOR_MAP_SWIZZLE_128B);
        enc(f, &mp.p2, pS, 5, d, s, b2, CU_TENSOR_MAP_SWIZZLE_128B);
    }
    { cuuint64_t d[3] = {64, 144, 49}, s[2] = {128, 18432}; cuuint32_t b[3] = {64, 3, 49}; enc(f, &mp.w, d_in[1], 3, d, s, b, CU_TENSOR_MAP_SWIZZLE_128B); }
    fftconv_kernel<<<NCTA, 512, SMEM>>>(mp);
}
```

```cpp
#include <cuda_runtime.h>
#include <cuda_bf16.h>
#include <cuda.h>
#include <stdint.h>

namespace {

constexpr int RW = 260;
constexpr int R1A = 338;
constexpr int R1 = 283;
constexpr int R2 = 245;
constexpr int R3 = 280;
constexpr int BAL = 248;
constexpr int CREDIT = 350;
constexpr int CREDIT2 = 1500;
constexpr int YD = 500;
constexpr int LATE2 = 400;
constexpr int XD0 = 1900;
constexpr int XE = 300;
constexpr int XD1 = 3400;
constexpr int XD = 600;
constexpr int LPW = 250;
constexpr int VT = 1900;
constexpr int NAP = 30;
constexpr int WIN = 4;

constexpr int NCTA = 132, NH = 66;
constexpr int NUH = 294;
constexpr int NFP = 121;
constexpr int BLK = 33792;
constexpr int SLAB = 242 * 128;
constexpr int WPIECE = 19456;
constexpr int STG = 24576;
constexpr int NPS = 16, NPAGE = 21;
constexpr int O_B4 = 0, O_B0 = 87040, O_B2 = O_B0 + 2 * BLK, O_B3 = O_B0 + 3 * BLK;
constexpr int O_W1 = 0, O_W0 = 2 * WPIECE, O_WT = 4 * WPIECE;
constexpr int O_IN = 33792, O_OUT = O_IN + 3 * STG, O_Z3 = O_IN, O_S0 = O_OUT + 4096, O_Z4 = 124928;
constexpr int O_C = 222208, O_BAR = 230912, SMEM = 232448;
constexpr int C_P1A = 0, C_P1B = 2560, C_P3 = 7168, C_BYTES = 8704, WT_BYTES = 6912;
constexpr int BC = 0, BW = 1, BX = 3, BZ = 8, BWF = 13, BPF = 16, BCM = 23, BDW = 24, BD1 = 26, BDP = 31, BD2 = 37, BIS = 39, BEP = 50, BI2 = 51, BRT = 58, BRL = 62;
constexpr int BPE = 64, BWC = 70;
constexpr int BR2 = 72, BRW = 78, BWL = 84, BR1 = 86, BR3 = 91, BWE = 96;
constexpr int O_NEXT = O_BAR + 1016, O_ROLE = O_BAR + 1000, O_PT = O_BAR + 976, O_CM = O_BAR + 1008, O_PERM = O_BAR + 944, O_EP = O_BAR + 1012;
constexpr uint32_t TAGM = 0x00010001u, TAGX = 0x00000001u, TAGZ = 0x00010000u;

constexpr uint16_t LUT_A[11] = {0x3f95, 0x3f92, 0x3f8c, 0x3f83, 0x3f6f, 0x3f53, 0x3f33, 0x3f0f, 0x3ed1, 0x3e7e, 0x3daa};
constexpr uint16_t LUT_B[11] = {0x3fe9, 0x3fe4, 0x3fdb, 0x3fcd, 0x3fbb, 0x3fa5, 0x3f8c, 0x3f60, 0x3f23, 0x3ec7, 0x3e05};
constexpr uint16_t LUT_W[12] = {0x3abb, 0x3ab9, 0x3ab3, 0x3aaa, 0x3a9d, 0x3a8d, 0x3a75, 0x3a4a, 0x3a1b, 0x39d3, 0x3955, 0};
constexpr uint16_t basis(int setb, int f, int a, int sn) {
    if (f < 0 || f > 10 || a < 0 || a > 21) return 0;
    int k = ((2 * f + 1) * (2 * a - 21) - 22 * sn + 88 * 7) % 88;
    if (k > 44) k = 88 - k;
    int neg = 0;
    if (k > 22) { k = 44 - k; neg = 1; }
    return (uint16_t)((setb ? LUT_B[k >> 1] : LUT_A[k >> 1]) | (neg << 15));
}
constexpr uint16_t neg16(uint16_t v) { return v ? (uint16_t)(v ^ 0x8000) : v; }
constexpr uint16_t wcoef(int fw, int fl, int sn, int tap) {
    if (fl > 21) return 0;
    int fh = fl >> 1, kh = tap / 7, kw = tap - 7 * kh;
    int u = (2 * fh + 1) * kh;
    if (fl & 1) u = -u;
    int k = (u + (2 * fw + 1) * kw - 11 * sn + 44 * 4) % 44;
    if (k > 22) k = 44 - k;
    int neg = 0;
    if (k > 11) { k = 22 - k; neg = 1; }
    return (uint16_t)(LUT_W[k] | (neg << 15));
}
struct alignas(128) CTab { uint16_t v[C_BYTES / 2]; };
struct alignas(128) WTab { uint16_t v[WT_BYTES / 2]; };
constexpr CTab make_ctab() {
    CTab t{};
    for (int lane = 0; lane < 32; lane++) {
        int g = lane >> 2, q = lane & 3;
        for (int r = 0; r < 18; r++) {
            int quad = r >> 2, j = r & 3;
            int set = quad < 3 ? quad : (quad == 3 ? 1 + (j >> 1) : 0);
            int sn = (j ^ (set == 0 ? g : g >> 1)) & 1;
            int t8 = quad < 3 ? 1 + (j >> 1) : 0;
            int b = 8 * t8 + 2 * q - 2;
            int fw = set == 0 ? g : (((g & 1) == set - 1) ? 8 + (g >> 1) : -1);
            int o = (C_P1A + (quad * 32 + lane) * 16 + j * 4) / 2;
            t.v[o] = basis(0, fw, b, sn); t.v[o + 1] = basis(0, fw, b + 1, sn);
        }
        for (int r = 0; r < 12; r++) {
            int o = (C_P3 + ((r >> 2) * 32 + lane) * 16 + (r & 3) * 4) / 2;
            if (r < 6) {
                int a = 6 + g + 8 * (r & 1), fh = 4 * (r >> 1) + q;
                t.v[o] = basis(0, fh, a, 0); t.v[o + 1] = basis(0, fh, a, 1);
            } else {
                int be = r < 8 ? r - 6 : (r - 8) >> 1, nu = r < 8 ? 2 : (r & 1);
                int b = 6 + 8 * be + 4 * (g & 1) + (g >> 1);
                t.v[o] = basis(1, 4 * nu + q, b, 0); t.v[o + 1] = basis(1, 4 * nu + q, b, 1);
            }
        }
    }
    for (int kc = 0; kc < 6; kc++)
        for (int nb = 0; nb < 6; nb++)
            for (int n = 0; n < 8; n++)
                for (int k = 0; k < 8; k++) {
                    int nu = kc >> 1, ds = kc & 1, im = nb & 1, fh = 4 * (nb >> 1) + (n >> 1), mi = n & 1;
                    int a = nu == 0 ? 6 + k : (nu == 1 ? 14 + k : (k < 6 ? k : -1));
                    uint16_t v = basis(0, fh, a, ds ^ im);
                    if (ds != im && (im ? mi : !mi)) v = neg16(v);
                    t.v[C_P1B / 2 + ((kc * 6 + nb) * 8 + n) * 8 + k] = v;
                }
    return t;
}
constexpr WTab make_wtab(int fw) {
    WTab t{};
    for (int nb = 0; nb < 6; nb++)
        for (int n = 0; n < 8; n++) {
            for (int tap = 0; tap < 48; tap++) t.v[(((tap >> 3) * 6 + nb) * 8 + n) * 8 + (tap & 7)] = wcoef(fw, 4 * nb + (n >> 1), n & 1, tap);
            t.v[((7 * 6 + nb) * 8 + n) * 8] = wcoef(fw, 4 * nb + (n >> 1), n & 1, 48);
        }
    return t;
}
__device__ const CTab g_ctab = make_ctab();
__device__ const WTab g_wtab[11] = {make_wtab(0), make_wtab(1), make_wtab(2), make_wtab(3), make_wtab(4), make_wtab(5),
                                    make_wtab(6), make_wtab(7), make_wtab(8), make_wtab(9), make_wtab(10)};

__device__ __align__(1024) unsigned char g_S[(size_t)(NPAGE + 1) << 21];
constexpr int CT = 0, CX = 2, CY = 10, CW = 18, CD = 29, CV = 32;
__device__ __align__(512) unsigned g_cnt[40 * 64];

struct Maps {
    const unsigned char* ctab; const unsigned char* wtab; unsigned* cnt; unsigned char* s;
    alignas(64) CUtensorMap w, x22, x6, x16, wf, s32, s30, p16, p2, y;
};

__device__ __forceinline__ uint32_t s2u(const void* p) { return (uint32_t)__cvta_generic_to_shared(p); }
__device__ __forceinline__ void mbar_init(uint32_t b, int c) { asm volatile("mbarrier.init.shared::cta.b64 [%0],%1;" ::"r"(b), "r"(c) : "memory"); }
__device__ __forceinline__ void mbar_expect(uint32_t b, uint32_t tx) { asm volatile("mbarrier.arrive.expect_tx.shared::cta.b64 _,[%0],%1;" ::"r"(b), "r"(tx) : "memory"); }
__device__ __forceinline__ void mbar_arrive(uint32_t b) { asm volatile("mbarrier.arrive.shared::cta.b64 _,[%0];" ::"r"(b) : "memory"); }
__device__ __forceinline__ bool mbar_try(uint32_t b, uint32_t ph) {
    uint32_t ok;
    asm volatile("{.reg .pred p; mbarrier.try_wait.parity.shared::cta.b64 p,[%1],%2; selp.u32 %0,1,0,p;}" : "=r"(ok) : "r"(b), "r"(ph) : "memory");
    return ok;
}
__device__ __forceinline__ void mbar_wait_ph(uint32_t b, uint32_t ph) {
    if (mbar_try(b, ph)) return;
#pragma unroll 1
    for (int it = 0; it < (1 << 16); it++)
        if (mbar_try(b, ph)) return;
}
__device__ __forceinline__ void mbar_wait(uint32_t b) { mbar_wait_ph(b, 0); }
__device__ __forceinline__ void region_end(uint32_t b) {
    int it = 0;
    while (!mbar_try(b, 0) && ++it < (1 << 16)) {}
}
__device__ __forceinline__ bool mbar_test(uint32_t b) {
    uint32_t ok;
    asm volatile("{.reg .pred p; mbarrier.test_wait.parity.shared::cta.b64 p,[%1],0; selp.u32 %0,1,0,p;}" : "=r"(ok) : "r"(b) : "memory");
    return ok;
}
__device__ __forceinline__ bool elect() {
    uint32_t r;
    asm volatile("{.reg .pred p; elect.sync _|p,0xffffffff; selp.u32 %0,1,0,p;}" : "=r"(r));
    return r;
}
__device__ __forceinline__ uint32_t until(uint32_t t, int nap) {
    uint32_t now = clock();
    while ((int)(now - t) < 0) { if (nap) __nanosleep(nap); now = clock(); }
    return now;
}
__device__ __forceinline__ int bcast(int v, int l) { return __shfl_sync(0xffffffffu, v, l); }
__device__ __forceinline__ void poll(const unsigned* c, unsigned tgt) {
    unsigned v; int it = 0;
    do { asm volatile("ld.acquire.gpu.global.u32 %0,[%1];" : "=r"(v) : "l"(c) : "memory"); } while (v < tgt && ++it < (1 << 16));
}
__device__ __forceinline__ bool bar_any(int id, int n, bool v) {
    uint32_t r;
    asm volatile("{.reg .pred p,q; setp.ne.u32 p,%3,0; bar.red.or.pred q,%1,%2,p; selp.u32 %0,1,0,q;}" : "=r"(r) : "r"(id), "r"(n), "r"((uint32_t)v) : "memory");
    return __any_sync(0xffffffffu, r);
}
__device__ __forceinline__ int laneid() { int l; asm volatile("mov.u32 %0,%%laneid;" : "=r"(l)); return l; }
__device__ __forceinline__ uint32_t lds32(uint32_t a) { uint32_t v; asm volatile("ld.shared.u32 %0,[%1];" : "=r"(v) : "r"(a) : "memory"); return v; }
__device__ __forceinline__ uint32_t lds8(uint32_t a) { uint32_t v; asm volatile("ld.shared.u8 %0,[%1];" : "=r"(v) : "r"(a) : "memory"); return v; }
__device__ __forceinline__ uint32_t tagged(uint32_t v, uint32_t m, uint32_t t) { return (v & ~m) | (t & m); }
__device__ __forceinline__ void red_add(unsigned* c, unsigned v = 1) { asm volatile("red.relaxed.gpu.global.add.u32 [%0],%1;" ::"l"(c), "r"(v) : "memory"); }
__device__ __forceinline__ void fence_async_s() { asm volatile("fence.proxy.async.shared::cta;" ::: "memory"); }
__device__ __forceinline__ void bulk_ld(uint32_t dst, const void* src, uint32_t bytes, uint32_t bar) {
    asm volatile("cp.async.bulk.shared::cluster.global.mbarrier::complete_tx::bytes [%0],[%1],%2,[%3];" ::"r"(dst), "l"(src), "r"(bytes), "r"(bar) : "memory");
}
__device__ __forceinline__ void tma_ld2(uint32_t dst, const CUtensorMap* m, uint32_t bar, int c0, int c1) {
    asm volatile("cp.async.bulk.tensor.2d.shared::cluster.global.mbarrier::complete_tx::bytes [%0],[%1,{%3,%4}],[%2];" ::"r"(dst), "l"(m), "r"(bar), "r"(c0), "r"(c1) : "memory");
}
__device__ __forceinline__ void tma_ld3(uint32_t dst, const CUtensorMap* m, uint32_t bar, int c0, int c1, int c2) {
    asm volatile("cp.async.bulk.tensor.3d.shared::cluster.global.mbarrier::complete_tx::bytes [%0],[%1,{%3,%4,%5}],[%2];" ::"r"(dst), "l"(m), "r"(bar), "r"(c0), "r"(c1), "r"(c2) : "memory");
}
__device__ __forceinline__ void tma_ld4(uint32_t dst, const CUtensorMap* m, uint32_t bar, int c0, int c1, int c2, int c3) {
    asm volatile("cp.async.bulk.tensor.4d.shared::cluster.global.mbarrier::complete_tx::bytes [%0],[%1,{%3,%4,%5,%6}],[%2];" ::"r"(dst), "l"(m), "r"(bar), "r"(c0), "r"(c1), "r"(c2), "r"(c3) : "memory");
}
__device__ __forceinline__ void bulk_st(void* dst, uint32_t src, uint32_t bytes) {
    asm volatile("cp.async.bulk.global.shared::cta.bulk_group [%0],[%1],%2;" ::"l"(dst), "r"(src), "r"(bytes) : "memory");
}
__device__ __forceinline__ void tma_ld5(uint32_t dst, const CUtensorMap* m, uint32_t bar, int c0, int c1, int c2, int c3, int c4) {
    asm volatile("cp.async.bulk.tensor.5d.shared::cluster.global.mbarrier::complete_tx::bytes [%0],[%1,{%3,%4,%5,%6,%7}],[%2];" ::"r"(dst), "l"(m), "r"(bar), "r"(c0), "r"(c1), "r"(c2), "r"(c3), "r"(c4) : "memory");
}
__device__ __forceinline__ void tma_st2(const CUtensorMap* m, uint32_t src, int c0, int c1) {
    asm volatile("cp.async.bulk.tensor.2d.global.shared::cta.bulk_group [%0,{%2,%3}],[%1];" ::"l"(m), "r"(src), "r"(c0), "r"(c1) : "memory");
}
__device__ __forceinline__ void tma_st4(const CUtensorMap* m, uint32_t src, int c0, int c1, int c2, int c3) {
    asm volatile("cp.async.bulk.tensor.4d.global.shared::cta.bulk_group [%0,{%2,%3,%4,%5}],[%1];" ::"l"(m), "r"(src), "r"(c0), "r"(c1), "r"(c2), "r"(c3) : "memory");
}
__device__ __forceinline__ void tma_st5(const CUtensorMap* m, uint32_t src, int c0, int c1, int c2, int c3, int c4) {
    asm volatile("cp.async.bulk.tensor.5d.global.shared::cta.bulk_group [%0,{%2,%3,%4,%5,%6}],[%1];" ::"l"(m), "r"(src), "r"(c0), "r"(c1), "r"(c2), "r"(c3), "r"(c4) : "memory");
}
__device__ __forceinline__ void bulk_commit() { asm volatile("cp.async.bulk.commit_group;" ::: "memory"); }
template <int N> __device__ __forceinline__ void bulk_wait_read() { asm volatile("cp.async.bulk.wait_group.read %0;" ::"n"(N) : "memory"); }
__device__ __forceinline__ void bar_sync(int id, int n) { asm volatile("bar.sync %0,%1;" ::"r"(id), "r"(n) : "memory"); }

__device__ __forceinline__ uint4 lds128(uint32_t a) {
    uint4 v; asm volatile("ld.shared.v4.u32 {%0,%1,%2,%3},[%4];" : "=r"(v.x), "=r"(v.y), "=r"(v.z), "=r"(v.w) : "r"(a)); return v;
}
__device__ __forceinline__ void sts128(uint32_t a, uint32_t x, uint32_t y, uint32_t z, uint32_t w) {
    asm volatile("st.shared.v4.u32 [%0],{%1,%2,%3,%4};" ::"r"(a), "r"(x), "r"(y), "r"(z), "r"(w) : "memory");
}
__device__ __forceinline__ void sts64(uint32_t a, uint32_t x, uint32_t y) { asm volatile("st.shared.v2.u32 [%0],{%1,%2};" ::"r"(a), "r"(x), "r"(y) : "memory"); }
__device__ __forceinline__ void sts128p(uint32_t a, uint32_t x, uint32_t y, uint32_t z, uint32_t w, bool p) {
    asm volatile("{.reg .pred p; setp.ne.u32 p,%5,0; @p st.shared.v4.u32 [%0],{%1,%2,%3,%4};}" ::"r"(a), "r"(x), "r"(y), "r"(z), "r"(w), "r"((uint32_t)p) : "memory");
}
__device__ __forceinline__ void sts32(uint32_t a, uint32_t x) { asm volatile("st.shared.u32 [%0],%1;" ::"r"(a), "r"(x) : "memory"); }
__device__ __forceinline__ uint32_t pk(float lo, float hi) { uint32_t r; asm("cvt.rn.bf16x2.f32 %0,%1,%2;" : "=r"(r) : "f"(hi), "f"(lo)); return r; }

__device__ __forceinline__ uint32_t pkv(float lo, float hi) { uint32_t r; asm volatile("cvt.rn.bf16x2.f32 %0,%1,%2;" : "=r"(r) : "f"(hi), "f"(lo)); return r; }

__device__ __forceinline__ void mma16z(float* d, uint32_t a0, uint32_t a1, uint32_t a2, uint32_t a3, uint32_t b0, uint32_t b1) {
    asm("mma.sync.aligned.m16n8k16.row.col.f32.bf16.bf16.f32 {%0,%1,%2,%3},{%4,%5,%6,%7},{%8,%9},{%10,%10,%10,%10};"
        : "=f"(d[0]), "=f"(d[1]), "=f"(d[2]), "=f"(d[3]) : "r"(a0), "r"(a1), "r"(a2), "r"(a3), "r"(b0), "r"(b1), "f"(0.f));
}
__device__ __forceinline__ void mma16(float* d, uint32_t a0, uint32_t a1, uint32_t a2, uint32_t a3, uint32_t b0, uint32_t b1) {
    asm("mma.sync.aligned.m16n8k16.row.col.f32.bf16.bf16.f32 {%0,%1,%2,%3},{%4,%5,%6,%7},{%8,%9},{%0,%1,%2,%3};"
        : "+f"(d[0]), "+f"(d[1]), "+f"(d[2]), "+f"(d[3]) : "r"(a0), "r"(a1), "r"(a2), "r"(a3), "r"(b0), "r"(b1));
}
__device__ __forceinline__ void mma8(float* d, uint32_t a0, uint32_t a1, uint32_t b0) {
    asm("mma.sync.aligned.m16n8k8.row.col.f32.bf16.bf16.f32 {%0,%1,%2,%3},{%4,%5},{%6},{%0,%1,%2,%3};"
        : "+f"(d[0]), "+f"(d[1]), "+f"(d[2]), "+f"(d[3]) : "r"(a0), "r"(a1), "r"(b0));
}
__device__ __forceinline__ void wg_fence() { asm volatile("wgmma.fence.sync.aligned;" ::: "memory"); }
__device__ __forceinline__ void wg_commit() { asm volatile("wgmma.commit_group.sync.aligned;" ::: "memory"); }
template <int N> __device__ __forceinline__ void wg_wait() { asm volatile("wgmma.wait_group.sync.aligned %0;" ::"n"(N) : "memory"); }
template <int N> __device__ __forceinline__ void pin(float (&d)[N]) {
#pragma unroll
    for (int i = 0; i < N; i++) asm volatile("" : "+f"(d[i])::"memory");
}
#define ACC8(o) "+f"(d[o]), "+f"(d[o + 1]), "+f"(d[o + 2]), "+f"(d[o + 3]), "+f"(d[o + 4]), "+f"(d[o + 5]), "+f"(d[o + 6]), "+f"(d[o + 7])
#define OUT8(o) "=f"(d[o]), "=f"(d[o + 1]), "=f"(d[o + 2]), "=f"(d[o + 3]), "=f"(d[o + 4]), "=f"(d[o + 5]), "=f"(d[o + 6]), "=f"(d[o + 7])
template <int ACC> __device__ __forceinline__ void wgmma48(float (&d)[24], uint32_t a0, uint32_t a1, uint32_t a2, uint32_t a3, uint64_t desc) {
    if (ACC)
        asm volatile("wgmma.mma_async.sync.aligned.m64n48k16.f32.bf16.bf16 "
                     "{%0,%1,%2,%3,%4,%5,%6,%7,%8,%9,%10,%11,%12,%13,%14,%15,%16,%17,%18,%19,%20,%21,%22,%23},{%24,%25,%26,%27},%28,%29,1,1,0;"
                     : ACC8(0), ACC8(8), ACC8(16) : "r"(a0), "r"(a1), "r"(a2), "r"(a3), "l"(desc), "n"(ACC & 1));
    else
        asm volatile("wgmma.mma_async.sync.aligned.m64n48k16.f32.bf16.bf16 "
                     "{%0,%1,%2,%3,%4,%5,%6,%7,%8,%9,%10,%11,%12,%13,%14,%15,%16,%17,%18,%19,%20,%21,%22,%23},{%24,%25,%26,%27},%28,0,1,1,0;"
                     : OUT8(0), OUT8(8), OUT8(16) : "r"(a0), "r"(a1), "r"(a2), "r"(a3), "l"(desc));
}
template <int ACC> __device__ __forceinline__ void wgmma_p2(float (&d)[32], const uint32_t* a, uint64_t desc) {
    if (ACC)
        asm volatile("wgmma.mma_async.sync.aligned.m64n64k16.f32.bf16.bf16 "
                     "{%0,%1,%2,%3,%4,%5,%6,%7,%8,%9,%10,%11,%12,%13,%14,%15,%16,%17,%18,%19,%20,%21,%22,%23,%24,%25,%26,%27,%28,%29,%30,%31},{%32,%33,%34,%35},%36,1,1,1,0;"
                     : ACC8(0), ACC8(8), ACC8(16), ACC8(24) : "r"(a[0]), "r"(a[1]), "r"(a[2]), "r"(a[3]), "l"(desc));
    else
        asm volatile("wgmma.mma_async.sync.aligned.m64n64k16.f32.bf16.bf16 "
                     "{%0,%1,%2,%3,%4,%5,%6,%7,%8,%9,%10,%11,%12,%13,%14,%15,%16,%17,%18,%19,%20,%21,%22,%23,%24,%25,%26,%27,%28,%29,%30,%31},{%32,%33,%34,%35},%36,0,1,1,0;"
                     : OUT8(0), OUT8(8), OUT8(16), OUT8(24) : "r"(a[0]), "r"(a[1]), "r"(a[2]), "r"(a[3]), "l"(desc));
}
template <int ACC> __device__ __forceinline__ void wgmma_p2(float (&d)[4], const uint32_t* a, uint64_t desc) {
    if (ACC)
        asm volatile("wgmma.mma_async.sync.aligned.m64n8k16.f32.bf16.bf16 {%0,%1,%2,%3},{%4,%5,%6,%7},%8,1,1,1,0;"
                     : "+f"(d[0]), "+f"(d[1]), "+f"(d[2]), "+f"(d[3]) : "r"(a[0]), "r"(a[1]), "r"(a[2]), "r"(a[3]), "l"(desc));
    else
        asm volatile("wgmma.mma_async.sync.aligned.m64n8k16.f32.bf16.bf16 {%0,%1,%2,%3},{%4,%5,%6,%7},%8,0,1,1,0;"
                     : "=f"(d[0]), "=f"(d[1]), "=f"(d[2]), "=f"(d[3]) : "r"(a[0]), "r"(a[1]), "r"(a[2]), "r"(a[3]), "l"(desc));
}
__device__ __forceinline__ uint64_t desc_tab(uint32_t a) { return (uint64_t)((a & 0x3FFFF) >> 4) | ((uint64_t)(768 >> 4) << 16) | ((uint64_t)(128 >> 4) << 32); }

__device__ __forceinline__ void staged(uint32_t bar, int lane) {
    fence_async_s();
    __syncwarp();
    if (lane == 0) mbar_arrive(bar);
}

__device__ __forceinline__ void wgen(uint32_t win, uint32_t tab, uint32_t out, int c, int qq, int lane, uint32_t consumed, uint32_t chain, uint32_t gate, uint32_t cma) {
    uint32_t A[28];
    int mi = lane >> 3, rr = lane & 7;
    int L = 12 * (mi & 1) + c;
#pragma unroll
    for (int s = 0; s < 7; s++) {
        int u = s < 6 ? s / 3 : mi >> 1;
        int tap = s < 6 ? 16 * (s % 3) + 8 * (mi >> 1) + rr : 48;
        int line = 3 * tap + (L >> 3);
        uint32_t ad = win + u * WPIECE + line * 128 + (((L ^ line) & 7) << 4);
        asm volatile("ldmatrix.sync.aligned.m8n8.x4.trans.shared.b16 {%0,%1,%2,%3},[%4];"
                     : "=r"(A[4 * s]), "=r"(A[4 * s + 1]), "=r"(A[4 * s + 2]), "=r"(A[4 * s + 3]) : "r"(ad));
    }
    float d0[24], d1[24];
    uint64_t ds = desc_tab(tab);
    wg_fence();
    wgmma48<0>(d0, A[0], A[1], A[2], A[3], ds);
    wgmma48<0>(d1, A[12], A[13], A[14], A[15], ds);
    wgmma48<1>(d0, A[4], A[5], A[6], A[7], ds + 96);
    wgmma48<1>(d1, A[16], A[17], A[18], A[19], ds + 96);
    wgmma48<1>(d0, A[8], A[9], A[10], A[11], ds + 192);
    wgmma48<1>(d1, A[20], A[21], A[22], A[23], ds + 192);
    wgmma48<1>(d0, A[24], A[25], A[26], A[27], ds + 336);
    wgmma48<1>(d1, A[24], A[25], A[26], A[27], ds + 288);
    wg_commit();
    if (lane == 0) { if (chain) mbar_arrive(chain); mbar_arrive(consumed); }
    mbar_wait(gate);
    const uint32_t tag = ~lds32(cma);
    wg_wait<0>();
    pin(d0); pin(d1);
    int g = lane >> 2, q = lane & 3;
    const uint32_t p = out + q * 512 + (8 * (c & 3) + (g ^ (2 * (q ^ qq)))) * 16;
#pragma unroll
    for (int nb = 0; nb < 6; nb++)
        if (nb < 5 || q < 2)
            sts128(p + nb * 2048, pk(d0[4 * nb], d0[4 * nb + 2]), pk(d0[4 * nb + 1], d0[4 * nb + 3]), pk(d1[4 * nb], d1[4 * nb + 2]),
                   tagged(pk(d1[4 * nb + 1], d1[4 * nb + 3]), g == 7, tag));
}

__device__ __forceinline__ void p1_unit(uint32_t blk, uint32_t out, uint32_t cst, uint32_t full, int wg, int wq, int lane) {
    int g = lane >> 2, q = lane & 3;
    uint32_t T[20];
#pragma unroll
    for (int v = 0; v < 5; v++) { uint4 x = lds128(cst + C_P1A + (v * 32 + lane) * 16); T[4 * v] = x.x; T[4 * v + 1] = x.y; T[4 * v + 2] = x.z; T[4 * v + 3] = x.w; }
    uint32_t P[6][3][4];
    const uint32_t a0 = blk + g * 512 + (2 * q + (g & 1)) * 64 + ((wq ^ q) << 4), a1 = a0 ^ 64;
    const uint32_t sel0 = (g & 1) ? 0x1054 : 0x5410, sel1 = sel0 + 0x2222;
    uint32_t vv[2][3][2][4];
    auto ldv = [&](int nu) {
        const int ro = (nu == 0 ? 6 : (nu == 1 ? 14 : 0)) * 512;
#pragma unroll
        for (int t = 0; t < 3; t++)
#pragma unroll
            for (int e = 0; e < 2; e++) {
                uint4 x = lds128((e ? a1 : a0) + t * 11264 + ro);
                vv[nu & 1][t][e][0] = x.x; vv[nu & 1][t][e][1] = x.y; vv[nu & 1][t][e][2] = x.z; vv[nu & 1][t][e][3] = x.w;
            }
    };
    mbar_wait(full);
    ldv(0);
#pragma unroll
    for (int nu = 0; nu < 3; nu++) {
        if (nu < 2) ldv(nu + 1);
        auto& v = vv[nu & 1];
#pragma unroll
        for (int ch = 0; ch < 4; ch++) {
            const uint32_t sel = (ch & 1) ? sel1 : sel0;
            uint32_t b[2][3];
#pragma unroll
            for (int hf = 0; hf < 2; hf++)
#pragma unroll
                for (int t = 0; t < 3; t++) b[hf][t] = __byte_perm(v[t][0][(ch >> 1) + 2 * hf], v[t][1][(ch >> 1) + 2 * hf], sel);
            float d1[4];
            mma16z(d1, T[12], T[13], T[14], T[15], b[0][0], b[1][0]);
#pragma unroll
            for (int hf = 0; hf < 2; hf++) {
                float d0[4];
                mma16z(d0, T[0], T[1], T[2], T[3], b[hf][1], b[hf][2]);
                mma8(d0, T[16], T[17], b[hf][0]);
                mma16(d1, T[4 + 4 * hf], T[5 + 4 * hf], T[6 + 4 * hf], T[7 + 4 * hf], b[hf][1], b[hf][2]);
                P[(ch >> 1) + 2 * hf][nu][ch & 1] = pk(d0[0], d0[1]);
                P[(ch >> 1) + 2 * hf][nu][2 + (ch & 1)] = pk(d0[2], d0[3]);
            }
            P[4 + (ch >> 1)][nu][ch & 1] = pk(d1[0], d1[1]);
            P[4 + (ch >> 1)][nu][2 + (ch & 1)] = pk(d1[2], d1[3]);
        }
#pragma unroll
        for (int pb = 0; pb < 6; pb++) asm volatile("" : "+r"(P[pb][nu][0]), "+r"(P[pb][nu][1]), "+r"(P[pb][nu][2]), "+r"(P[pb][nu][3]));
                if (nu < 2) region_end(cst + (O_BAR - O_C) + 8 * BC);
    }
    const uint64_t ds = desc_tab(cst + C_P1B);
    float dA[24], dB[24];
    auto issue = [&](int pb) {
        wg_fence();
        if (pb == 4) {
            wgmma48<0>(dA, P[pb][0][0], P[pb][0][1], P[pb][0][2], P[pb][0][3], ds);
            wgmma48<0>(dB, P[pb + 1][0][0], P[pb + 1][0][1], P[pb + 1][0][2], P[pb + 1][0][3], ds);
        } else {
            wgmma48<2>(dA, P[pb][0][0], P[pb][0][1], P[pb][0][2], P[pb][0][3], ds);
            wgmma48<2>(dB, P[pb + 1][0][0], P[pb + 1][0][1], P[pb + 1][0][2], P[pb + 1][0][3], ds);
        }
        wgmma48<1>(dA, P[pb][1][0], P[pb][1][1], P[pb][1][2], P[pb][1][3], ds + 96);
        wgmma48<1>(dB, P[pb + 1][1][0], P[pb + 1][1][1], P[pb + 1][1][2], P[pb + 1][1][3], ds + 96);
        wgmma48<1>(dA, P[pb][2][0], P[pb][2][1], P[pb][2][2], P[pb][2][3], ds + 192);
        wgmma48<1>(dB, P[pb + 1][2][0], P[pb + 1][2][1], P[pb + 1][2][2], P[pb + 1][2][3], ds + 192);
        wg_commit();
    };
    issue(4);
    bar_sync(1 + wg, 128);
    asm volatile("" : "+r"(g), "+r"(q));
    wg_wait<0>(); pin(dA); pin(dB);
    uint32_t o[12][2];
#pragma unroll
    for (int k = 0; k < 12; k++) { const int i = 4 * (k >> 1) + (k & 1); o[k][0] = pkv(dA[i], dA[i + 2]); o[k][1] = pkv(dB[i], dB[i + 2]); }
    issue(0);
    {
        const int sw = (g >> 1) & 1, r0 = 2 * (lds8(cst + (O_PERM - O_C) + (g < 6 ? 8 + (g >> 1) : 1)) * 11 + q) + sw;
        const uint32_t a0 = out + r0 * 128 + ((((4 * sw + wq) ^ r0) & 7) << 4) + 8 * (g & 1);
        const uint32_t m = wq == 3 && (g & 1) ? TAGM : 0, m0 = sw ? m : 0, m1 = m ^ m0;
#pragma unroll
        for (int k = 11; k >= 0; k--) {
            sts64((a0 ^ ((k & 2) * 72 + (k & 1) * 64)) + 1024 * (k >> 2), o[k][0], tagged(o[k][1], (k & 1) ? m1 : m0, TAGX));
            if (k == 8) __syncwarp();
        }
    }
    wg_wait<0>(); pin(dA); pin(dB);
#pragma unroll
    for (int k = 0; k < 12; k++) { const int i = 4 * (k >> 1) + (k & 1); o[k][0] = pkv(dA[i], dA[i + 2]); o[k][1] = pkv(dB[i], dB[i + 2]); }
    issue(2);
    region_end(cst + (O_BAR - O_C) + 8 * BC);
    const int r0 = 2 * (lds8(cst + (O_PERM - O_C) + g) * 11 + q) + (g & 1);
    const uint32_t ao = out + r0 * 128 + ((((4 * (g & 1) + wq) ^ r0) & 7) << 4);
    const uint32_t m = wq == 3 ? TAGM : 0, m0 = (g & 1) ? m : 0, m1 = m ^ m0;
    wg_wait<0>(); pin(dA); pin(dB);
#pragma unroll
    for (int k = 0; k < 12; k++) {
        const int i = 4 * (k >> 1) + (k & 1);
        sts128p((ao ^ ((k & 2) * 72 + (k & 1) * 64)) + 1024 * (k >> 2), o[k][0], o[k][1], pk(dA[i], dA[i + 2]),
                tagged(pk(dB[i], dB[i + 2]), (k & 1) ? m1 : m0, TAGX), k < 8 || q < 3);
    }
}

template <int NB, class F>
__device__ __forceinline__ void p2_step(const uint32_t (&Wf)[48], uint32_t in, uint32_t a0, uint32_t m, uint32_t t, uint32_t bar, int lane, int wg, int s, F meanwhile) {
    float dp[4 * NB], dm[4 * NB];
    const uint32_t lo = ((in & 0x3FFFF) >> 4) | (1u << 16);
    auto desc = [&](int o) { return (uint64_t)(lo + o) | ((uint64_t)(1024 >> 4) << 32) | (1ull << 62); };
    if (NB > 1 && (wg || s > 1)) bar_sync(4 + wg, 256);
    wg_fence();
    wgmma_p2<0>(dp, &Wf[0], desc(0));
    wgmma_p2<0>(dm, &Wf[24], desc(4));
#pragma unroll
    for (int ks = 1; ks < 6; ks++) {
        wgmma_p2<1>(dp, &Wf[4 * ks], desc((ks >> 1) * NB * 64 + (ks & 1) * 2));
        wgmma_p2<1>(dm, &Wf[24 + 4 * ks], desc((ks >> 1) * NB * 64 + (ks & 1) * 2 + 4));
    }
    wg_commit();
    if (NB > 1 && (wg < 2 || s < 6)) asm volatile("bar.arrive %0,256;" ::"r"(wg == 2 ? 4 : 5 + wg) : "memory");
    meanwhile();
    mbar_wait_ph(bar + 8 * (s < 2 ? BD1 + 1 : BDP + 2 * wg + (s & 1)), s >= 2 ? ((s >> 1) & 1) ^ 1 : 0);
    wg_wait<0>();
    pin(dp); pin(dm);
    if (NB > 1 && s < 6 && lane == 0) mbar_arrive(bar + 8 * (BPE + s));
    uint32_t v[2 * NB];
#pragma unroll
    for (int nb = 0; nb < NB; nb++) {
        float pr = dp[4 * nb] - dp[4 * nb + 3], pi = dp[4 * nb + 1] + dp[4 * nb + 2];
        float mr = dm[4 * nb] - dm[4 * nb + 3], mi = dm[4 * nb + 1] + dm[4 * nb + 2];
        v[2 * nb] = tagged(pk(pr + mr, pi - mi), m, t);
        v[2 * nb + 1] = tagged(pk(pi + mi, mr - pr), m, t);
        if (nb & 1)
            asm volatile("stmatrix.sync.aligned.m8n8.x4.trans.shared.b16 [%0],{%1,%2,%3,%4};" ::"r"(a0 + (nb - 1) * 1024), "r"(v[2 * nb - 2]), "r"(v[2 * nb - 1]),
                         "r"(v[2 * nb]), "r"(v[2 * nb + 1]) : "memory");
    }
    if (NB == 1) asm volatile("stmatrix.sync.aligned.m8n8.x2.trans.shared.b16 [%0],{%1,%2};" ::"r"(a0), "r"(v[0]), "r"(v[1]) : "memory");
}

__device__ __forceinline__ bool p3_unit(uint32_t blk, uint32_t cst, uint32_t full, uint32_t ph, int wg, int wq, int lane) {
    int g = lane >> 2, q = lane & 3;
    uint32_t T[12];
#pragma unroll
    for (int v = 0; v < 3; v++) { uint4 x = lds128(cst + C_P3 + (v * 32 + lane) * 16); T[4 * v] = x.x; T[4 * v + 1] = x.y; T[4 * v + 2] = x.z; T[4 * v + 3] = x.w; }
    uint32_t ad[3][2];
#pragma unroll
    for (int nu = 0; nu < 3; nu++) {
        const int pos = lds8(cst + (O_PERM - O_C) + min(4 * nu + (g >> 1), 10));
#pragma unroll
        for (int ka = 0; ka < 2; ka++) {
            int r = 2 * (pos * 11 + (ka ? min(8 + q, 10) : q)) + (g & 1);
            ad[nu][ka] = blk + r * 128 + ((((2 * wq) ^ r) & 7) << 4);
        }
    }
    mbar_wait_ph(full, ph);
    uint32_t o[2][4][4], bad = 0, P[8][3][2];
#pragma unroll
    for (int nu = 0; nu < 3; nu++) {
        uint32_t z[3][2][4];
#pragma unroll
        for (int ka = 0; ka < 3; ka++)
#pragma unroll
            for (int h = 0; h < 2; h++) {
                uint4 x = lds128((ad[nu][ka >> 1] ^ (h << 4)) + (ka & 1) * 1024);
                z[ka][h][0] = x.x; z[ka][h][1] = x.y; z[ka][h][2] = x.z; z[ka][h][3] = x.w;
                if (h) bad |= x.w ^ TAGZ;
            }
#pragma unroll
        for (int ch = 0; ch < 8; ch++) {
            const uint32_t sel = (ch & 1) ? 0x7632 : 0x5410;
            float d[4];
            mma16z(d, T[0], T[1], T[2], T[3], __byte_perm(z[0][0][ch >> 1], z[0][1][ch >> 1], sel), __byte_perm(z[1][0][ch >> 1], z[1][1][ch >> 1], sel));
            mma8(d, T[4], T[5], __byte_perm(z[2][0][ch >> 1], z[2][1][ch >> 1], sel));
            P[ch][nu][0] = pk(d[0], d[1]); P[ch][nu][1] = pk(d[2], d[3]);
        }
    }
    if (bar_any(1 + wg, 128, wq == 3 && (bad & TAGM))) return false;
#pragma unroll
    for (int j = 0; j < 4; j++) {
        float d2[2][2][4];
#pragma unroll
        for (int e = 0; e < 2; e++)
#pragma unroll
            for (int be = 0; be < 2; be++) {
                const int ch = 2 * j + e;
                mma16z(d2[e][be], P[ch][0][0], P[ch][0][1], P[ch][1][0], P[ch][1][1], T[8 + 2 * be], T[9 + 2 * be]);
                mma8(d2[e][be], P[ch][2][0], P[ch][2][1], T[6 + be]);
            }
#pragma unroll
        for (int be = 0; be < 2; be++)
#pragma unroll
            for (int k = 0; k < 4; k++) o[be][k][j] = pk(d2[0][be][k], d2[1][be][k]);
    }
    const int p = 4 * g + q;
    const uint32_t a = blk + p * 64 + ((wq ^ ((p >> 1) & 3)) << 4);
#pragma unroll
    for (int be = 0; be < 2; be++)
#pragma unroll
        for (int k = 0; k < 4; k++)
            sts128(a + (2 * be + (k & 1)) * 4096 + (k >> 1) * 2048, o[be][k][0], o[be][k][1], o[be][k][2], o[be][k][3]);
    return true;
}

template <int Z> __device__ __forceinline__ int s_row(int gr, int st, int cg, int ci, unsigned cm) {
    const int sf = (ci >> 2) & 1, y = 3 * (3 * gr + cg) + ((st ^ sf) << (Z ^ (cm >> 31))), pg = y >> 2;
    const int r = (pg << 14) | ((ci & 1) << 6) | ((ci & 2) << 8) | ((y & 1) << 10) | ((y & 2) << 11);
    return r | ((((Z ? st : sf) ^ ci ^ (ci >> 1) ^ y ^ (y >> 1) ^ (cm >> pg)) & 1) << 5);
}
__device__ __forceinline__ int w_row(int fw, int hg, int cg, int io, unsigned cm) {
    const int home = fw == 5 ? hg >> 1 : fw > 5;
    const int col = fw == 5 ? 15 + (hg & 1) : 3 * (fw > 5 ? fw - 6 : fw) + hg;
    const int z = 9 * col + 3 * cg + io, pg = NPS + (z >> 5);
    const int r = (pg << 12) | ((z & 1) << 4) | ((z & 6) << 6) | ((z & 24) << 7);
    return r | (((home ^ __popc(z & 15) ^ (cm >> pg)) & 1) << 3);
}
__device__ __forceinline__ int s_tile(int t) { return ((t & 3) << 7) | ((t & 4) << 9) | ((t & 8) << 10); }
__device__ __forceinline__ int xoff(int r) { return r < 3 ? O_B0 + r * BLK : (r == 3 ? O_B4 : O_B3); }
__device__ __forceinline__ int soff(int r) { return r == 2 ? O_B2 + 2048 : xoff(r); }
__device__ __forceinline__ int zoff(int r) { return r == 0 ? O_B2 + 2048 : (r == 1 ? O_B3 : (r == 2 ? O_B4 : (r == 3 ? O_Z3 : O_Z4))); }

struct Role1 {
    int sd, k, nu;
    __device__ __forceinline__ Role1(int cta) {
        sd = cta >= NH; k = cta - sd * NH;
        if (k < 60) k = (k >> 1) + ((k & 1) ? 0 : 30);
        nu = k < NUH - 4 * NH ? 5 : 4;
    }
};
struct Role {
    int sd, k, fp, nu;
    __device__ __forceinline__ Role(int rho) {
        sd = rho >= NH;
        const int kk = sd ? NCTA - 1 - rho : rho;
        k = NH - 1 - kk;
        nu = k < NUH - 4 * NH ? 5 : 4;
        fp = k >= 5 + sd ? 60 * sd + k - 5 : -1;
    }
};
__device__ __forceinline__ int stage_row(const Role& R, int s, int lane, unsigned cm, int z) {
    const int ci = R.fp > 0 ? (R.fp - 1) / 15 : 0, rw = 2 * (ci ? R.fp - 15 * ci - 1 : R.fp);
    return (z ? s_row<1>(s, lane & 1, lane >> 1, ci, cm) : s_row<0>(s, lane & 1, lane >> 1, ci, cm)) + rw + (s ? 0 : s_tile(14));
}
__device__ __forceinline__ int stage_off(int s, int lane) { return (lane >> 1) * 8192 + (lane & 1) * (s ? 4096 : 512); }
template <int Z, class RT> __device__ __forceinline__ int unit_row(const RT& R, int r, int lane, unsigned cm) {
    const int u = r * NH + R.k, ts = u / 3;
    return s_row<Z>((ts + 14) >> 4, R.sd, u - 3 * ts, lane, cm) + s_tile(ts + 14);
}
__device__ __forceinline__ int unit_off(int lane) { return lane ? 3840 * lane + 256 : 0; }

__global__ void __launch_bounds__(512, 1) fftconv_kernel(const __grid_constant__ Maps mp) {
    extern __shared__ __align__(1024) unsigned char smraw[];
    const uint32_t sm = s2u(smraw);
    const uint32_t bar = sm + O_BAR;
    const int tid = threadIdx.x, lane = tid & 31;
    const uint32_t tstart = clock();
    if (tid >= 480) {
        if (elect()) {
            const int c = blockIdx.x, ip = c % 12, pr = 3 * (8 * (ip >> 1) + 2 * (ip & 1));
#pragma unroll
            for (int i = 0; i < 8; i++) mbar_init(bar + 8 * i, 1);
            mbar_expect(bar + 8 * BW, 2 * 18816 + WT_BYTES);
            tma_ld3(sm + O_W0, &mp.w, bar + 8 * BW, 0, pr, 0);
            tma_ld3(sm + O_W0 + WPIECE, &mp.w, bar + 8 * BW, 0, pr + 12, 0);
            bulk_ld(sm + O_WT, mp.wtab + (c / 12) * WT_BYTES, WT_BYTES, bar + 8 * BW);
            asm volatile("prefetch.tensormap [%0];" ::"l"(&mp.x22) : "memory");
        }
        __syncwarp();
        asm volatile("bar.arrive 9,64;\n bar.arrive 0,288;" ::: "memory");
    }
    if (tid < 128) {
        const int c = blockIdx.x, vp = min(c & 31, NPAGE - 2);
        const int r0 = 94 + (c & 1) + ((c >> 1) << 7);
        const int r1 = ((vp + 1) << 14) + 94 + ((c >> 5) & 1) + ((c >> 6) << 7) + (vp < NPS - 1 ? 0 : ((0xA151 >> (5 * (vp - NPS + 1))) & 31) << 9);
        unsigned* a = reinterpret_cast<unsigned*>(mp.s) + ((tid & 64 ? r1 : r0) + (tid & 32)) * 32 + lane;
        const bool on = tid < 64 || (c & 31) < NPAGE - 1;
        if (on) *a = 0;
        bar_sync(10, 128);
        unsigned t = 0;
        if (on) asm volatile("{.reg .u32 v; .reg .pred p;\n atom.relaxed.gpu.global.exch.b32 v,[%1],1;\n setp.eq.u32 p,v,0;\n @p mov.u32 %0,%%clock;}" : "+r"(t) : "l"(a) : "memory");
        if (lane == 0) sts32(sm + O_PT + (tid >> 3), t);
        bar_sync(10, 128);
        const uint4 tt = lds128(sm + O_PT);
        const int far = (((int)(tt.x - tt.y) > 0) ^ __popc(r0 & 0x1640)) & 1;
        if (lane == 0 && (tid == 32 || (tid == 64 && on))) {
            const int i = tid == 32 ? 20 + c / 12 : vp, v = tid == 32 ? far : (far ^ ((int)(tt.z - tt.w) > 0) ^ __popc(r1 & 0x1640)) & 1;
            red_add(mp.cnt + 64 * (CV + (i & 7)), 1u << ((i & 24) + 4 * v));
        }
        if (tid == 0) sts32(sm + O_ROLE, far);
        __syncwarp();
        bar_sync(11, 160);
        if (tid == 0) mbar_arrive(bar + 8 * (BRL + 1));
        __syncwarp();
    }
    const int warp = __shfl_sync(0xffffffffu, tid >> 5, 0);
    int cta;
    asm volatile("mov.u32 %0,%%ctaid.x;" : "=r"(cta));
    const int wip = cta % 12;
    const Role1 X(cta);

    if (warp >= 12) {
        asm volatile("setmaxnreg.dec.sync.aligned.u32 32;");
        if (warp & 1) bar_sync(warp, 64);
        uint32_t next = tstart;
        auto pace = [&](int cost) {
            const uint32_t now = until(next, NAP);
            next = ((int)(now - next) > CREDIT ? now - CREDIT : next) + cost;
        };
        if (warp == 12) {
            {
                const int pr = 3 * (8 * (wip >> 1) + 2 * (wip & 1) + 1);
                const int ts = X.k / 3, xc = 32 * (X.k - 3 * ts), tr = ts >= 14, th = 7 * X.sd + tr, w0 = 16 * (ts - 14 * tr);
                const CUtensorMap* xm = th ? &mp.x22 : &mp.x16;
                const uint32_t xd = sm + O_B0 + (th ? 0 : 3072);
                const int xh = th ? 16 * th - 6 : 0;
                bar_sync(9, 64);
                if (elect()) {
                    mbar_expect(bar + 8 * BC, C_BYTES); mbar_expect(bar + 8 * (BW + 1), 2 * 18816); mbar_expect(bar + 8 * BX, BLK);
                    bulk_ld(sm + O_C, mp.ctab, C_BYTES, bar + 8 * BC);
                    until(tstart + XD0, 0);
                    tma_ld3(sm + O_W1, &mp.w, bar + 8 * (BW + 1), 0, pr, 0);
                    tma_ld3(sm + O_W1 + WPIECE, &mp.w, bar + 8 * (BW + 1), 0, pr + 12, 0);
                    tma_ld3(xd + 11264, xm, bar + 8 * BX, xc, w0, xh);
                    until(tstart + XD0 + XE, 0);
                    tma_ld3(xd + 22528, xm, bar + 8 * BX, xc, w0 + 8, xh);
                    until(tstart + XD0 + 2 * XE, 0);
                    tma_ld3(xd, xm, bar + 8 * BX, xc, w0 ? w0 - 8 : 216, xh);
                    if (!th) {
#pragma unroll
                        for (int t = 0; t < 3; t++) tma_ld3(sm + O_B0 + t * 11264, &mp.x6, bar + 8 * BX, xc, t || w0 ? w0 - 8 + 8 * t : 216, 218);
                    }
                }
                __syncwarp();
            }
            const int r = lane / 3 + 1, t = lane - 3 * r + 3;
            const int u = r * NH + X.k, ts = u / 3, tr = ts / 14, tw = ts - 14 * tr;
            const int xc = 32 * (u - 3 * ts), xw = t || tw ? 16 * tw - 8 + 8 * t : 216, xh = 16 * (7 * X.sd + tr) - 6;
            const uint32_t xd = sm + xoff(r) + t * 11264, xb = bar + 8 * (BX + r);
            if (lane && lane < X.nu) mbar_expect(bar + 8 * (BX + lane), BLK);
            bar_sync(12, 64);
            uint32_t due = tstart + XD1;
#pragma unroll 1
            for (int i = 0; i < 3 * X.nu - 3; i++) {
                if (i == 6 || i == 9) mbar_wait(bar + 8 * (i == 6 ? BWC + 1 : BDW));
                until(due, NAP);
                due += XD;
                if (lane == i) tma_ld3(xd, &mp.x22, xb, xc, xw, xh);
                __syncwarp();
            }
        } else if (warp == 13) {
            mbar_wait(bar + 8 * (BRL + 1));
            if (lane == 0) {
                const unsigned far = lds32(sm + O_ROLE), t = atomicAdd(mp.cnt + 64 * (CT + far), 1u);
                sts32(sm + O_ROLE, far ? NCTA - 1 - t : t);
                mbar_arrive(bar + 8 * BRL);
            }
            __syncwarp();
        } else if (warp == 14) {
            unsigned par, ep = 0, vote = 0;
            asm volatile("ld.relaxed.gpu.global.u32 %0,[%1];" : "=r"(par) : "l"(mp.cnt + 64 * (CV + (cta & 7)) + 1) : "memory");
            const int w = lane / 3, hg = lane - 3 * w;
            unsigned char* dst; int wfw;
#pragma unroll 1
            for (int it = 0; it < (1 << 16); it++) {
                const unsigned cm = __ballot_sync(0xffffffffu, lane < 20 && (vote >> 4) > (vote & 15)) << 1;
                const unsigned gm = 0x7ff00000u, lo = __ballot_sync(0xffffffffu, vote < 64) & gm, hi = __ballot_sync(0xffffffffu, vote >= 144) & gm, mid = gm ^ lo ^ hi;
                const unsigned below = (1u << lane) - 1;
                const int pos = vote < 64 ? __popc(lo & below) : (vote < 144 ? __popc(lo) + __popc(mid & below) : 11 - __popc(hi) + __popc(hi & below));
                if (lane >= 20) asm volatile("st.shared.u8 [%0],%1;" ::"r"(sm + O_PERM + lane - 20), "r"(pos) : "memory");
                if (lane == 0) sts32(sm + O_CM, cm | (ep << 31));
                wfw = bcast(pos, 20 + cta / 12);
                dst = mp.s + (size_t)w_row(wfw, hg, w, wip >> 2, cm) * 512 + ((wip & 1) << 15) + ((wip & 2) << 17);
                asm volatile("" : "+l"(dst));
                if (!__any_sync(0xffffffffu, lane < 31 && (vote & 15) + (vote >> 4) < (lane < 4 ? 5u : (lane < 20 ? 4u : 12u)))) break;
                if (it == 0) {
                    ep = par;
                    bar_sync(14, 64);
                    if (lane == 0) { sts32(sm + O_EP, par); mbar_arrive(bar + 8 * BEP); }
                    until(tstart + VT, 0);
                }
                asm volatile("ld.acquire.gpu.global.u8 %0,[%1];" : "=r"(vote) : "l"(reinterpret_cast<unsigned char*>(mp.cnt + 64 * (CV + (lane & 7))) + (lane >> 3)) : "memory");
            }
            __syncwarp();
            if (lane == 0) mbar_arrive(bar + 8 * BCM);
            uint32_t src = sm + O_B3 + w * 11264 + hg * 4096;
#pragma unroll 1
            for (int i = 0; i < 6; i++) {
                mbar_wait(bar + 8 * (BRW + i));
                pace(RW * 11 / 4);
                if (w == (i < 3 ? i : i - 3)) bulk_st(dst, src, hg < 2 ? 4096 : 3072);
                __syncwarp();
                if (i == 2) { dst += 16384; src += O_W0 - O_B3; }
                if (i == 2 || i == 3) bulk_commit();
                if (i == 3) {
                    bulk_wait_read<1>();
                    __syncwarp();
                    if (lane == 0) mbar_arrive(bar + 8 * BDW);
                }
            }
            if (lane == 0) { sts32(sm + O_NEXT, next); mbar_arrive(bar + 8 * (BIS + 1)); red_add(mp.cnt + 64 * (CW + wfw)); }
            bulk_commit(); bulk_wait_read<0>();
            __syncwarp();
            if (lane == 0) mbar_arrive(bar + 8 * (BDW + 1));
        }
        auto role = [&]() { mbar_wait(bar + 8 * BRL); return Role(bcast(lds32(sm + O_ROLE), 0)); };

        if (warp == 12) {
            const Role R = role();
            if (R.fp >= 0) {
                mbar_wait(bar + 8 * BCM);
                const unsigned cm = lds32(sm + O_CM);
                if (lane < 7) mbar_expect(bar + 8 * (BPF + lane), lane ? STG : 3072);
                mbar_wait(bar + 8 * (BIS + 2));
                const int v0 = stage_row(R, lane >> 3, lane & 7, cm, 0), v1 = stage_row(R, 4 + (lane >> 3), lane & 7, cm, 0);
                uint32_t dst = sm + O_S0, seen = 0;
#pragma unroll 1
                for (int s = 0; s < 7; s++) {
                    int row[6];
#pragma unroll
                    for (int i = 0; i < 6; i++) row[i] = bcast(s < 4 ? v0 : v1, 8 * s + i);
                    const CUtensorMap* m = s ? &mp.p16 : &mp.p2;
                    const uint32_t hs = s ? 4096 : 512;
                    for (int it = 0; !(seen >> s & 1) && it < (1 << 16); it++) {
                        unsigned v = 0;
                        if (lane == s || (s >= WIN && lane > s && lane < 7)) asm volatile("ld.acquire.gpu.global.u32 %0,[%1];" : "=r"(v) : "l"(mp.cnt + 64 * (CX + lane)) : "memory");
                        seen = __ballot_sync(0xffffffffu, v >= (lane ? 96u : 12u));
                    }
                    mbar_wait(bar + 8 * (s > 3 ? BPE + s - 3 : (s ? BWE + s - 1 : BD1)));
                    if (elect()) {
#pragma unroll
                        for (int i = 0; i < 6; i++) tma_ld5(dst + i * hs, m, bar + 8 * (BPF + s), 0, row[i], 0, 0, 0);
                    }
                    __syncwarp();
                    dst = dst >= sm + O_IN + 2 * STG ? sm + O_IN : dst + STG;
                }
            }
        } else if (warp == 13) {
            const Role R = role();
            mbar_wait(bar + 8 * BCM);
            if (R.fp >= 0) {
                const unsigned cm = lds32(sm + O_CM);
                if (lane < 3) mbar_expect(bar + 8 * (BWF + lane), STG);
                const int fw = R.fp / 11;
                {
                    const int fh = R.fp - 11 * fw, b = lane / 3, io = lane - 3 * b;
                    const int row = w_row(fw, fh >> 2, b, io, cm) + 2 * (fh & 3);
                    mbar_wait(bar + 8 * (BDW + 1));
                    poll(mp.cnt + 64 * (CW + fw), 12);
                    const uint32_t t0 = clock();
#pragma unroll 1
                    for (int i = 0; i < 9; i++) {
                        if (i == 6) mbar_wait(bar + 8 * BD1);
                        until(t0 + i * LPW, NAP);
                        if (lane == i) tma_ld4(sm + O_IN + lane * 8192, &mp.wf, bar + 8 * (BWF + b), 0, row, 0, 0);
                        __syncwarp();
                    }
                }
                {
                    const int row = stage_row(R, 0, lane & 7, cm, lane < 8);
                    mbar_wait(bar + 8 * BR2); mbar_wait(bar + 8 * (BR2 + 2)); mbar_wait(bar + 8 * (BR2 + 4));
                    if (lane < 6 || (R.fp == 15 && lane < 14 && (lane & 9) == 9)) tma_st5(&mp.p2, sm + O_OUT + stage_off(0, lane & 7), 0, row, 0, 0, 0);
                    __syncwarp();
                    bulk_commit(); bulk_wait_read<0>();
                    __syncwarp();
                    if (lane < 4) mbar_arrive(bar + 8 * (lane < 3 ? BDP + 2 * lane : BI2));
                    if (lane == 0) red_add(mp.cnt + 64 * CY);
                    __syncwarp();
                }
            }
            if (lane < R.nu) mbar_expect(bar + 8 * (BZ + lane), SLAB);
            const int v = unit_row<1>(R, lane >> 1, 4 * (lane & 1), lds32(sm + O_CM));
            mbar_wait(bar + 8 * (BD1 + X.nu - 2)); mbar_wait(bar + 8 * (BD1 + X.nu - 1));
#pragma unroll 1
            for (int r = 0; r < R.nu; r++) {
                const int r0 = bcast(v, 2 * r), r1 = bcast(v, 2 * r + 1), gr = (r * NH + R.k + 42) / 48;
                const uint32_t dst = sm + zoff(r), fb = bar + 8 * (BZ + r);
                if (R.fp >= 0) {
                    if (r >= 3) { mbar_wait(bar + 8 * (r == 3 ? BPE + 4 : BD2)); mbar_wait(bar + 8 * (r == 3 ? BPE + 5 : BD2 + 1)); }
                    mbar_wait(bar + 8 * (BI2 + gr));
                }
                poll(mp.cnt + 64 * (CY + gr), NFP);
                if (elect()) {
#pragma unroll
                    for (int i = 0; i < 8; i++)
                        tma_ld2(dst + unit_off(i), i ? &mp.s30 : &mp.s32, fb, 0, (i < 4 ? r0 : r1) ^ (((i & 1) * 96) ^ ((i & 2) * 272)));
                }
                __syncwarp();
            }
            if (R.fp >= 0) mbar_wait(bar + 8 * (BPF + 6));
            unsigned last = 0;
            if (lane == 0) last = atomicAdd(mp.cnt + 64 * CD, 1u) == NCTA - 1;
            if (__shfl_sync(0xffffffffu, last, 0)) {
                mp.cnt[64 * lane] = 0;
                if (lane < 16) mp.cnt[64 * (CV + (lane >> 1)) + (lane & 1)] = (lane & 1) ? lds32(sm + O_EP) ^ 1 : 0;
            }
        } else {
            const int me = ~warp & 1;
            const int bal = X.nu == 5 ? BAL : (256 * 588 - BAL * 300) / 288;
            mbar_wait(bar + 8 * BCM);
            const unsigned cm = __shfl_sync(0xffffffffu, lds32(sm + O_CM), 0);
            const int vu = unit_row<0>(X, lane >> 1, 4 * (lane & 1), cm);
            const Role R = role();
            const int first = (X.nu ^ me) & 1;
            int v, vx;
            { const int n = first + (lane & 30), s = n / 3, l = 2 * (n - 3 * s) + (lane & 1); v = stage_row(R, s + 1, l, cm, 1); vx = stage_row(R, s + 1, l, cm, 0); }
            asm volatile("" : "+r"(v), "+r"(vx));
#pragma unroll 1
            for (int j = me; j < X.nu; j += 2) {
                const int r0 = bcast(vu, 2 * j), r1 = bcast(vu, 2 * j + 1), cost = ((j < 2 ? R1A : R1) * 121 / 64 * bal) >> 8;
                const uint32_t src = sm + soff(j);
                unsigned* cn = mp.cnt + 64 * (CX + (j * NH + X.k + 42) / 48);
                mbar_wait(bar + 8 * (BR1 + j));
                mbar_wait(bar + 8 * (BIS + 1 + j));
                next = lds32(sm + O_NEXT);
                if (elect()) {
#pragma unroll
                    for (int i = 0; i < 4; i++) {
                        const int x = ((i & 1) * 96) ^ ((i & 2) * 272);
                        pace(cost);
                        tma_st2(i ? &mp.s30 : &mp.s32, src + unit_off(i), 0, r0 ^ x);
                        tma_st2(i || X.sd ? &mp.s30 : &mp.s32, src + unit_off(4 + i), 0, r1 ^ x);
                    }
                    sts32(sm + O_NEXT, next); mbar_arrive(bar + 8 * (BIS + 2 + j));
                    red_add(cn);
                    bulk_commit(); bulk_wait_read<0>();
                    mbar_arrive(bar + 8 * (BD1 + j));
                }
                __syncwarp();
            }
            if (R.fp >= 0) {
                mbar_wait(bar + 8 * (BIS + 1 + X.nu));
                next = lds32(sm + O_NEXT) + first * 2 * R2;
                uint32_t prev = 0;
                int s = 1, w = first;
#pragma unroll 1
                for (int i = 0; i < 18; i += 2) {
                    const int r0 = bcast(v, i), r1 = bcast(v, i + 1), rx = bcast(vx, i + 1);
                    const int bi = 2 * w + (s & 1);
                    const uint32_t src = sm + O_OUT + (s & 1) * STG + w * 8192;
                    mbar_wait_ph(bar + 8 * (BR2 + bi), (s >> 1) & 1);
                    const uint32_t now = until(next, NAP);
                    next = ((int)(now - next) > CREDIT2 ? now - CREDIT2 : next) + 4 * R2;
                    if (elect()) {
                        tma_st5(&mp.p16, src, 0, r0, 0, 0, 0);
                        tma_st5(&mp.p16, src + 4096, 0, r1, 0, 0, 0);
                        if (R.fp == 15) tma_st5(&mp.p16, src + 4096, 0, rx, 0, 0, 0);
                        bulk_commit();
                        bulk_wait_read<1>();
                        if (prev) mbar_arrive(prev);
                        if (w == 2) { until(now + LATE2, 0); red_add(mp.cnt + 64 * (CY + s)); mbar_arrive(bar + 8 * (BI2 + s)); }
                    }
                    __syncwarp();
                    prev = bar + 8 * (BDP + bi);
                    w += 2; if (w > 2) { w -= 3; s++; }
                }
                if (elect()) { bulk_wait_read<0>(); mbar_arrive(bar + 8 * (BD2 + me)); }
                __syncwarp();
                next = clock() + YD;
            }
#pragma unroll 1
            for (int r = me; r < 3; r += 2) {
                const int u = r * NH + R.k, ts = u / 3, cg = u - 3 * ts, tr = ts / 14, th = 7 * R.sd + tr, tw = ts - 14 * tr;
                mbar_wait(bar + 8 * (BR3 + r));
                if (r) { mbar_wait(bar + 8 * (BIS + 6 + r)); next = lds32(sm + O_NEXT); }
#pragma unroll 1
                for (int c = 0; c < 2; c++) {
                    pace(2 * R3);
                    if (elect()) tma_st4(&mp.y, sm + zoff(r) + c * 8192, 32 * cg, 0, 16 * th, 4 * tw + 2 * c);
                    __syncwarp();
                }
                if (lane == 0 && r < 2) { sts32(sm + O_NEXT, next); mbar_arrive(bar + 8 * (BIS + 7 + r)); }
                __syncwarp();
            }
            bulk_commit(); bulk_wait_read<0>();
        }
    } else {
        if (warp >= 4) {
            if (elect()) {
                const int gi = warp - 3;
#pragma unroll
                for (int i = 0; i < 8; i++) mbar_init(bar + 64 * gi + 8 * i, gi < 8 ? 1 : 12);
                if (gi < 5) {
#pragma unroll
                    for (int i = 0; i < 8; i++) mbar_init(bar + 64 * (gi + 8) + 8 * i, 4);
                }
            }
            __syncwarp();
            bar_sync(0, 288);
            if (warp < 9) asm volatile("bar.arrive %0,%1;" ::"r"(warp + 7), "r"(warp == 4 ? 160 : 64) : "memory");
            else if (warp == 10 && lane < 8) asm volatile("prefetch.tensormap [%0];" ::"l"(&mp.x6 + lane) : "memory");
            __syncwarp();
        }
        asm volatile("setmaxnreg.inc.sync.aligned.u32 160;");
        const int lane = laneid();
        const int wg = __shfl_sync(0xffffffffu, tid >> 7, 0), wq = __shfl_sync(0xffffffffu, tid >> 5, 0) & 3;
        const int pw = wg ? wg - 1 : 2;
#pragma unroll 1
        for (int it = 0; it <= pw; it++) {
            const int j = it > 0, cg = j ? pw + it - 2 : pw;
            mbar_wait(bar + 8 * (j == 0 && pw ? BWL + pw - 1 : BW + j));
            wgen(sm + (j ? O_W1 : O_W0), sm + O_WT, sm + (j ? O_W0 : O_B3) + cg * 11264, 4 * cg + wq, (2 * wip + j) & 3, lane, bar + 8 * (BWC + j),
                 j == 0 && pw < 2 ? bar + 8 * (BWL + pw) : 0, bar + 8 * (j ? BWC : BEP), sm + O_EP);
            staged(bar + 8 * (BRW + 3 * j + cg), lane);
        }
        mbar_wait(bar + 8 * BC); mbar_wait(bar + 8 * BCM);
#pragma unroll 1
        for (int r = pw; r < X.nu; r += 3) {
            p1_unit(sm + xoff(r), sm + soff(r), sm + O_C, bar + 8 * (BX + r), wg, wq, laneid());
            staged(bar + 8 * (BR1 + r), laneid());
        }
        mbar_wait(bar + 8 * BRL);
        const Role R(__shfl_sync(0xffffffffu, lds32(sm + O_ROLE), 0));
        uint32_t phw = 0;
        if (R.fp >= 0) {
            const int lane = laneid();
            uint32_t Wf[48];
            const int g = lane >> 2, q = lane & 3;
            {
                const int b = wg;
                const uint32_t p = sm + O_IN + b * STG + q * 1024 + wq * 128 + ((g ^ (2 * q) ^ (4 * ((R.fp % 11) & 1))) << 4);
                mbar_wait(bar + 8 * (BWF + b));
#pragma unroll 1
                for (int it = 0; it < 4096; it++) {
                    const uint32_t tag = ~lds32(sm + O_CM) >> 31, m = g == 7;
                    uint32_t bad = 0;
#pragma unroll
                    for (int i = 0; i < 12; i++) {
                        uint4 v = lds128((p ^ (i >= 6 ? 544 : 0)) + (i % 6) * 4096);
                        Wf[4 * i] = v.x; Wf[4 * i + 1] = v.y; Wf[4 * i + 2] = v.z; Wf[4 * i + 3] = v.w & ~m;
                        bad |= v.w ^ tag;
                    }
                    if (!bar_any(1 + wg, 128, bad & m)) break;
                    if (wq == 0) {
                        fence_async_s();
                        if (lane == 0) mbar_expect(bar + 8 * (BRT + 1 + wg), STG);
                        __syncwarp();
                        const int l = laneid(), fp = Role(lds32(sm + O_ROLE)).fp, fw = fp / 11, fh = fp - 11 * fw;
                        if (l < 3) tma_ld4(sm + O_IN + b * STG + l * 8192, &mp.wf, bar + 8 * (BRT + 1 + wg), 0, w_row(fw, fh >> 2, wg, l, lds32(sm + O_CM)) + 2 * (fh & 3), 0, 0);
                        __syncwarp();
                    }
                    mbar_wait_ph(bar + 8 * (BRT + 1 + wg), phw); phw ^= 1;
                }
                staged(bar + 8 * (BWE + b), lane);
            }
            const int ro = (lane & 6) + ((lane >> 3) & 1);
            const uint32_t o0 = sm + O_OUT + wg * 8192 + (lane >> 4) * 1024 + ro * 128 + (((2 * wq + (lane & 1)) ^ ro) << 4);
            const uint32_t m = wq == 3 && g >= 6 ? 0x10000 : 0, tg = g == 6 ? TAGZ << 16 : TAGZ;
            uint32_t ph = 0;
            const int t = 32 * wq + lane;
            uint32_t c0 = t * 128 + ((7 ^ (t & 7)) << 4) + 12, c1 = (c0 & 8191) + 16384;
            auto stale = [&](uint32_t in) { return (((lds32(in + c0) ^ TAGX) | (lds32(in + c1) ^ TAGX)) & TAGM) != 0; };
            auto landed = [&](int s, uint32_t in) {
                mbar_wait(bar + 8 * (BPF + s));
#pragma unroll 1
                for (int it = 0; it < 4096; it++) {
                    if (!bar_any(1 + wg, 128, stale(in))) break;
                    fence_async_s();
                    bar_sync(7, 384);
                    if (wg + wq == 0) {
                        if (lane == 0) mbar_expect(bar + 8 * BRT, s ? STG : 3072);
                        __syncwarp();
                        const int l = laneid();
                        if (l < 6) tma_ld5(in + l * (s ? 4096 : 512), s ? &mp.p16 : &mp.p2, bar + 8 * BRT, 0, stage_row(Role(lds32(sm + O_ROLE)), s, l, lds32(sm + O_CM), 0), 0, 0, 0);
                        __syncwarp();
                    }
                    mbar_wait_ph(bar + 8 * BRT, ph); ph ^= 1;
                }
            };
            mbar_wait(bar + 8 * BD1);
            c0 &= 2047; c1 = (c1 & 1023) + 2048;
            landed(0, sm + O_S0);
            p2_step<1>(Wf, sm + O_S0, o0, m, tg, bar, lane, wg, 0, []() {});
            staged(bar + 8 * (BR2 + 2 * wg), lane);
            c0 |= t << 7; c1 = (c0 & 8191) + 16384;
            uint32_t in = sm + O_IN;
            bool todo = true;
#pragma unroll 1
            for (int s = 1; s < 7; s++) {
                if (todo) landed(s, in);
                const uint32_t nx = in == sm + O_IN + 2 * STG ? sm + O_IN : in + STG;
                p2_step<8>(Wf, in, o0 + (s & 1) * STG, m, tg, bar, lane, wg, s, [&]() { todo = !mbar_test(bar + 8 * (BPF + s + 1)) || stale(nx); });
                todo = bar_any(1 + wg, 128, todo);
                in = nx;
                staged(bar + 8 * (BR2 + 2 * wg + (s & 1)), lane);
            }
        }
#pragma unroll 1
        for (int r = wg; r < R.nu; r += 3) {
            const int yu = r * NH + R.k, yt = yu / 3, yr = yt / 14, yc = 32 * (yu - 3 * yt), yh = 16 * (7 * R.sd + yr), yw = 4 * (yt - 14 * yr);
#pragma unroll 1
            for (int it = 0; it < 4096; it++) {
                if (p3_unit(sm + zoff(r), sm + O_C, bar + 8 * (it ? BRT + 1 + wg : BZ + r), it ? phw ^ 1 : 0, wg, wq, laneid())) break;
                if (wq == 0) {
                    fence_async_s();
                    if (laneid() == 0) mbar_expect(bar + 8 * (BRT + 1 + wg), SLAB);
                    __syncwarp();
                    const int l = laneid();
                    if (l < 8) tma_ld2(sm + zoff(r) + unit_off(l), l ? &mp.s30 : &mp.s32, bar + 8 * (BRT + 1 + wg), 0, unit_row<1>(Role(lds32(sm + O_ROLE)), r, l, lds32(sm + O_CM)));
                    __syncwarp();
                }
                phw ^= 1;
            }
            if (r < 3) staged(bar + 8 * (BR3 + r), laneid());
            else {
                fence_async_s();
                bar_sync(1 + wg, 128);
                if (wq < 2 && elect()) {
                    tma_st4(&mp.y, sm + zoff(r) + wq * 8192, yc, 0, yh, yw + 2 * wq);
                    bulk_commit(); bulk_wait_read<0>();
                }
                __syncwarp();
            }
        }
    }
}

__global__ void direct_kernel(const __nv_bfloat16* __restrict__ x, const __nv_bfloat16* __restrict__ w, __nv_bfloat16* __restrict__ y) {
    __shared__ float xs[49 * 96];
    const int h = blockIdx.x / 224, p = blockIdx.x % 224, o = threadIdx.x;
    for (int t = 0; t < 49; t++) xs[t * 96 + o] = __bfloat162float(x[(((h + 224 - t / 7) % 224) * 224 + (p + 224 - t % 7) % 224) * 96 + o]);
    __syncthreads();
    float a = 0.f;
    for (int k = 0; k < 49 * 96; k++) a += xs[k] * __bfloat162float(w[k * 96 + o]);
    y[blockIdx.x * 96 + o] = __float2bfloat16(a);
}

typedef CUresult (*EncFn)(CUtensorMap*, CUtensorMapDataType, cuuint32_t, void*, const cuuint64_t*, const cuuint64_t*, const cuuint32_t*,
                          const cuuint32_t*, CUtensorMapInterleave, CUtensorMapSwizzle, CUtensorMapL2promotion, CUtensorMapFloatOOBfill);

void enc(EncFn f, CUtensorMap* m, void* p, int rank, const cuuint64_t* dims, const cuuint64_t* strides, const cuuint32_t* box,
         CUtensorMapSwizzle sw, CUtensorMapL2promotion pr = CU_TENSOR_MAP_L2_PROMOTION_NONE) {
    cuuint32_t es[5] = {1, 1, 1, 1, 1};
    f(m, CU_TENSOR_MAP_DATA_TYPE_BFLOAT16, rank, p, dims, strides, box, es, CU_TENSOR_MAP_INTERLEAVE_NONE, sw, pr, CU_TENSOR_MAP_FLOAT_OOB_FILL_NONE);
}

}

extern "C" void kernel_launch(void* const* d_in, const int* in_sizes, int n_in, void* d_out, int out_size) {
    void* fn = nullptr; cudaDriverEntryPointQueryResult qr;
    cudaGetDriverEntryPoint("cuTensorMapEncodeTiled", &fn, cudaEnableDefault, &qr);
    EncFn f = (EncFn)fn;
    int dev = 0, sms = 0;
    cudaGetDevice(&dev);
    cudaDeviceGetAttribute(&sms, cudaDevAttrMultiProcessorCount, dev);
    if (sms < NCTA || !f || cudaFuncSetAttribute(fftconv_kernel, cudaFuncAttributeMaxDynamicSharedMemorySize, SMEM) != cudaSuccess) {
        direct_kernel<<<224 * 224, 96>>>((const __nv_bfloat16*)d_in[0], (const __nv_bfloat16*)d_in[1], (__nv_bfloat16*)d_out);
        return;
    }
    void* pS; cudaGetSymbolAddress(&pS, g_S);
    pS = (void*)(((uintptr_t)pS + (1u << 21) - 1) & ~(uintptr_t)((1u << 21) - 1));
    Maps mp;
    cudaGetSymbolAddress((void**)&mp.ctab, g_ctab); cudaGetSymbolAddress((void**)&mp.wtab, g_wtab); cudaGetSymbolAddress((void**)&mp.cnt, g_cnt);
    mp.s = (unsigned char*)pS;
    { cuuint64_t d[4] = {256, NPAGE << 12, 4, 2}, s[3] = {512, 1 << 14, 1 << 18}; cuuint32_t b[4] = {256, 2, 4, 2}; enc(f, &mp.wf, pS, 4, d, s, b, CU_TENSOR_MAP_SWIZZLE_NONE); }
    {
        cuuint64_t d[3] = {96, 224, 224}, s[2] = {192, 43008};
        cuuint32_t b6[3] = {32, 8, 6}, b16[3] = {32, 8, 16}, b22[3] = {32, 8, 22};
        enc(f, &mp.x22, d_in[0], 3, d, s, b22, CU_TENSOR_MAP_SWIZZLE_64B, CU_TENSOR_MAP_L2_PROMOTION_L2_128B);
        enc(f, &mp.x6, d_in[0], 3, d, s, b6, CU_TENSOR_MAP_SWIZZLE_64B, CU_TENSOR_MAP_L2_PROMOTION_L2_128B);
        enc(f, &mp.x16, d_in[0], 3, d, s, b16, CU_TENSOR_MAP_SWIZZLE_64B, CU_TENSOR_MAP_L2_PROMOTION_L2_128B);
    }
    { cuuint64_t d[4] = {96, 4, 224, 56}, s[3] = {192, 43008, 768}; cuuint32_t b[4] = {32, 4, 16, 2}; enc(f, &mp.y, d_out, 4, d, s, b, CU_TENSOR_MAP_SWIZZLE_64B); }
    {
        cuuint64_t d[2] = {64, NPAGE << 14}, s[1] = {128};
        cuuint32_t b32[2] = {64, 32}, b30[2] = {64, 30};
        enc(f, &mp.s32, pS, 2, d, s, b32, CU_TENSOR_MAP_SWIZZLE_128B);
        enc(f, &mp.s30, pS, 2, d, s, b30, CU_TENSOR_MAP_SWIZZLE_128B);
    }
    {
        cuuint64_t d[5] = {64, NPAGE << 14, 4, 2, 2}, s[4] = {128, 1 << 14, 1 << 18, 1 << 20};
        cuuint32_t b16[5] = {64, 2, 4, 2, 2}, b2[5] = {64, 2, 2, 1, 1};
        enc(f, &mp.p16, pS, 5, d, s, b16, CU_TENSOR_MAP_SWIZZLE_128B);
        enc(f, &mp.p2, pS, 5, d, s, b2, CU_TENSOR_MAP_SWIZZLE_128B);
    }
    { cuuint64_t d[3] = {64, 144, 49}, s[2] = {128, 18432}; cuuint32_t b[3] = {64, 3, 49}; enc(f, &mp.w, d_in[1], 3, d, s, b, CU_TENSOR_MAP_SWIZZLE_128B); }
    fftconv_kernel<<<NCTA, 512, SMEM>>>(mp);
}
```
